```python
import torch

def _softmax(x, axis=-1):
    return torch.softmax(x, dim=axis)
def _gelu(x):
    return torch.nn.functional.gelu(x, approximate="tanh")
def _silu(x):
    return torch.nn.functional.silu(x)
def _sigmoid(x):
    return torch.sigmoid(x)
def _layernorm(x, axis=-1, eps=1e-5):
    m = x.mean(dim=axis, keepdim=True)
    v = x.var(dim=axis, keepdim=True, unbiased=False)
    return (x - m) / torch.sqrt(v + eps)
def _scatter_add(tgt, idx, src, axis=0):
    return tgt.clone().index_add_(axis, idx, src)
def _segment_sum(src, seg, n):
    out = torch.zeros((n,) + src.shape[1:], dtype=src.dtype)
    return out.index_add_(0, seg, src)
def _pad(x, pw):
    flat = tuple(v for pair in reversed(pw) for v in pair)
    return torch.nn.functional.pad(x, flat)

kernel_name = 'sequential_preLN__mha_block_cached__moe_arch_mod__decode'

def setup_inputs():

    _w = (lambda a: (lambda t: t.to(torch.bfloat16) if t.is_floating_point() else t)(torch.as_tensor(a)))
    def _A_setup():
        B, Sq, D = 4, 1, 640
        H, Sk, Dh = 32, 8192, 192
        return {
            "x": _w((lambda *s: torch.randn(*s, dtype=torch.bfloat16) * 0.05)(B, Sq, D)),
            "k_cache": _w((lambda *s: torch.randn(*s, dtype=torch.bfloat16) * 3.2)(B, H, Sk, Dh)),
            "v_cache": _w((lambda *s: torch.randn(*s, dtype=torch.bfloat16) * 0.4)(B, H, Sk, Dh)),
            "wq": _w((lambda *s: torch.randn(*s, dtype=torch.bfloat16) * 3.2)(D, H * Dh) * (D ** -0.5)),
            "wo": _w((lambda *s: torch.randn(*s, dtype=torch.bfloat16) * 0.4)(H * Dh, D) * ((H * Dh) ** -0.5)),
        }
    _A_in = _A_setup()

    def _B_setup():
        B, S, D, F, C = 4, 1, 640, 1536, 1
        return {
            "x": _w((lambda *s: torch.randn(*s, dtype=torch.bfloat16) * 0.05)(B, S, D)),
            "w_r": _w((lambda *s: torch.randn(*s, dtype=torch.bfloat16) * 0.05)(D)),
            "w_gate": _w((lambda *s: torch.randn(*s, dtype=torch.bfloat16) * 0.05)(D, F)),
            "w_up": _w((lambda *s: torch.randn(*s, dtype=torch.bfloat16) * 0.05)(D, F)),
            "w_down": _w((lambda *s: torch.randn(*s, dtype=torch.bfloat16) * 0.05)(F, D)),
        }
    _B_in = _B_setup()

    return {
        "A_x": _A_in["x"],
        "A_k_cache": _A_in["k_cache"],
        "A_v_cache": _A_in["v_cache"],
        "A_wq": _A_in["wq"],
        "A_wo": _A_in["wo"],
        "B_x": _B_in["x"],
        "B_w_r": _B_in["w_r"],
        "B_w_gate": _B_in["w_gate"],
        "B_w_up": _B_in["w_up"],
        "B_w_down": _B_in["w_down"],
    }

def reference(A_x, A_k_cache, A_v_cache, A_wq, A_wo, B_x, B_w_r, B_w_gate, B_w_up, B_w_down):
    def _A_ref(x, k_cache, v_cache, wq, wo):
        B, Sq, D = x.shape
        H, Dh = 32, 192
        q = (lambda x, *d: x.permute(*d))((x @ wq).reshape(B, Sq, H, Dh), 0, 2, 1, 3)
        scores = torch.einsum("bhqd,bhkd->bhqk", q, k_cache) * (Dh ** -0.5)
        p = _softmax(scores, axis=-1)
        o = torch.einsum("bhqk,bhkd->bhqd", p, v_cache)
        return (lambda x, *d: x.permute(*d))(o, 0, 2, 1, 3).reshape(B, Sq, H * Dh) @ wo

    def _B_ref(x, w_r, w_gate, w_up, w_down):
        B, S, D = x.shape
        C = 1
        r = x @ w_r
        idx = torch.argsort(-r, axis=-1)[:, :C]
        idx_e = (lambda x, n, axis: torch.repeat_interleave(x, n, dim=axis))(idx.reshape(B, C, 1), D, axis=2)
        x_sel = (lambda x, i, axis: torch.take_along_dim(x, i, dim=axis))(x, idx_e, axis=1)
        g = _silu(x_sel @ w_gate)
        u = x_sel @ w_up
        y = (g * u) @ w_down
        r_sel = _sigmoid((lambda x, i, axis: torch.take_along_dim(x, i, dim=axis))(r, idx, axis=1))
        y = y * r_sel.reshape(B, C, 1)
        b_off = (torch.arange(B) * S).reshape(B, 1)
        flat_idx = (idx + b_off).reshape(B * C)
        zero = (x * 0.0).reshape(B * S, D)
        upd = _scatter_add(zero, flat_idx, y.reshape(B * C, D), axis=0)
        return x + upd.reshape(B, S, D)

    x = A_x
    h = x + _A_ref(_layernorm(x, axis=-1), A_k_cache, A_v_cache, A_wq, A_wo)
    h2 = h + _B_ref(_layernorm(h, axis=-1), B_w_r, B_w_gate, B_w_up, B_w_down)
    return h2
```

```cpp
#include <cuda_runtime.h>
#include <cuda_bf16.h>
#include <cuda.h>
#include <stdint.h>

namespace {

constexpr int NB = 4, NH = 32, SK = 8192, DH = 192, DM = 640, FF = 1536;
constexpr int NBH = NB * NH;
constexpr int TILE = 64;
constexpr int UPB = SK / TILE;
constexpr int NUNITS = NBH * UPB;
constexpr int TILE_BYTES = TILE * DH * 2;
constexpr int TILE_ROWS = TILE * 3;
constexpr int NCTAS = 132;
constexpr int NQ_CTAS = 128;
constexpr int NE_CTAS = 112;
constexpr int NF_CTAS = 96;
constexpr int NG_CTAS = 40;

#define NWORK 2
#define LAG 2
#define NPOOL 640
#define RED0 116
#define RING 12
#define OREP 2
#define HREP 2
#define AREP 2
#define K0_DELAY_NS 1000
#define WO_AT_NS 3800
#define FW_TICKET 400
#define FW_AT_NS 3840
#define FW_GAP 400
#define FW_GAP2 200
#define FW_MID 0
constexpr int NAUX = 8;
constexpr int NTHREADS = (NAUX + NWORK + 2) * 32;
constexpr int SPIN_MAX = 1 << 22;

constexpr int SM_KV = 0;
constexpr int SM_A = SM_KV + NWORK * TILE_BYTES;
constexpr int SM_G = SM_A + 61440;
constexpr int SM_D = SM_G + 40960;
constexpr int SM_WQ = SM_G;
constexpr int SM_X = SM_D + 49152;
constexpr int XPITCH = 648;
constexpr int HPITCH = 1312;
constexpr int SM_RED = SM_X + 5 * HPITCH + 96;
constexpr int SM_RED2 = SM_RED + 8 * 48 * 4 * 4;
constexpr int SM_MISC = SM_RED2 + 4096;
constexpr int BAR_WQ = SM_MISC + 32, BAR_WO = SM_MISC + 40, BAR_GU = SM_MISC + 64, BAR_WD = SM_MISC + 128;
constexpr int SM_TOTAL = SM_MISC + 192;
static_assert(NB * XPITCH * 2 <= 4 * HPITCH && SM_RED % 128 == 0, "smem layout");

struct Params {
    CUtensorMap k, v;
    CUtensorMap wq;
    CUtensorMap wo;
    CUtensorMap wg, wu;
    CUtensorMap wd;
    const __nv_bfloat16 *x, *wr;
    __nv_bfloat16* out;
};

struct Early {
    uint32_t q[96];
    uint32_t umax[UPB];
};
constexpr int NACC = NBH + 4 * (OREP - 1);
#define LSTRIDE 16
struct State {
    float4 oacc[NACC][64];
    float2 attn[NB][DM];
    uint32_t hx[NB][HREP][DM / 2];
    uint32_t ax[2][AREP][NB * FF / 2];
    uint32_t fw_time[32];
    float2 lsum[NACC][LSTRIDE];
    uint32_t score[NPOOL][32];
};
constexpr int STATE_V4 = ((sizeof(State) / 32 + NQ_CTAS - 1) / NQ_CTAS) * 2;
static_assert(sizeof(State) % 32 == 0, "State is cleared in whole sectors");
static_assert(sizeof(Early) == 56 * 16, "an Early entry is cleared by 56 threads");
struct Scratch {
    unsigned work[64];
    unsigned cnt_z[32];
    Early early[NBH];
    State st;
    float4 ring[RING][UPB][64];
};
constexpr size_t PAGE = 2u << 20;
static_assert(sizeof(Scratch) <= PAGE, "scratch must fit one page");
__device__ __align__(128) unsigned char g_raw[2 * PAGE];
__device__ __forceinline__ Scratch* scratch() {
    return reinterpret_cast<Scratch*>((reinterpret_cast<uintptr_t>(g_raw) + PAGE - 1) & ~(uintptr_t)(PAGE - 1));
}
#define g_early scratch()->early
#define g_st scratch()->st
#define g_ring scratch()->ring
#define g_cnt_z scratch()->cnt_z
#define g_work scratch()->work
#define TS(i)
#define TSW(i)
#define TS2(i)
#define TSI(n, i)
#define PH(i)
#define CK(i, dep)
#define ARR()
#define PROG(u)

__device__ __forceinline__ uint32_t s2u(const void* p) { return (uint32_t)__cvta_generic_to_shared(p); }
__device__ __forceinline__ void mbar_init(uint32_t bar, int cnt) {
    asm volatile("mbarrier.init.shared::cta.b64 [%0], %1;" :: "r"(bar), "r"(cnt) : "memory");
}
__device__ __forceinline__ void mbar_expect_tx(uint32_t bar, uint32_t bytes) {
    asm volatile("mbarrier.arrive.expect_tx.shared::cta.b64 _, [%0], %1;" :: "r"(bar), "r"(bytes) : "memory");
}
__device__ __forceinline__ void mbar_wait(uint32_t bar, uint32_t parity) {
    asm volatile("{\n.reg .pred p;\n.reg .u32 n;\nmov.u32 n, 0;\nWAIT_LOOP:\n"
                 "mbarrier.try_wait.parity.shared::cta.b64 p, [%0], %1;\n"
                 "@p bra WAIT_DONE;\nadd.u32 n, n, 1;\nsetp.lt.u32 p, n, %2;\n@p bra WAIT_LOOP;\nWAIT_DONE:\n}"
                 :: "r"(bar), "r"(parity), "n"(SPIN_MAX) : "memory");
}
__device__ __forceinline__ void tma_tile(uint32_t dst, const CUtensorMap* tm, int row, uint32_t bar, uint64_t pol) {
    asm volatile("cp.async.bulk.tensor.2d.shared::cluster.global.mbarrier::complete_tx::bytes.L2::cache_hint "
                 "[%0], [%1, {%3, %4}], [%2], %5;"
                 :: "r"(dst), "l"(tm), "r"(bar), "r"(0), "r"(row), "l"(pol) : "memory");
}
__device__ __forceinline__ void request_tile(uint32_t dst, const CUtensorMap* tm, int unit, uint32_t bar, uint64_t pol) {
    asm volatile("{\n.reg .pred p;\nelect.sync _|p, 0xffffffff;\n"
                 "@p mbarrier.arrive.expect_tx.shared::cta.b64 _, [%2], %6;\n"
                 "@p cp.async.bulk.tensor.2d.shared::cluster.global.mbarrier::complete_tx::bytes.L2::cache_hint "
                 "[%0], [%1, {%3, %4}], [%2], %5;\n}"
                 :: "r"(dst), "l"(tm), "r"(bar), "r"(0), "r"(unit * TILE_ROWS), "l"(pol), "n"(TILE_BYTES) : "memory");
}
__device__ __forceinline__ void tma_box(uint32_t dst, const CUtensorMap* tm, int col, int row, uint32_t bar) {
    asm volatile("cp.async.bulk.tensor.2d.shared::cluster.global.mbarrier::complete_tx::bytes [%0], [%1, {%3, %4}], [%2];"
                 :: "r"(dst), "l"(tm), "r"(bar), "r"(col), "r"(row) : "memory");
}
__device__ __forceinline__ uint32_t lds32(uint32_t addr) {
    uint32_t v;
    asm volatile("ld.shared.u32 %0, [%1];" : "=r"(v) : "r"(addr) : "memory");
    return v;
}
__device__ __forceinline__ void ldsm4(uint32_t (&r)[4], uint32_t addr) {
    asm volatile("ldmatrix.sync.aligned.m8n8.x4.shared.b16 {%0,%1,%2,%3}, [%4];"
                 : "=r"(r[0]), "=r"(r[1]), "=r"(r[2]), "=r"(r[3]) : "r"(addr) : "memory");
}
__device__ __forceinline__ void ldsm4t(uint32_t (&r)[4], uint32_t addr) {
    asm volatile("ldmatrix.sync.aligned.m8n8.x4.trans.shared.b16 {%0,%1,%2,%3}, [%4];"
                 : "=r"(r[0]), "=r"(r[1]), "=r"(r[2]), "=r"(r[3]) : "r"(addr) : "memory");
}
__device__ __forceinline__ void mma16816(float (&c)[4], const uint32_t (&a)[4], uint32_t b0, uint32_t b1) {
    asm volatile("mma.sync.aligned.m16n8k16.row.col.f32.bf16.bf16.f32 {%0,%1,%2,%3}, {%4,%5,%6,%7}, {%8,%9}, {%0,%1,%2,%3};"
                 : "+f"(c[0]), "+f"(c[1]), "+f"(c[2]), "+f"(c[3])
                 : "r"(a[0]), "r"(a[1]), "r"(a[2]), "r"(a[3]), "r"(b0), "r"(b1));
}
__device__ __forceinline__ uint4 ld_relaxed_v4(const void* p) {
    uint4 v;
    asm volatile("ld.relaxed.gpu.global.v4.u32 {%0,%1,%2,%3}, [%4];" : "=r"(v.x), "=r"(v.y), "=r"(v.z), "=r"(v.w) : "l"(p) : "memory");
    return v;
}
__device__ __forceinline__ float4 ld_relaxed_f4(const void* p) {
    float4 v;
    asm volatile("ld.relaxed.gpu.global.v4.f32 {%0,%1,%2,%3}, [%4];" : "=f"(v.x), "=f"(v.y), "=f"(v.z), "=f"(v.w) : "l"(p) : "memory");
    return v;
}
__device__ __forceinline__ float2 ld_relaxed_f2(const void* p) {
    float2 v;
    asm volatile("ld.relaxed.gpu.global.v2.f32 {%0,%1}, [%2];" : "=f"(v.x), "=f"(v.y) : "l"(p) : "memory");
    return v;
}
__device__ __forceinline__ float4 ld_relaxed_b128(const void* p) {
    float4 v;
    asm volatile("{\n.reg .b128 t;\n.reg .b64 a, b;\nld.relaxed.gpu.global.b128 t, [%4];\nmov.b128 {a, b}, t;\n"
                 "mov.b64 {%0, %1}, a;\nmov.b64 {%2, %3}, b;\n}" : "=f"(v.x), "=f"(v.y), "=f"(v.z), "=f"(v.w) : "l"(p) : "memory");
    return v;
}
__device__ __forceinline__ void st_relaxed_b128(void* p, float x, float y, float z, float w) {
    asm volatile("{\n.reg .b128 t;\n.reg .b64 a, b;\nmov.b64 a, {%1, %2};\nmov.b64 b, {%3, %4};\nmov.b128 t, {a, b};\n"
                 "st.relaxed.gpu.global.b128 [%0], t;\n}" :: "l"(p), "f"(x), "f"(y), "f"(z), "f"(w) : "memory");
}
__device__ __forceinline__ unsigned ld_acquire(const unsigned* p) {
    unsigned v;
    asm volatile("ld.acquire.gpu.global.u32 %0, [%1];" : "=r"(v) : "l"(p) : "memory");
    return v;
}
__device__ __forceinline__ void st_relaxed(void* p, uint32_t v) {
    asm volatile("st.relaxed.gpu.global.u32 [%0], %1;" :: "l"(p), "r"(v) : "memory");
}
__device__ __forceinline__ void red_f2(float* p, float a, float b) {
    asm volatile("red.relaxed.gpu.global.add.v2.f32 [%0], {%1,%2};" :: "l"(p), "f"(a), "f"(b) : "memory");
}
__device__ __forceinline__ void red_f4(float* p, float a, float b, float c, float d) {
    asm volatile("red.relaxed.gpu.global.add.v4.f32 [%0], {%1,%2,%3,%4};" :: "l"(p), "f"(a), "f"(b), "f"(c), "f"(d) : "memory");
}
__device__ __forceinline__ void draw(int& ticket, unsigned* ctr, bool pred) {
    asm volatile("{\n.reg .pred p;\nsetp.ne.u32 p, %2, 0;\n@p atom.relaxed.gpu.global.inc.u32 %0, [%1], 0x7fffffff;\n}"
                 : "+r"(ticket) : "l"(ctr), "r"((uint32_t)pred) : "memory");
}
__device__ __forceinline__ void red_release(unsigned* p) {
    asm volatile("red.release.gpu.global.add.u32 [%0], 1;" :: "l"(p) : "memory");
}
__device__ __forceinline__ uint32_t ld_relaxed_u32(const void* p) {
    uint32_t v;
    asm volatile("ld.relaxed.gpu.global.u32 %0, [%1];" : "=r"(v) : "l"(p) : "memory");
    return v;
}
__device__ __forceinline__ float rcp_approx(float v) {
    float r;
    asm("rcp.approx.ftz.f32 %0, %1;" : "=f"(r) : "f"(v));
    return r;
}
__device__ __forceinline__ float sigmoid_approx(float v) {
    float e;
    asm("ex2.approx.ftz.f32 %0, %1;" : "=f"(e) : "f"(v * -1.4426950408889634f));
    return rcp_approx(1.0f + e);
}
__device__ __forceinline__ float sqrt_approx(float v) {
    float r;
    asm("sqrt.approx.ftz.f32 %0, %1;" : "=f"(r) : "f"(v));
    return r;
}
__device__ __forceinline__ uint2 ld_relaxed_v2(const void* p) {
    uint2 v;
    asm volatile("ld.relaxed.gpu.global.v2.u32 {%0,%1}, [%2];" : "=r"(v.x), "=r"(v.y) : "l"(p) : "memory");
    return v;
}
__device__ __forceinline__ void wait_count(const unsigned* p, unsigned target) {
#pragma unroll 1
    for (int it = 0; it < SPIN_MAX; it++) {
        if (ld_acquire(p) >= target) break;
        __nanosleep(400);
    }
}
__device__ __forceinline__ void wait_row(int bh, float n) {
#pragma unroll 1
    for (int it = 0; it < SPIN_MAX; it++) {
        const float c = ld_relaxed_f2(g_st.lsum[bh]).y;
        if (c >= n) break;
        if (c == 0.f) __nanosleep(600);
    }
}
__device__ __forceinline__ void wait_row_o(int bh, float n) {
    wait_row(bh, n);
    if (bh >= RED0) return;
#pragma unroll 1
    for (int it = 0; it < SPIN_MAX; it++) {
        if (__uint_as_float(ld_relaxed_u32(&g_st.oacc[bh][0].w)) == UPB) break;
        __nanosleep(300);
    }
}
__device__ __forceinline__ void spin_ns(int ns) {
    const long long t0 = clock64();
    while (clock64() - t0 < (long long)ns * 2) {}
}
__device__ __forceinline__ uint32_t pack_bf16(float lo, float hi) {
    uint32_t r;
    asm("cvt.rn.bf16x2.f32 %0, %1, %2;" : "=r"(r) : "f"(hi), "f"(lo));
    return r;
}
__device__ __forceinline__ float bf16r(float v) { return __uint_as_float(pack_bf16(0.f, v)); }
__device__ __forceinline__ uint32_t pack_neg(float lo, float hi) {
    const uint32_t w = pack_bf16(-lo, -hi);
    return w ? w : 0x80008000u;
}
__device__ __forceinline__ float lo_f(uint32_t v) { return __uint_as_float(v << 16); }
__device__ __forceinline__ float hi_f(uint32_t v) { return __uint_as_float(v & 0xffff0000u); }
__device__ __forceinline__ float warp_sum(float v) {
#pragma unroll
    for (int o = 16; o; o >>= 1) v += __shfl_xor_sync(0xffffffffu, v, o);
    return v;
}
__device__ __forceinline__ void layernorm20(float (&v)[20]) {
    float s = 0.f;
#pragma unroll
    for (int i = 0; i < 20; i++) s += v[i];
    const float mean = warp_sum(s) * (1.0f / DM);
    float q = 0.f;
#pragma unroll
    for (int i = 0; i < 20; i++) { const float d = v[i] - mean; q += d * d; }
    const float var = bf16r(warp_sum(q) * (1.0f / DM));
    const float m = bf16r(mean);
    const float rden = 1.0f / bf16r(sqrtf(bf16r(var + 1e-5f)));
#pragma unroll
    for (int i = 0; i < 20; i++) v[i] = bf16r(bf16r(v[i] - m) * rden);
}

__device__ __forceinline__ float sel4(int j, float a, float b, float c, float d) {
    float lo, hi, r;
    asm("{\n.reg .pred p;\nsetp.ne.s32 p, %3, 0;\nselp.f32 %0, %2, %1, p;\n}" : "=f"(lo) : "f"(a), "f"(b), "r"(j & 1));
    asm("{\n.reg .pred p;\nsetp.ne.s32 p, %3, 0;\nselp.f32 %0, %2, %1, p;\n}" : "=f"(hi) : "f"(c), "f"(d), "r"(j & 1));
    asm("{\n.reg .pred p;\nsetp.ne.s32 p, %3, 0;\nselp.f32 %0, %2, %1, p;\n}" : "=f"(r) : "f"(lo), "f"(hi), "r"(j & 2));
    return r;
}
template <typename T> __device__ __forceinline__ void pin(T*& p) { asm volatile("" : "+l"(p)); }
__device__ __forceinline__ void pin(uint32_t& v) { asm volatile("" : "+r"(v)); }
__device__ __forceinline__ void pin(float& v) { asm volatile("" : "+f"(v)); }
__device__ __forceinline__ uint32_t after(uint32_t n, float v) {
    asm volatile("{\n.reg .pred p;\nsetp.eq.u32 p, %1, 0x7fc1a5a5;\n@p add.u32 %0, %0, 32;\n}" : "+r"(n) : "r"(__float_as_uint(v)));
    return n;
}
__device__ __forceinline__ float2 lds64f(uint32_t addr) {
    float2 v;
    asm volatile("ld.shared.v2.f32 {%0,%1}, [%2];" : "=f"(v.x), "=f"(v.y) : "r"(addr) : "memory");
    return v;
}
__device__ __forceinline__ void sts32f(uint32_t addr, float v) { asm volatile("st.shared.f32 [%0], %1;" :: "r"(addr), "f"(v) : "memory"); }
template <int ID> __device__ __forceinline__ void fin_arrive() { asm volatile("bar.arrive %0, 288;" :: "n"(ID) : "memory"); }
template <int ID> __device__ __forceinline__ void fin_sync() { asm volatile("bar.sync %0, 288;" :: "n"(ID) : "memory"); }
template <int ID> __device__ __forceinline__ void fin_sync(uint32_t n) { asm volatile("bar.sync %0, %1;" :: "n"(ID), "r"(n) : "memory"); }
__device__ __forceinline__ float2 sum8(uint32_t addr) {
    float2 t[8];
#pragma unroll
    for (int w = 0; w < 8; w++) t[w] = lds64f(addr + w * 128);
    return make_float2(((t[0].x + t[1].x) + (t[2].x + t[3].x)) + ((t[4].x + t[5].x) + (t[6].x + t[7].x)),
                       ((t[0].y + t[1].y) + (t[2].y + t[3].y)) + ((t[4].y + t[5].y) + (t[6].y + t[7].y)));
}
__device__ __forceinline__ float4 sum8x4(uint32_t addr, int pitch) {
    float4 t[8];
#pragma unroll
    for (int w = 0; w < 8; w++)
        asm volatile("ld.shared.v4.f32 {%0,%1,%2,%3}, [%4];" : "=f"(t[w].x), "=f"(t[w].y), "=f"(t[w].z), "=f"(t[w].w) : "r"(addr + w * pitch) : "memory");
    return make_float4(((t[0].x + t[1].x) + (t[2].x + t[3].x)) + ((t[4].x + t[5].x) + (t[6].x + t[7].x)),
                       ((t[0].y + t[1].y) + (t[2].y + t[3].y)) + ((t[4].y + t[5].y) + (t[6].y + t[7].y)),
                       ((t[0].z + t[1].z) + (t[2].z + t[3].z)) + ((t[4].z + t[5].z) + (t[6].z + t[7].z)),
                       ((t[0].w + t[1].w) + (t[2].w + t[3].w)) + ((t[4].w + t[5].w) + (t[6].w + t[7].w)));
}
__device__ __forceinline__ void sts128f(uint32_t addr, float x, float y, float z, float w) {
    asm volatile("st.shared.v4.f32 [%0], {%1,%2,%3,%4};" :: "r"(addr), "f"(x), "f"(y), "f"(z), "f"(w) : "memory");
}
template <int NJ>
__device__ __forceinline__ void load_o(uint32_t (&ob)[3 * NJ][2], int bh, int J0, int j) {
    float4 v[NJ][4];
    float2 l;
#pragma unroll 1
    for (int it = 0; it < SPIN_MAX; it++) {
#pragma unroll
        for (int J = 0; J < NJ; J++) {
#pragma unroll
            for (int e = 0; e < 4; e++) v[J][e] = ld_relaxed_f4(&g_st.oacc[bh][(J0 + J) * 16 + e * 4 + j]);
        }
        l = ld_relaxed_f2(g_st.lsum[bh]);
        bool ok = l.y == UPB;
#pragma unroll
        for (int J = 0; J < NJ; J++) {
#pragma unroll
            for (int e = 0; e < 4; e++) ok &= v[J][e].w == UPB;
        }
        if (__all_sync(0xffffffffu, ok)) break;
    }
    const float rl = __fdividef(1.0f, l.x);
#pragma unroll
    for (int J = 0; J < NJ; J++) {
        ob[3 * J][0] = pack_bf16(v[J][0].x * rl, v[J][1].x * rl);     ob[3 * J][1] = pack_bf16(v[J][2].x * rl, v[J][3].x * rl);
        ob[3 * J + 1][0] = pack_bf16(v[J][0].y * rl, v[J][1].y * rl); ob[3 * J + 1][1] = pack_bf16(v[J][2].y * rl, v[J][3].y * rl);
        ob[3 * J + 2][0] = pack_bf16(v[J][0].z * rl, v[J][1].z * rl); ob[3 * J + 2][1] = pack_bf16(v[J][2].z * rl, v[J][3].z * rl);
    }
}
__device__ __forceinline__ void aux_sync() { asm volatile("bar.sync 1, 256;" ::: "memory"); }

__global__ void __launch_bounds__(NTHREADS, 1)
fused_decode_kernel(const __grid_constant__ Params p) {
    extern __shared__ __align__(1024) unsigned char smem[];
    const uint32_t sb = s2u(smem);
    const int tid = threadIdx.x, warp = __shfl_sync(0xffffffffu, tid >> 5, 0), lane = tid & 31;
    const int cta = blockIdx.x;
    constexpr int grid = NCTAS;
    const int g = lane >> 2, j = lane & 3;

    TS(0);
    if (tid == 128) {
        mbar_init(sb + BAR_WQ, 1);
        asm volatile("fence.mbarrier_init.release.cluster;" ::: "memory");
        asm volatile("fence.proxy.async.shared::cta;" ::: "memory");
        if (cta < NQ_CTAS) {
            mbar_expect_tx(sb + BAR_WQ, 61440);
#pragma unroll 1
            for (int i = 0; i < 4; i++) tma_box(sb + SM_WQ + i * 15360, &p.wq, cta * 48, i * 160, sb + BAR_WQ);
        }
    } else if (tid == 160) {
#pragma unroll
        for (int w = 0; w < NWORK; w++) mbar_init(sb + SM_MISC + w * 8, 1);
        mbar_init(sb + BAR_WO, 1);
        asm volatile("fence.mbarrier_init.release.cluster;" ::: "memory");
        asm volatile("fence.proxy.async.shared::cta;" ::: "memory");
    } else if (tid >= 192 && tid < 208) {
        mbar_init(sb + BAR_GU + (tid - 192) * 8, 1);
        asm volatile("fence.mbarrier_init.release.cluster;" ::: "memory");
        asm volatile("fence.proxy.async.shared::cta;" ::: "memory");
    }
    __syncthreads();
    if (warp == NAUX + NWORK + 1) {
        asm volatile("bar.sync 2, %0;" :: "n"((NWORK + 2) * 32) : "memory");
        if (cta < NF_CTAS && lane == 0) {
            uint32_t t0 = 0, now;
#pragma unroll 1
            for (int it = 0; it < SPIN_MAX; it++) {
                t0 = ld_relaxed_u32(g_st.fw_time);
                if (t0) break;
                __nanosleep(400);
            }
#pragma unroll 1
            for (int it = 0; it < SPIN_MAX; it++) {
                asm volatile("mov.u32 %0, %%globaltimer_lo;" : "=r"(now));
                if ((int)(now - t0) >= FW_AT_NS) break;
            }
            TS2(9);
            asm volatile("fence.proxy.async.shared::cta;" ::: "memory");
            uint32_t t = clock() + (cta & 3) * (FW_GAP / 4);
#pragma unroll 1
            for (int i = 0; i < 8; i++, t += FW_GAP) {
                mbar_expect_tx(sb + BAR_GU + i * 8, 5120);
                while ((int)(clock() - t) < 0) {}
                tma_box(sb + SM_G + i * 2560, &p.wg, cta * 16, i * 80, sb + BAR_GU + i * 8);
                tma_box(sb + SM_G + 20480 + i * 2560, &p.wu, cta * 16, i * 80, sb + BAR_GU + i * 8);
            }
            if (cta < NG_CTAS) {
                t += FW_MID;
#pragma unroll 1
                for (int i = 0; i < 8; i++, t += FW_GAP2) {
                    mbar_expect_tx(sb + BAR_WD + i * 8, 6144);
                    while ((int)(clock() - t) < 0) {}
                    asm volatile("cp.async.bulk.tensor.4d.shared::cluster.global.mbarrier::complete_tx::bytes [%0], [%1, {%3, %4, %4, %5}], [%2];"
                                 :: "r"(sb + SM_D + i * 6144), "l"(&p.wd), "r"(sb + BAR_WD + i * 8), "r"(cta * 16), "r"(0), "r"(i * 12) : "memory");
                }
            }
        }
        return;
    }
    if (warp == NAUX + NWORK) {
        if (cta < NQ_CTAS) {
#pragma unroll
            for (int i = lane; i < STATE_V4; i += 32)
                if (cta * STATE_V4 + i < (int)(sizeof(State) / 16)) reinterpret_cast<uint4*>(&g_st)[cta * STATE_V4 + i] = make_uint4(0u, 0u, 0u, 0u);
            __syncwarp();
            if (lane == 0) red_release(g_cnt_z);
        }
        if (lane == 0) { TS2(2); wait_count(g_cnt_z, NQ_CTAS); TS2(29); }
        __syncwarp();
        asm volatile("bar.arrive 2, %0;" :: "n"((NWORK + 2) * 32) : "memory");
        fin_arrive<3>();
        int job = cta;
        auto sum_rows = [&](int row_end) {
#pragma unroll 1
            for (; job < 8 * min(row_end, RED0); job += NCTAS) {
                const int row = job >> 3, grp = (job & 7) * 8 + (lane & 7);
                if (lane == 0) wait_row(row, UPB);
                __syncwarp();
                const float4* src = &g_ring[row % RING][lane >> 3][grp];
                float sx = 0.f, sy = 0.f, sz = 0.f;
#pragma unroll 1
                for (int i = 0; i < 2; i++, src += 64 * 64) {
                    float4 v[16];
#pragma unroll 1
                    for (int it = 0; it < SPIN_MAX; it++) {
                        bool ok = true;
#pragma unroll
                        for (int k = 0; k < 16; k++) v[k] = ld_relaxed_b128(src + k * 4 * 64);
#pragma unroll
                        for (int k = 0; k < 16; k++) ok &= v[k].w == (float)(row + 1);
                        if (__all_sync(0xffffffffu, ok)) break;
                    }
#pragma unroll
                    for (int k = 0; k < 16; k++) { sx += v[k].x; sy += v[k].y; sz += v[k].z; }
                }
#pragma unroll
                for (int o = 8; o < 32; o <<= 1) {
                    sx += __shfl_xor_sync(0xffffffffu, sx, o); sy += __shfl_xor_sync(0xffffffffu, sy, o); sz += __shfl_xor_sync(0xffffffffu, sz, o);
                }
                if (lane < 8) st_relaxed_b128(&g_st.oacc[row][grp], sx, sy, sz, UPB);
            }
        };
        if (cta >= NE_CTAS) {
            const int col = (cta - NE_CTAS) * 32 + 2 * (lane & 15);
            uint32_t part = sb + SM_RED + (lane & 15) * 8;
#pragma unroll 1
            for (int b = 0; b < NB; b++) {
                const uint32_t xv = *reinterpret_cast<const uint32_t*>(p.x + b * DM + col);
                uint32_t* dst = &g_st.hx[b][lane >> 4][(col >> 4) * 8 + (col & 6) + ((col >> 3) & 1)];
                sum_rows((b + 1) * NH);
                if (lane == 0) wait_row(b * NH + 28, 1);
                __syncwarp();
                float4 early;
#pragma unroll 1
                for (int it = 0; it < SPIN_MAX; it++) {
                    early = ld_relaxed_f4(&g_st.attn[b][col]);
                    if (__all_sync(0xffffffffu, early.y == NE_CTAS / 4 && early.w == NE_CTAS / 4)) break;
                }
                float x0 = lo_f(xv), x1 = hi_f(xv);
                pin(dst); pin(part); pin(x0); pin(x1);
                fin_sync<4>();
                CK(2, lds32(sb + SM_RED));
                const float2 late = sum8(part);
                const uint32_t hv = pack_neg(x0 + bf16r(early.x + late.x), x1 + bf16r(early.z + late.y));
#pragma unroll
                for (int r = 0; r < HREP / 2; r++) st_relaxed(dst + 2 * r * (DM / 2), hv);
                CK(3, 0);
                fin_sync<5>();
            }
        } else if (cta < NF_CTAS) {
            uint32_t wr[10];
            float wsum = 0.f;
#pragma unroll
            for (int i = 0; i < 10; i++) {
                const int w = 4 * lane + 128 * (i >> 2) + (i & 3) - (i >= 8 ? 2 * lane : 0);
                wr[i] = *reinterpret_cast<const uint32_t*>(p.wr + (w >> 3) * 16 + (w & 1) * 8 + (w & 6));
                wsum += lo_f(wr[i]) + hi_f(wr[i]);
            }
            wsum = warp_sum(wsum);
            const int fb = lane >> 3, fg = lane & 7;
            uint32_t part = sb + SM_RED + fb * 128 + ((fg + (fb & 2)) & 7) * 16;
            uint32_t psum = sb + SM_RED + 4 * 128 + ((fg + 4) & 7) * 16;
            const int yj = 2 * (fb & 1) + (fb >> 1);
            uint32_t ypart = sb + SM_RED2 + yj * 128 + ((fg + 2 * yj) & 7) * 16;
#pragma unroll
            for (int i = lane; i < DM / 2; i += 32) sts32f(sb + SM_X + 4 * HPITCH + i * 4, __uint_as_float(0x3f803f80u));
            float nmean = 0.f, rden = 0.f, sig = 0.f;
#pragma unroll 1
            for (int b = 0; b < NB; b++) {
                const uint32_t* src = g_st.hx[b][cta % HREP];
                const uint32_t hrow = sb + SM_X + b * HPITCH;
                const int ks = cta % 12;
                uint32_t* dst = &g_st.ax[b & 1][0][(((cta / 12) * 3 + (ks >> 2)) * 32 + ((ks & 1) * 4 + fb) * 4 + (fg & 3)) * 4 + (ks & 2) + (fg >> 2)];
                __nv_bfloat16* out = p.out + fb * DM + cta * 16 + fg;
                sum_rows((b + 1) * NH);
                if (lane == 0) wait_row(b * NH + NH - 1, 1);
                __syncwarp();
                uint4 h0, h1;
                uint2 h2;
#pragma unroll 1
                for (int it = 0; it < SPIN_MAX; it++) {
                    h0 = ld_relaxed_v4(src + 4 * lane);
                    h1 = ld_relaxed_v4(src + 128 + 4 * lane);
                    h2 = ld_relaxed_v2(src + 256 + 2 * lane);
                    asm volatile("st.shared.v4.u32 [%0], {%1,%2,%3,%4};" :: "r"(hrow + lane * 16), "r"(h0.x), "r"(h0.y), "r"(h0.z), "r"(h0.w) : "memory");
                    asm volatile("st.shared.v4.u32 [%0], {%1,%2,%3,%4};" :: "r"(hrow + 512 + lane * 16), "r"(h1.x), "r"(h1.y), "r"(h1.z), "r"(h1.w) : "memory");
                    asm volatile("st.shared.v2.u32 [%0], {%1,%2};" :: "r"(hrow + 1024 + lane * 8), "r"(h2.x), "r"(h2.y) : "memory");
                    const uint32_t lo = min(min(min(h0.x, h0.y), min(h0.z, h0.w)), min(min(min(h1.x, h1.y), min(h1.z, h1.w)), min(h2.x, h2.y)));
                    const bool ok = __all_sync(0xffffffffu, lo != 0) || it == SPIN_MAX - 1;
                    asm volatile("{\n.reg .pred p;\nsetp.ne.u32 p, %0, 0;\n@p bar.arrive 7, 288;\n}" :: "r"((uint32_t)(ok && b >= NB - 2)) : "memory");
                    if (ok) break;
                }
                CK(4, h0.x);
                if (h0.x != 0x12345 && lane == 0) TS2(12);
                const uint32_t hw[10] = {h0.x, h0.y, h0.z, h0.w, h1.x, h1.y, h1.z, h1.w, h2.x, h2.y};
                float s1[2] = {}, s2[2] = {};
#pragma unroll
                for (int i = 0; i < 10; i++) {
                    const float v0 = lo_f(hw[i]), v1 = hi_f(hw[i]);
                    s1[i & 1] += v0 + v1;
                    s2[i & 1] = fmaf(v0, v0, fmaf(v1, v1, s2[i & 1]));
                }
                float m1 = s1[0] + s1[1], m2 = s2[0] + s2[1];
#pragma unroll
                for (int o = 16; o; o >>= 1) { m1 += __shfl_xor_sync(0xffffffffu, m1, o); m2 += __shfl_xor_sync(0xffffffffu, m2, o); }
                m1 *= 1.0f / DM;
                const float var = bf16r(fmaxf(fmaf(-m1, m1, m2 * (1.0f / DM)), 0.f));
                const float rd = rcp_approx(bf16r(sqrt_approx(bf16r(var + 1e-5f))));
                if (fb == b) { nmean = bf16r(m1); rden = rd; }
                if (b >= NB - 2) {
                    CK(5, __float_as_uint(rden));
                    fin_sync<4>(after(288, rden));
                    CK(6, lds32(part));
                    const float4 d = sum8x4(part, 640), cs = sum8x4(psum, 640);
                    const float g0 = bf16r(fmaf(nmean, cs.x, -d.x) * rden), g1 = bf16r(fmaf(nmean, cs.y, -d.y) * rden);
                    const float u0 = bf16r(fmaf(nmean, cs.z, -d.z) * rden), u1 = bf16r(fmaf(nmean, cs.w, -d.w) * rden);
                    const uint32_t av = pack_neg(bf16r(g0 * sigmoid_approx(g0)) * u0, bf16r(g1 * sigmoid_approx(g1)) * u1);
#pragma unroll
                    for (int r = 0; r < AREP; r++) st_relaxed(dst + r * (NB * FF / 2), av);
                    CK(7, 0);
                    if (cta < NG_CTAS) fin_arrive<5>();
                }
                if (cta < NG_CTAS) {
                    float rr = 0.f;
#pragma unroll
                    for (int i = 0; i < 10; i++) rr = fmaf(lo_f(hw[i]), lo_f(wr[i]), fmaf(hi_f(hw[i]), hi_f(wr[i]), rr));
                    const float sg = bf16r(sigmoid_approx(bf16r((nmean * wsum - warp_sum(rr)) * rden)));
                    if (fb == b) sig = sg;
                    if (b >= NB - 2) {
                        const float2 hw2 = lds64f(sb + SM_X + fb * HPITCH + (cta * 8 + (fg & 6)) * 4);
                        const uint32_t w0 = __float_as_uint(hw2.x), w1 = __float_as_uint(hw2.y);
                        float nh0 = (fg & 1) ? hi_f(w0) : lo_f(w0), nh1 = (fg & 1) ? hi_f(w1) : lo_f(w1);
                        float ln0 = bf16r(bf16r(nmean - nh0) * rden), ln1 = bf16r(bf16r(nmean - nh1) * rden);
                        fin_sync<6>(after(after(after(288, sig), ln0), ln1));
                        CK(10, lds32(ypart));
                        const float4 y = sum8x4(ypart, 512);
                        const float y0 = -(((fb & 1) ? y.y : y.x) + __shfl_xor_sync(0xffffffffu, (fb & 1) ? y.x : y.y, 8));
                        const float y1 = -(((fb & 1) ? y.w : y.z) + __shfl_xor_sync(0xffffffffu, (fb & 1) ? y.z : y.w, 8));
                        const uint32_t ov = pack_bf16(bf16r(ln0 + bf16r(bf16r(y0) * sig)) - nh0, bf16r(ln1 + bf16r(bf16r(y1) * sig)) - nh1);
                        if (b == NB - 1) {
                            asm volatile("st.global.u16 [%0], %1;" :: "l"(out), "h"((unsigned short)(ov & 0xffffu)) : "memory");
                            asm volatile("st.global.u16 [%0], %1;" :: "l"(out + 8), "h"((unsigned short)(ov >> 16)) : "memory");
                        }
                        CK(11, 0);
                        if (lane == 0) TS2(13);
                    }
                }
            }
            if (cta == 0 && lane == 0) { g_work[0] = 0; g_work[32] = 0; g_cnt_z[0] = 0; }
        } else {
            sum_rows(NBH);
        }
        return;
    }
    if (warp >= NAUX) {
        const int wk = warp - NAUX;
        const uint32_t bar = sb + SM_MISC + wk * 8;
        const uint32_t buf = sb + SM_KV + wk * TILE_BYTES;
        uint64_t pol;
        asm volatile("createpolicy.fractional.L2::evict_first.b64 %0, 1.0;" : "=l"(pol));
        const int nstatic = NWORK * grid;
        constexpr int POOL0 = NUNITS - NPOOL;
        int uk = wk * grid + cta;
        if (lane == 0) {
            if (K0_DELAY_NS) spin_ns(K0_DELAY_NS);
            mbar_expect_tx(bar, TILE_BYTES);
            tma_tile(buf, &p.k, uk * TILE_ROWS, bar, pol);
            if (wk == 0) {
                const uint32_t wbar = sb + BAR_WO;
                spin_ns(WO_AT_NS - K0_DELAY_NS);
                mbar_expect_tx(wbar, cta < NE_CTAS ? 61440 : 49152);
#pragma unroll 1
                for (int i = 0; i < (cta < NE_CTAS ? 5 : 4); i++) {
                    if (cta < NE_CTAS) tma_box(sb + SM_A + i * 12288, &p.wo, (cta & 3) * 160 + i * 32, (cta >> 2) * DH, wbar);
                    else tma_box(sb + SM_A + i * 12288, &p.wo, (cta - NE_CTAS) * 32, (28 + i) * DH, wbar);
                }
            }
        }
        __syncwarp();
        uint32_t koff[3], voff[3];
        {
            const int r = lane & 7, hf = (lane >> 3) & 1;
            const int kkey = hf ? 8 + (r ^ 1) : r;
            const int vh = lane >> 4;
            const int vkey = ((r & 1) ? 8 : 0) + (vh ? (r ^ 1) : r);
#pragma unroll
            for (int b = 0; b < 3; b++) {
                const int rk = 3 * kkey + b, rv = 3 * vkey + b;
                koff[b] = buf + rk * 128 + (((lane >> 4) ^ (rk & 7)) << 4);
                voff[b] = buf + rv * 128 + ((hf ^ (rv & 7)) << 4);
            }
        }
        uint32_t phase = 0;
        uint4 qf[6];
        auto load_q = [&](int u) {
            const uint32_t* q = &g_early[u / UPB].q[j * 4];
#pragma unroll
            for (int i = 0; i < 6; i++) qf[i] = ld_relaxed_v4(q + i * 16);
        };
        load_q(uk);
        int uq[LAG];
        uint32_t sq[LAG];
#pragma unroll
        for (int i = 0; i < LAG; i++) { uq[i] = -1; sq[i] = 0; }
        uint4 mv = make_uint4(0u, 0u, 0u, 0u);
        float freed = UPB;
        while (true) {
            const int uv = uq[0];
            uint32_t sv = sq[0];
#pragma unroll
            for (int i = 0; i + 1 < LAG; i++) { uq[i] = uq[i + 1]; sq[i] = sq[i + 1]; }
            uq[LAG - 1] = uk;
            if (uk < NUNITS) {
                PH(7);
#pragma unroll 1
                for (int it = 0; it < SPIN_MAX; it++) {
                    uint32_t lo = 0xffffffffu;
#pragma unroll
                    for (int i = 0; i < 6; i++) lo = min(min(lo, min(qf[i].x, qf[i].y)), min(qf[i].z, qf[i].w));
                    if (__all_sync(0xffffffffu, lo != 0)) break;
                    __nanosleep(250);
                    load_q(uk);
                }
                mbar_wait(bar, phase); phase ^= 1;
                PH(0); ARR();
                TSI(0, 16); TSI(1, 18);
                float acc[2][4][4] = {};
#pragma unroll
                for (int ks = 0; ks < 12; ks++) {
                    const uint4 qq = qf[ks >> 1];
                    const uint32_t b0 = (ks & 1) ? qq.z : qq.x, b1 = (ks & 1) ? qq.w : qq.y;
#pragma unroll
                    for (int mt = 0; mt < 4; mt++) {
                        uint32_t a[4];
                        ldsm4(a, (koff[ks >> 2] ^ ((ks & 3) << 5)) + mt * 6144);
                        mma16816(acc[ks & 1][mt], a, b0, b1);
                    }
                }
                PH(1);
                TSI(0, 17); TSI(1, 19);
                if (uv < NUNITS) request_tile(buf, uv >= 0 ? &p.v : &p.k, uv >= 0 ? uv : uk + nstatic, bar, pol);
                const float sa = sel4(j, acc[0][0][0], acc[0][1][0], acc[0][2][0], acc[0][3][0]) + sel4(j, acc[1][0][0], acc[1][1][0], acc[1][2][0], acc[1][3][0]);
                const float sc = sel4(j, acc[0][0][2], acc[0][1][2], acc[0][2][2], acc[0][3][2]) + sel4(j, acc[1][0][2], acc[1][1][2], acc[1][2][2], acc[1][3][2]);
                const uint32_t raw = pack_bf16(sa, sc);
                const float scale = -0.07216878364870322f;
                const uint32_t sk = pack_bf16(lo_f(raw) * scale, hi_f(raw) * scale);
                sq[LAG - 1] = sk;
                if (uk >= POOL0) st_relaxed(&g_st.score[uk - POOL0][lane], sk ? sk : 0x80008000u);
                int a = (int)(sk << 16), b = (int)(sk & 0xffff0000u);
                a ^= (a >> 31) & 0x7fff0000; b ^= (b >> 31) & 0x7fff0000;
                const int mx = __reduce_max_sync(0xffffffffu, max(a, b));
                if (lane == 0) st_relaxed(&g_early[uk / UPB].umax[uk % UPB], (uint32_t)mx | 1u);
            }
            if (uv < 0) {
                uk += nstatic;
                load_q(uk);
                continue;
            }
            if (uv >= NUNITS) break;
            const int bh = uv / UPB;
#pragma unroll 1
            for (int it = 0; it < SPIN_MAX; it++) {
                if (__all_sync(0xffffffffu, (mv.x & mv.y & mv.z & mv.w & 1u) && (uv < POOL0 || sv != 0) && freed == UPB)) break;
                mv = ld_relaxed_v4(&g_early[bh].umax[lane * 4]);
                if (bh >= RING && bh < RED0) freed = __uint_as_float(ld_relaxed_u32(&g_st.oacc[bh - RING][(lane & 7) * 8].w));
                if (uv >= POOL0) sv = ld_relaxed_u32(&g_st.score[uv - POOL0][lane]);
            }
            PH(2);
            int un = NUNITS, vn = 0;
            draw(un, g_work, uk < NUNITS && lane == 0);
            uint32_t tdraw;
            asm volatile("mov.u32 %0, %%globaltimer_lo;" : "=r"(tdraw));
            draw(vn, g_work + 32, uq[0] >= POOL0 && lane == 0);
            int mx = __reduce_max_sync(0xffffffffu, max(max((int)mv.x, (int)mv.y), max((int)mv.z, (int)mv.w))) & 0xffff0000;
            mx ^= (mx >> 31) & 0x7fff0000;
            const float m = __int_as_float(mx);
            const float l2e = 1.4426950408889634f;
            const uint32_t pp = pack_bf16(exp2f((lo_f(sv) - m) * l2e), exp2f((hi_f(sv) - m) * l2e));
            uint32_t pb[8];
#pragma unroll
            for (int t = 0; t < 4; t++) {
                pb[2 * t] = __shfl_sync(0xffffffffu, pp, 8 * j + t);
                pb[2 * t + 1] = __shfl_sync(0xffffffffu, pp, 8 * j + 4 + t);
            }
            float lacc[4] = {};
            const uint32_t ones[4] = {0x3f803f80u, 0x3f803f80u, 0x3f803f80u, 0x3f803f80u};
#pragma unroll
            for (int t = 0; t < 4; t++) mma16816(lacc, ones, pb[2 * t], pb[2 * t + 1]);
            PH(3);
            mbar_wait(bar, phase); phase ^= 1;
            PH(4); ARR();
            float acc[12][4] = {};
#pragma unroll
            for (int t = 0; t < 4; t++) {
#pragma unroll
                for (int mt = 0; mt < 12; mt++) {
                    uint32_t a[4];
                    ldsm4t(a, (voff[mt >> 2] ^ ((mt & 3) << 5)) + t * 6144);
                    mma16816(acc[mt], a, pb[2 * t], pb[2 * t + 1]);
                }
            }
            un = __shfl_sync(0xffffffffu, un, 0) + (LAG + 1) * nstatic;
            vn = __shfl_sync(0xffffffffu, vn, 0);
            if (uq[0] >= POOL0) uq[0] = POOL0 + vn;
            PH(5);
            if (lane == 0) PROG(un);
            if (un < NUNITS || uq[0] < NUNITS) request_tile(buf, un < NUNITS ? &p.k : &p.v, un < NUNITS ? un : uq[0], bar, pol);
            if (un < NUNITS) load_q(un);
            if (vn == FW_TICKET && lane == 0) st_relaxed(g_st.fw_time, tdraw | 1u);
            float o[6];
#pragma unroll
            for (int e = 0; e < 6; e++) {
                const int q = e % 3, c = (e / 3) * 2;
                o[e] = sel4(j, acc[q][c], acc[3 + q][c], acc[6 + q][c], acc[9 + q][c]);
            }
            if (uv < nstatic) {
                asm volatile("bar.sync 2, %0;" :: "n"((NWORK + 2) * 32) : "memory");
                TSW(3);
            }
            const int grp = 16 * j + 4 * (g & 1) + (g >> 1);
            if (bh < RED0) {
                float4* dst = &g_ring[bh % RING][uv % UPB][grp];
                st_relaxed_b128(dst, o[0], o[1], o[2], (float)(bh + 1));
                st_relaxed_b128(dst + 8, o[3], o[4], o[5], (float)(bh + 1));
            }
            const int acc_row = bh >= NBH - 4 && uv % OREP ? bh + 4 * (uv % OREP) : bh;
            if (bh >= RED0) {
                red_f4(&g_st.oacc[acc_row][grp].x, o[0], o[1], o[2], 1.f);
                red_f4(&g_st.oacc[acc_row][grp + 8].x, o[3], o[4], o[5], 1.f);
            }
            if (lane == 0) red_f2(&g_st.lsum[acc_row][0].x, lacc[0], 1.f);
            PH(6);
            if (uq[0] >= NUNITS && un >= NUNITS) break;
            uk = un;
            if (uq[0] < NUNITS) {
                const int nb = uq[0] / UPB;
                mv = ld_relaxed_v4(&g_early[nb].umax[lane * 4]);
                freed = nb >= RING && nb < RED0 ? __uint_as_float(ld_relaxed_u32(&g_st.oacc[nb - RING][(lane & 7) * 8].w)) : UPB;
                if (uq[0] >= POOL0) sq[0] = ld_relaxed_u32(&g_st.score[uq[0] - POOL0][lane]);
            }
        }
        TSW(4 + wk);
        return;
    }

    __nv_bfloat16* xs = reinterpret_cast<__nv_bfloat16*>(smem + SM_X);
    float* red = reinterpret_cast<float*>(smem + SM_RED);
    const int frow = (lane & 7) + ((lane >> 4) << 3), fcol = (lane >> 3) & 1;
    if (cta < NQ_CTAS) {
        uint2 xr[5];
        if (warp < NB) {
#pragma unroll
            for (int i = 0; i < 5; i++) xr[i] = *reinterpret_cast<const uint2*>(p.x + warp * DM + i * 128 + lane * 4);
        }
        TS(26);
        if (warp < NB) {
            float v[20];
#pragma unroll
            for (int i = 0; i < 5; i++) {
                v[4 * i] = lo_f(xr[i].x); v[4 * i + 1] = hi_f(xr[i].x); v[4 * i + 2] = lo_f(xr[i].y); v[4 * i + 3] = hi_f(xr[i].y);
            }
            layernorm20(v);
#pragma unroll
            for (int i = 0; i < 5; i++)
                *reinterpret_cast<uint2*>(xs + warp * XPITCH + i * 128 + lane * 4) =
                    make_uint2(pack_bf16(v[4 * i], v[4 * i + 1]), pack_bf16(v[4 * i + 2], v[4 * i + 3]));
        }
        TS(27);
        aux_sync();
        mbar_wait(sb + BAR_WQ, 0);
        TS(1);
        const uint32_t xfrag = sb + SM_X + ((g & 3) * XPITCH + 2 * j) * 2;
        float acc[3][4] = {};
#pragma unroll
        for (int s = 0; s < 5; s++) {
            const int ks = warp * 5 + s;
            const uint32_t b0 = lds32(xfrag + ks * 32), b1 = lds32(xfrag + ks * 32 + 16);
            const int row = ks * 16 + frow;
#pragma unroll
            for (int mt = 0; mt < 3; mt++) {
                uint32_t a[4];
                ldsm4t(a, sb + SM_WQ + (row * 6 + 2 * mt + fcol) * 16);
                mma16816(acc[mt], a, b0, b1);
            }
        }
        if (j < 2) {
#pragma unroll
            for (int mt = 0; mt < 3; mt++) {
                *reinterpret_cast<float2*>(red + (warp * 48 + mt * 16 + g) * 4 + 2 * j) = make_float2(acc[mt][0], acc[mt][1]);
                *reinterpret_cast<float2*>(red + (warp * 48 + mt * 16 + 8 + g) * 4 + 2 * j) = make_float2(acc[mt][2], acc[mt][3]);
            }
        }
        aux_sync();
        if (tid < 96) {
            const int b = tid & 3, cp = tid >> 2;
            float s0 = 0.f, s1 = 0.f;
#pragma unroll
            for (int w = 0; w < 8; w++) { s0 += red[(w * 48 + 2 * cp) * 4 + b]; s1 += red[(w * 48 + 2 * cp + 1) * 4 + b]; }
            const int h = cta >> 2, d = (cta & 3) * 48 + 2 * cp;
            const int ch = d >> 3, jj = (d & 7) >> 1;
            st_relaxed(&g_early[b * NH + h].q[(ch >> 2) * 16 + jj * 4 + (ch & 3)], pack_neg(s0, s1));
        }
        TS(28);
    }
    fin_sync<3>();
    mbar_wait(sb + BAR_WO, 0);
    TS(7);
    uint32_t part = sb + SM_RED + (warp * 32 + 8 * j + g) * 4;

#pragma unroll 1
    for (int b = 0; b < NB; b++) {
        if (cta >= NE_CTAS) {
            uint32_t a[6][2][4];
#pragma unroll
            for (int s = 0; s < 6; s++) {
                const int row = (warp * 6 + s) * 16 + frow;
#pragma unroll
                for (int mt = 0; mt < 2; mt++) ldsm4t(a[s][mt], sb + SM_A + (row * 4 + ((2 * mt + fcol) ^ ((row >> 1) & 3))) * 16);
            }
            const int bh = b * NH + 28 + (warp >> 1);
            if (lane == 0) wait_row_o(bh, UPB * 3 / (4 * OREP));
            __syncwarp();
            float4 ov;
            float2 lv;
            pin(part);
#pragma unroll 1
            for (int it = 0; it < SPIN_MAX; it++) {
                float4 oc[OREP];
                float2 lc[OREP];
#pragma unroll
                for (int c = 0; c < OREP; c++) {
                    const int row = b == NB - 1 ? bh + 4 * c : bh;
                    oc[c] = ld_relaxed_f4(&g_st.oacc[row][(warp & 1) * 32 + lane]);
                    lc[c] = ld_relaxed_f2(g_st.lsum[row]);
                }
                ov = oc[0]; lv = lc[0];
                if (b == NB - 1) {
#pragma unroll
                    for (int c = 1; c < OREP; c++) {
                        ov.x += oc[c].x; ov.y += oc[c].y; ov.z += oc[c].z; ov.w += oc[c].w; lv.x += lc[c].x; lv.y += lc[c].y;
                    }
                }
                if (__all_sync(0xffffffffu, ov.w == UPB && lv.y == UPB)) break;
            }
            CK(0, __float_as_uint(ov.x));
            if (ov.x != 1.2345f && warp == 7) TSW(14);
            const float rl = rcp_approx(lv.x);
            const float px = __shfl_xor_sync(0xffffffffu, ov.x, 4), py = __shfl_xor_sync(0xffffffffu, ov.y, 4),
                        pz = __shfl_xor_sync(0xffffffffu, ov.z, 4);
            const uint32_t w[3] = {pack_bf16(ov.x * rl, px * rl), pack_bf16(ov.y * rl, py * rl), pack_bf16(ov.z * rl, pz * rl)};
            float acc[2][2][4] = {};
#pragma unroll
            for (int s = 0; s < 6; s++) {
                const uint32_t b0 = __shfl_sync(0xffffffffu, w[s % 3], (s / 3) * 16 + j);
                const uint32_t b1 = __shfl_sync(0xffffffffu, w[s % 3], (s / 3) * 16 + 8 + j);
#pragma unroll
                for (int mt = 0; mt < 2; mt++) mma16816(acc[mt][s & 1], a[s][mt], b0, b1);
            }
            sts32f(part, sel4(j, acc[0][0][0] + acc[0][1][0], acc[0][0][2] + acc[0][1][2], acc[1][0][0] + acc[1][1][0], acc[1][0][2] + acc[1][1][2]));
            CK(1, 0);
            fin_arrive<4>();
            fin_sync<5>();
            if (cta < NE_CTAS + 4 && tid < 56) reinterpret_cast<uint4*>(&g_early[b * NH + 28 + cta - NE_CTAS])[tid] = make_uint4(0u, 0u, 0u, 0u);
            continue;
        }
        {
            const int bh = b * NH + (cta >> 2);
            if (tid == 0) wait_row_o(bh, UPB);
            aux_sync();
            if (warp < 5) {
                uint32_t ob[12][2];
                load_o<4>(ob, bh, 0, j);
                float acc[2][2][4] = {};
#pragma unroll
                for (int ks = 0; ks < 12; ks++) {
                    const int row = ks * 16 + frow;
#pragma unroll
                    for (int mt = 0; mt < 2; mt++) {
                        uint32_t a[4];
                        ldsm4t(a, sb + SM_A + warp * 12288 + (row * 4 + ((2 * mt + fcol) ^ ((row >> 1) & 3))) * 16);
                        mma16816(acc[mt][ks & 1], a, ob[ks][0], ob[ks][1]);
                    }
                }
                red_f2(&g_st.attn[b][(cta & 3) * 160 + warp * 32 + 8 * j + g].x,
                       sel4(j, acc[0][0][0] + acc[0][1][0], acc[0][0][2] + acc[0][1][2], acc[1][0][0] + acc[1][1][0], acc[1][0][2] + acc[1][1][2]), 1.f);
                TS(8);
            } else if (warp > 5 && (cta & 3) == 0 && tid - 192 < 56) {
                reinterpret_cast<uint4*>(&g_early[bh])[tid - 192] = make_uint4(0u, 0u, 0u, 0u);
            }
        }
        if (cta >= NF_CTAS || b < NB - 2) continue;

        uint32_t ga[5][2][4];
        if (b == NB - 1) mbar_wait(sb + BAR_GU + warp * 8, 0);
        if (warp == 7) TSW(10);
#pragma unroll
        for (int s = 0; s < 5; s++) {
            const int row = (warp * 5 + s) * 16 + frow;
#pragma unroll
            for (int mt = 0; mt < 2; mt++) ldsm4t(ga[s][mt], sb + SM_G + mt * 20480 + (row * 2 + (fcol ^ ((row >> 2) & 1))) * 16);
        }
        const uint32_t* asrc = &g_st.ax[b & 1][cta % AREP][(warp * 96 + lane) * 4];
        uint32_t gpart = sb + SM_RED + warp * 640 + j * 256 + ((g + 2 * j) & 7) * 16;
        uint32_t ypart = sb + SM_RED2 + warp * 512 + j * 128 + ((g + 2 * j) & 7) * 16;
        uint32_t hfrag = sb + SM_X + min(g, 4) * HPITCH + (warp * 40 + 2 * j) * 4;
        pin(gpart); pin(asrc); pin(ypart); pin(hfrag);
        fin_sync<7>();
        {
            float acc[2][2][4] = {};
#pragma unroll
            for (int s = 0; s < 5; s++) {
                const float2 hv = lds64f(hfrag + s * 32);
#pragma unroll
                for (int mt = 0; mt < 2; mt++) mma16816(acc[mt][s & 1], ga[s][mt], __float_as_uint(hv.x), __float_as_uint(hv.y));
            }
            if (j < 3) sts128f(gpart, acc[0][0][0] + acc[0][1][0], acc[0][0][2] + acc[0][1][2], acc[1][0][0] + acc[1][1][0], acc[1][0][2] + acc[1][1][2]);
            if (j < 2) sts128f(gpart + 128, acc[0][0][1] + acc[0][1][1], acc[0][0][3] + acc[0][1][3], acc[1][0][1] + acc[1][1][1], acc[1][0][3] + acc[1][1][3]);
        }
        CK(5, 0);
        fin_arrive<4>();
        if (cta < NG_CTAS) {
            uint32_t wb[12][4];
            fin_sync<5>();
            if (b == NB - 1) mbar_wait(sb + BAR_WD + warp * 8, 0);
            if (warp == 7) TSW(11);
#pragma unroll
            for (int s = 0; s < 12; s++) {
                const int row = (warp * 12 + s) * 16 + frow;
                ldsm4t(wb[s], sb + SM_D + (row * 2 + (fcol ^ ((row >> 2) & 1))) * 16);
            }
            uint4 va[3];
#pragma unroll 1
            for (int it = 0; it < SPIN_MAX; it++) {
                uint32_t lo = 0xffffffffu;
#pragma unroll
                for (int i = 0; i < 3; i++) va[i] = ld_relaxed_v4(asrc + i * 128);
#pragma unroll
                for (int i = 0; i < 3; i++) lo = min(min(lo, min(va[i].x, va[i].y)), min(va[i].z, va[i].w));
                if (__all_sync(0xffffffffu, lo != 0)) break;
            }
            CK(8, va[0].x);
            if (va[0].x != 0x12345 && warp == 7) TSW(15);
            float acc[4][4] = {};
#pragma unroll
            for (int s = 0; s < 12; s++) {
                const uint4 v = va[s >> 2];
                mma16816(acc[s & 3], wb[s], (s & 2) ? v.z : v.x, (s & 2) ? v.w : v.y);
            }
            float y[4];
#pragma unroll
            for (int e = 0; e < 4; e++) y[e] = j < 2 ? acc[0][e] + acc[2][e] : acc[1][e] + acc[3][e];
            sts128f(ypart, y[0], y[1], y[2], y[3]);
            CK(9, 0);
            fin_arrive<6>();
        }
    }
}

typedef CUresult (*EncodeFn)(CUtensorMap*, CUtensorMapDataType, cuuint32_t, void*, const cuuint64_t*, const cuuint64_t*,
                             const cuuint32_t*, const cuuint32_t*, CUtensorMapInterleave, CUtensorMapSwizzle,
                             CUtensorMapL2promotion, CUtensorMapFloatOOBfill);

CUtensorMap make_map(EncodeFn enc, void* ptr, uint64_t cols, uint64_t rows, uint32_t bcols, uint32_t brows,
                     CUtensorMapSwizzle sw, CUtensorMapL2promotion promo) {
    CUtensorMap m;
    const cuuint64_t dims[2] = {cols, rows};
    const cuuint64_t strides[1] = {cols * 2};
    const cuuint32_t box[2] = {bcols, brows};
    const cuuint32_t es[2] = {1, 1};
    enc(&m, CU_TENSOR_MAP_DATA_TYPE_BFLOAT16, 2, ptr, dims, strides, box, es, CU_TENSOR_MAP_INTERLEAVE_NONE, sw, promo,
        CU_TENSOR_MAP_FLOAT_OOB_FILL_NONE);
    return m;
}

}

extern "C" void kernel_launch(void* const* d_in, const int* in_sizes, int n_in, void* d_out, int out_size) {
    (void)in_sizes; (void)n_in; (void)out_size;
    static EncodeFn enc = nullptr;
    static int sms = 0;
    if (!enc) {
        cudaDriverEntryPointQueryResult qr;
        cudaGetDriverEntryPoint("cuTensorMapEncodeTiled", (void**)&enc, cudaEnableDefault, &qr);
        int dev = 0;
        cudaGetDevice(&dev);
        cudaDeviceGetAttribute(&sms, cudaDevAttrMultiProcessorCount, dev);
        cudaFuncSetAttribute(fused_decode_kernel, cudaFuncAttributeMaxDynamicSharedMemorySize, SM_TOTAL);
    }
    if (sms < NCTAS) return;
    const CUtensorMapL2promotion WPROMO = CU_TENSOR_MAP_L2_PROMOTION_L2_128B;
    Params p;
    p.k = make_map(enc, d_in[1], 64, (uint64_t)NBH * SK * 3, 64, TILE_ROWS, CU_TENSOR_MAP_SWIZZLE_128B, CU_TENSOR_MAP_L2_PROMOTION_NONE);
    p.v = make_map(enc, d_in[2], 64, (uint64_t)NBH * SK * 3, 64, TILE_ROWS, CU_TENSOR_MAP_SWIZZLE_128B, CU_TENSOR_MAP_L2_PROMOTION_NONE);
    p.wq = make_map(enc, d_in[3], NH * DH, DM, 48, 160, CU_TENSOR_MAP_SWIZZLE_NONE, WPROMO);
    p.wo = make_map(enc, d_in[4], DM, NH * DH, 32, DH, CU_TENSOR_MAP_SWIZZLE_64B, WPROMO);
    p.wg = make_map(enc, d_in[7], FF, DM, 16, 80, CU_TENSOR_MAP_SWIZZLE_32B, WPROMO);
    p.wu = make_map(enc, d_in[8], FF, DM, 16, 80, CU_TENSOR_MAP_SWIZZLE_32B, WPROMO);
    {
        const cuuint64_t dims[4] = {DM, 2, 8, FF / 16}, strides[3] = {8 * DM * 2, DM * 2, 16 * DM * 2};
        const cuuint32_t box[4] = {16, 2, 8, 12}, es[4] = {1, 1, 1, 1};
        enc(&p.wd, CU_TENSOR_MAP_DATA_TYPE_BFLOAT16, 4, d_in[9], dims, strides, box, es, CU_TENSOR_MAP_INTERLEAVE_NONE,
            CU_TENSOR_MAP_SWIZZLE_32B, WPROMO, CU_TENSOR_MAP_FLOAT_OOB_FILL_NONE);
    }
    p.x = (const __nv_bfloat16*)d_in[0];
    p.wr = (const __nv_bfloat16*)d_in[6];
    p.out = (__nv_bfloat16*)d_out;
    fused_decode_kernel<<<NCTAS, NTHREADS, SM_TOTAL, cudaStreamPerThread>>>(p);
}
```

```cpp
#include <cuda_runtime.h>
#include <cuda_bf16.h>
#include <cuda.h>
#include <stdint.h>

namespace {

constexpr int NB = 4, NH = 32, SK = 8192, DH = 192, DM = 640, FF = 1536;
constexpr int NBH = NB * NH;
constexpr int TILE = 64;
constexpr int UPB = SK / TILE;
constexpr int NUNITS = NBH * UPB;
constexpr int TILE_BYTES = TILE * DH * 2;
constexpr int TILE_ROWS = TILE * 3;
constexpr int NCTAS = 132;
constexpr int NQ_CTAS = 128;
constexpr int NE_CTAS = 112;
constexpr int NF_CTAS = 96;
constexpr int G0_CTA = NCTAS - 40;

#define NWORK 2
#define NPART 1
#define LAG 2
#define NPOOL 640
#define RED0 116
#define RING 12
#define OREP 3
#define K0_DELAY_NS 1000
#define WO_AT_NS 3800
#define FW_TICKET 400
#define FW_AT_NS 3840
#define FW_GAP 400
#define FW_GAP2 200
#define NPROBE 24
#define SIDE_XOR 0
#define FW_MID 3200
#define FW_MIDL FW_MID
#define FW_GAP2L FW_GAP2
constexpr int NAUX = 8;
constexpr int NTHREADS = (NAUX + NWORK + 2) * 32;
constexpr int SPIN_MAX = 1 << 22;

constexpr int SM_KV = 0;
constexpr int SM_A = SM_KV + NWORK * TILE_BYTES;
constexpr int SM_G = SM_A + 61440;
constexpr int SM_D = SM_G + 40960;
constexpr int SM_WQ = SM_G;
constexpr int SM_X = SM_D + 49152;
constexpr int XPITCH = 648;
constexpr int HPITCH = 1344;
constexpr int SM_RED = SM_X + 5 * HPITCH + 64;
constexpr int SM_RED2 = SM_RED + 8 * 48 * 4 * 4;
constexpr int SM_MISC = SM_RED2 + 4096;
constexpr int BAR_WQ = SM_MISC + 32, BAR_WO = SM_MISC + 40, SM_SIDE = SM_MISC + 48, BAR_GU = SM_MISC + 64, BAR_WD = SM_MISC + 128;
constexpr int BAR_KV = SM_MISC + 192;
constexpr int SM_TOTAL = BAR_KV + NWORK * NPART * 8;
static_assert(NB * XPITCH * 2 <= 4 * HPITCH && SM_RED % 128 == 0, "smem layout");

struct Params {
    CUtensorMap k, v;
    CUtensorMap wq;
    CUtensorMap wo;
    CUtensorMap wg, wu;
    CUtensorMap wd;
    const __nv_bfloat16 *x, *wr;
    __nv_bfloat16* out;
};

struct Early {
    uint32_t q[96];
    uint32_t umax[UPB];
};
struct Twin { uint32_t w[4][1024]; };
constexpr int PROBE = 1024 - 32;
#define LSTRIDE 16
struct State {
    Twin ax[3];
    Twin hx;
    Twin ox[OREP];
    Twin lx;
    float4 oacc[NBH * 64];
    float2 attn[NB][DM];
    uint32_t fw_time[32];
    float2 lsum[NBH][LSTRIDE];
    uint32_t score[NPOOL][32];
};
__host__ __device__ constexpr int oidx(int row, int grp) {
    return (row >> 2) * 256 + ((row & 1) * 2 + (grp >> 5)) * 64 + (row & 2) * 16 + (grp & 31);
}
constexpr int STATE_V4 = ((sizeof(State) / 32 + NQ_CTAS - 1) / NQ_CTAS) * 2;
static_assert(sizeof(State) % 32 == 0, "State is cleared in whole sectors");
static_assert(sizeof(Early) == 56 * 16, "an Early entry is cleared by 56 threads");
struct Scratch {
    State st;
    unsigned work[64];
    unsigned cnt_z[32];
    Early early[NBH];
    alignas(4096) float4 ring[RING][UPB][64];
};
constexpr size_t PAGE = 2u << 20;
static_assert(sizeof(Scratch) <= PAGE, "scratch must fit one page");
__device__ __align__(128) unsigned char g_raw[2 * PAGE];
__device__ __forceinline__ Scratch* scratch() {
    return reinterpret_cast<Scratch*>((reinterpret_cast<uintptr_t>(g_raw) + PAGE - 1) & ~(uintptr_t)(PAGE - 1));
}
#define g_early scratch()->early
#define g_st scratch()->st
#define g_ring scratch()->ring
#define g_cnt_z scratch()->cnt_z
#define g_work scratch()->work
#define TS(i)
#define TSW(i)
#define TS2(i)
#define TSI(n, i)
#define PH(i)
#define CK(i, dep)
#define ARR()
#define PROG(u)

__device__ __forceinline__ uint32_t s2u(const void* p) { return (uint32_t)__cvta_generic_to_shared(p); }
__device__ __forceinline__ void mbar_init(uint32_t bar, int cnt) {
    asm volatile("mbarrier.init.shared::cta.b64 [%0], %1;" :: "r"(bar), "r"(cnt) : "memory");
}
__device__ __forceinline__ void mbar_expect_tx(uint32_t bar, uint32_t bytes) {
    asm volatile("mbarrier.arrive.expect_tx.shared::cta.b64 _, [%0], %1;" :: "r"(bar), "r"(bytes) : "memory");
}
__device__ __forceinline__ void mbar_wait(uint32_t bar, uint32_t parity) {
    asm volatile("{\n.reg .pred p;\n.reg .u32 n;\nmov.u32 n, 0;\nWAIT_LOOP:\n"
                 "mbarrier.try_wait.parity.shared::cta.b64 p, [%0], %1;\n"
                 "@p bra WAIT_DONE;\nadd.u32 n, n, 1;\nsetp.lt.u32 p, n, %2;\n@p bra WAIT_LOOP;\nWAIT_DONE:\n}"
                 :: "r"(bar), "r"(parity), "n"(SPIN_MAX) : "memory");
}
__device__ __forceinline__ bool mbar_test(uint32_t bar, uint32_t parity) {
    uint32_t ok;
    asm volatile("{\n.reg .pred p;\nmbarrier.test_wait.parity.shared::cta.b64 p, [%1], %2;\nselp.u32 %0, 1, 0, p;\n}" : "=r"(ok) : "r"(bar), "r"(parity) : "memory");
    return __all_sync(0xffffffffu, ok);
}
__device__ __forceinline__ void request_tile(uint32_t dst, const CUtensorMap* tm, int unit, uint32_t bar, uint64_t pol) {
#pragma unroll
    for (int i = 0; i < NPART; i++)
        asm volatile("{\n.reg .pred p;\nelect.sync _|p, 0xffffffff;\n"
                     "@p mbarrier.arrive.expect_tx.shared::cta.b64 _, [%2], %6;\n"
                     "@p cp.async.bulk.tensor.2d.shared::cluster.global.mbarrier::complete_tx::bytes.L2::cache_hint "
                     "[%0], [%1, {%3, %4}], [%2], %5;\n}"
                     :: "r"(dst + i * (TILE_BYTES / NPART)), "l"(tm), "r"(bar + i * 8), "r"(0), "r"(unit * TILE_ROWS + i * (TILE_ROWS / NPART)),
                        "l"(pol), "n"(TILE_BYTES / NPART) : "memory");
}
__device__ __forceinline__ void put_groups(void* dst, int mode, const float (&o)[6], float tag, float tag2) {
    asm volatile("{\n.reg .pred s, r, t;\n.reg .b128 u, v;\n.reg .b64 a, b;\n"
                 "setp.eq.s32 s|r, %1, 0;\nsetp.eq.s32 t, %1, 2;\n"
                 "@r red.relaxed.gpu.global.add.v4.f32 [%0], {%2,%3,%4,%8};\n"
                 "@t red.relaxed.gpu.global.add.v4.f32 [%0+4096], {%2,%3,%4,%8};\n"
                 "@r red.relaxed.gpu.global.add.v4.f32 [%0+128], {%5,%6,%7,%9};\n"
                 "@t red.relaxed.gpu.global.add.v4.f32 [%0+4224], {%5,%6,%7,%9};\n"
                 "mov.b64 a, {%2, %3};\nmov.b64 b, {%4, %8};\nmov.b128 u, {a, b};\n"
                 "mov.b64 a, {%5, %6};\nmov.b64 b, {%7, %9};\nmov.b128 v, {a, b};\n"
                 "@s st.relaxed.gpu.global.b128 [%0], u;\n@s st.relaxed.gpu.global.b128 [%0+128], v;\n}"
                 :: "l"(dst), "r"(mode), "f"(o[0]), "f"(o[1]), "f"(o[2]), "f"(o[3]), "f"(o[4]), "f"(o[5]), "f"(tag), "f"(tag2) : "memory");
}
__device__ __forceinline__ void tma_box(uint32_t dst, const CUtensorMap* tm, int col, int row, uint32_t bar) {
    asm volatile("cp.async.bulk.tensor.2d.shared::cluster.global.mbarrier::complete_tx::bytes [%0], [%1, {%3, %4}], [%2];"
                 :: "r"(dst), "l"(tm), "r"(bar), "r"(col), "r"(row) : "memory");
}
__device__ __forceinline__ uint32_t lds32(uint32_t addr) {
    uint32_t v;
    asm volatile("ld.shared.u32 %0, [%1];" : "=r"(v) : "r"(addr) : "memory");
    return v;
}
__device__ __forceinline__ void ldsm4(uint32_t (&r)[4], uint32_t addr) {
    asm volatile("ldmatrix.sync.aligned.m8n8.x4.shared.b16 {%0,%1,%2,%3}, [%4];"
                 : "=r"(r[0]), "=r"(r[1]), "=r"(r[2]), "=r"(r[3]) : "r"(addr) : "memory");
}
__device__ __forceinline__ void ldsm4t(uint32_t (&r)[4], uint32_t addr) {
    asm volatile("ldmatrix.sync.aligned.m8n8.x4.trans.shared.b16 {%0,%1,%2,%3}, [%4];"
                 : "=r"(r[0]), "=r"(r[1]), "=r"(r[2]), "=r"(r[3]) : "r"(addr) : "memory");
}
__device__ __forceinline__ void mma16816(float (&c)[4], const uint32_t (&a)[4], uint32_t b0, uint32_t b1) {
    asm volatile("mma.sync.aligned.m16n8k16.row.col.f32.bf16.bf16.f32 {%0,%1,%2,%3}, {%4,%5,%6,%7}, {%8,%9}, {%0,%1,%2,%3};"
                 : "+f"(c[0]), "+f"(c[1]), "+f"(c[2]), "+f"(c[3])
                 : "r"(a[0]), "r"(a[1]), "r"(a[2]), "r"(a[3]), "r"(b0), "r"(b1));
}
__device__ __forceinline__ uint4 ld_relaxed_v4(const void* p) {
    uint4 v;
    asm volatile("ld.relaxed.gpu.global.v4.u32 {%0,%1,%2,%3}, [%4];" : "=r"(v.x), "=r"(v.y), "=r"(v.z), "=r"(v.w) : "l"(p) : "memory");
    return v;
}
__device__ __forceinline__ float4 ld_relaxed_f4(const void* p) {
    float4 v;
    asm volatile("ld.relaxed.gpu.global.v4.f32 {%0,%1,%2,%3}, [%4];" : "=f"(v.x), "=f"(v.y), "=f"(v.z), "=f"(v.w) : "l"(p) : "memory");
    return v;
}
__device__ __forceinline__ float2 ld_relaxed_f2(const void* p) {
    float2 v;
    asm volatile("ld.relaxed.gpu.global.v2.f32 {%0,%1}, [%2];" : "=f"(v.x), "=f"(v.y) : "l"(p) : "memory");
    return v;
}
__device__ __forceinline__ float4 ld_relaxed_b128(const void* p) {
    float4 v;
    asm volatile("{\n.reg .b128 t;\n.reg .b64 a, b;\nld.relaxed.gpu.global.b128 t, [%4];\nmov.b128 {a, b}, t;\n"
                 "mov.b64 {%0, %1}, a;\nmov.b64 {%2, %3}, b;\n}" : "=f"(v.x), "=f"(v.y), "=f"(v.z), "=f"(v.w) : "l"(p) : "memory");
    return v;
}
__device__ __forceinline__ void st_relaxed_b128(void* p, float x, float y, float z, float w) {
    asm volatile("{\n.reg .b128 t;\n.reg .b64 a, b;\nmov.b64 a, {%1, %2};\nmov.b64 b, {%3, %4};\nmov.b128 t, {a, b};\n"
                 "st.relaxed.gpu.global.b128 [%0], t;\n}" :: "l"(p), "f"(x), "f"(y), "f"(z), "f"(w) : "memory");
}
__device__ __forceinline__ unsigned ld_acquire(const unsigned* p) {
    unsigned v;
    asm volatile("ld.acquire.gpu.global.u32 %0, [%1];" : "=r"(v) : "l"(p) : "memory");
    return v;
}
__device__ __forceinline__ void st_relaxed(void* p, uint32_t v) {
    asm volatile("st.relaxed.gpu.global.u32 [%0], %1;" :: "l"(p), "r"(v) : "memory");
}
__device__ __forceinline__ void red_f2(float* p, float a, float b) {
    asm volatile("red.relaxed.gpu.global.add.v2.f32 [%0], {%1,%2};" :: "l"(p), "f"(a), "f"(b) : "memory");
}
__device__ __forceinline__ void red_f4(float* p, float a, float b, float c, float d) {
    asm volatile("red.relaxed.gpu.global.add.v4.f32 [%0], {%1,%2,%3,%4};" :: "l"(p), "f"(a), "f"(b), "f"(c), "f"(d) : "memory");
}
__device__ __forceinline__ void draw(int& ticket, unsigned* ctr, bool pred) {
    asm volatile("{\n.reg .pred p;\nsetp.ne.u32 p, %2, 0;\n@p atom.relaxed.gpu.global.inc.u32 %0, [%1], 0x7fffffff;\n}"
                 : "+r"(ticket) : "l"(ctr), "r"((uint32_t)pred) : "memory");
}
__device__ __forceinline__ void red_release(unsigned* p) {
    asm volatile("red.release.gpu.global.add.u32 [%0], 1;" :: "l"(p) : "memory");
}
__device__ __forceinline__ uint32_t ld_relaxed_u32(const void* p) {
    uint32_t v;
    asm volatile("ld.relaxed.gpu.global.u32 %0, [%1];" : "=r"(v) : "l"(p) : "memory");
    return v;
}
__device__ __forceinline__ float rcp_approx(float v) {
    float r;
    asm("rcp.approx.ftz.f32 %0, %1;" : "=f"(r) : "f"(v));
    return r;
}
__device__ __forceinline__ float sigmoid_approx(float v) {
    float e;
    asm("ex2.approx.ftz.f32 %0, %1;" : "=f"(e) : "f"(v * -1.4426950408889634f));
    return rcp_approx(1.0f + e);
}
__device__ __forceinline__ float sqrt_approx(float v) {
    float r;
    asm("sqrt.approx.ftz.f32 %0, %1;" : "=f"(r) : "f"(v));
    return r;
}
__device__ __forceinline__ uint2 ld_relaxed_v2(const void* p) {
    uint2 v;
    asm volatile("ld.relaxed.gpu.global.v2.u32 {%0,%1}, [%2];" : "=r"(v.x), "=r"(v.y) : "l"(p) : "memory");
    return v;
}
__device__ __forceinline__ void wait_count(const unsigned* p, unsigned target) {
#pragma unroll 1
    for (int it = 0; it < SPIN_MAX; it++) {
        if (ld_acquire(p) >= target) break;
        __nanosleep(400);
    }
}
__device__ __forceinline__ void wait_row(int bh, float n) {
#pragma unroll 1
    for (int it = 0; it < SPIN_MAX; it++) {
        const float c = ld_relaxed_f2(g_st.lsum[bh]).y;
        if (c >= n) break;
        if (c == 0.f) __nanosleep(600);
    }
}
__device__ __forceinline__ void wait_row_o(int bh, float n) {
    wait_row(bh, n);
    if (bh >= RED0) return;
#pragma unroll 1
    for (int it = 0; it < SPIN_MAX; it++) {
        if (__uint_as_float(ld_relaxed_u32(&g_st.oacc[oidx(bh, 0)].w)) == UPB) break;
        __nanosleep(300);
    }
}
__device__ __forceinline__ void spin_ns(int ns) {
    const long long t0 = clock64();
    while (clock64() - t0 < (long long)ns * 2) {}
}
__device__ __forceinline__ uint32_t pack_bf16(float lo, float hi) {
    uint32_t r;
    asm("cvt.rn.bf16x2.f32 %0, %1, %2;" : "=r"(r) : "f"(hi), "f"(lo));
    return r;
}
__device__ __forceinline__ float bf16r(float v) { return __uint_as_float(pack_bf16(0.f, v)); }
__device__ __forceinline__ uint32_t pack_neg(float lo, float hi) {
    const uint32_t w = pack_bf16(-lo, -hi);
    return w ? w : 0x80008000u;
}
__device__ __forceinline__ float lo_f(uint32_t v) { return __uint_as_float(v << 16); }
__device__ __forceinline__ float hi_f(uint32_t v) { return __uint_as_float(v & 0xffff0000u); }
__device__ __forceinline__ float warp_sum(float v) {
#pragma unroll
    for (int o = 16; o; o >>= 1) v += __shfl_xor_sync(0xffffffffu, v, o);
    return v;
}
__device__ __forceinline__ void layernorm20(float (&v)[20]) {
    float s = 0.f;
#pragma unroll
    for (int i = 0; i < 20; i++) s += v[i];
    const float mean = warp_sum(s) * (1.0f / DM);
    float q = 0.f;
#pragma unroll
    for (int i = 0; i < 20; i++) { const float d = v[i] - mean; q += d * d; }
    const float var = bf16r(warp_sum(q) * (1.0f / DM));
    const float m = bf16r(mean);
    const float rden = 1.0f / bf16r(sqrtf(bf16r(var + 1e-5f)));
#pragma unroll
    for (int i = 0; i < 20; i++) v[i] = bf16r(bf16r(v[i] - m) * rden);
}

__device__ __forceinline__ float sel4(int j, float a, float b, float c, float d) {
    float lo, hi, r;
    asm("{\n.reg .pred p;\nsetp.ne.s32 p, %3, 0;\nselp.f32 %0, %2, %1, p;\n}" : "=f"(lo) : "f"(a), "f"(b), "r"(j & 1));
    asm("{\n.reg .pred p;\nsetp.ne.s32 p, %3, 0;\nselp.f32 %0, %2, %1, p;\n}" : "=f"(hi) : "f"(c), "f"(d), "r"(j & 1));
    asm("{\n.reg .pred p;\nsetp.ne.s32 p, %3, 0;\nselp.f32 %0, %2, %1, p;\n}" : "=f"(r) : "f"(lo), "f"(hi), "r"(j & 2));
    return r;
}
template <typename T> __device__ __forceinline__ void pin(T*& p) { asm volatile("" : "+l"(p)); }
__device__ __forceinline__ void pin(uint32_t& v) { asm volatile("" : "+r"(v)); }
__device__ __forceinline__ void pin(float& v) { asm volatile("" : "+f"(v)); }
__device__ __forceinline__ uint32_t after(uint32_t n, float v) {
    asm volatile("{\n.reg .pred p;\nsetp.eq.u32 p, %1, 0x7fc1a5a5;\n@p add.u32 %0, %0, 32;\n}" : "+r"(n) : "r"(__float_as_uint(v)));
    return n;
}
__device__ __forceinline__ float2 lds64f(uint32_t addr) {
    float2 v;
    asm volatile("ld.shared.v2.f32 {%0,%1}, [%2];" : "=f"(v.x), "=f"(v.y) : "r"(addr) : "memory");
    return v;
}
__device__ __forceinline__ void sts32f(uint32_t addr, float v) { asm volatile("st.shared.f32 [%0], %1;" :: "r"(addr), "f"(v) : "memory"); }
template <int ID> __device__ __forceinline__ void fin_arrive() { asm volatile("bar.arrive %0, 288;" :: "n"(ID) : "memory"); }
template <int ID> __device__ __forceinline__ void fin_sync() { asm volatile("bar.sync %0, 288;" :: "n"(ID) : "memory"); }
template <int ID> __device__ __forceinline__ void fin_sync(uint32_t n) { asm volatile("bar.sync %0, %1;" :: "n"(ID), "r"(n) : "memory"); }
__device__ __forceinline__ float2 sum8(uint32_t addr) {
    float2 t[8];
#pragma unroll
    for (int w = 0; w < 8; w++) t[w] = lds64f(addr + w * 128);
    return make_float2(((t[0].x + t[1].x) + (t[2].x + t[3].x)) + ((t[4].x + t[5].x) + (t[6].x + t[7].x)),
                       ((t[0].y + t[1].y) + (t[2].y + t[3].y)) + ((t[4].y + t[5].y) + (t[6].y + t[7].y)));
}
__device__ __forceinline__ float4 sum4x4(uint32_t addr, int pitch) {
    float4 t[4];
#pragma unroll
    for (int w = 0; w < 4; w++)
        asm volatile("ld.shared.v4.f32 {%0,%1,%2,%3}, [%4];" : "=f"(t[w].x), "=f"(t[w].y), "=f"(t[w].z), "=f"(t[w].w) : "r"(addr + w * pitch) : "memory");
    return make_float4((t[0].x + t[1].x) + (t[2].x + t[3].x), (t[0].y + t[1].y) + (t[2].y + t[3].y),
                       (t[0].z + t[1].z) + (t[2].z + t[3].z), (t[0].w + t[1].w) + (t[2].w + t[3].w));
}
__device__ __forceinline__ void sts64f(uint32_t addr, float x, float y) {
    asm volatile("st.shared.v2.f32 [%0], {%1,%2};" :: "r"(addr), "f"(x), "f"(y) : "memory");
}
__device__ __forceinline__ void lds128_if(uint4& v, uint32_t addr, bool pred) {
    asm volatile("{\n.reg .pred p;\nsetp.ne.u32 p, %5, 0;\n@p ld.shared.v4.u32 {%0,%1,%2,%3}, [%4];\n}"
                 : "+r"(v.x), "+r"(v.y), "+r"(v.z), "+r"(v.w) : "r"(addr), "r"((uint32_t)pred) : "memory");
}
__device__ __forceinline__ void sts128f(uint32_t addr, float x, float y, float z, float w) {
    asm volatile("st.shared.v4.f32 [%0], {%1,%2,%3,%4};" :: "r"(addr), "f"(x), "f"(y), "f"(z), "f"(w) : "memory");
}
template <int NJ>
__device__ __forceinline__ void load_o(uint32_t (&ob)[3 * NJ][2], int bh, int J0, int j) {
    float4 v[NJ][4];
    float2 l;
#pragma unroll 1
    for (int it = 0; it < SPIN_MAX; it++) {
#pragma unroll
        for (int J = 0; J < NJ; J++) {
#pragma unroll
            for (int e = 0; e < 4; e++) v[J][e] = ld_relaxed_f4(&g_st.oacc[oidx(bh, j)] + oidx(0, (J0 + J) * 16 + e * 4));
        }
        l = ld_relaxed_f2(g_st.lsum[bh]);
        bool ok = l.y == UPB;
#pragma unroll
        for (int J = 0; J < NJ; J++) {
#pragma unroll
            for (int e = 0; e < 4; e++) ok &= v[J][e].w == UPB;
        }
        if (__all_sync(0xffffffffu, ok)) break;
    }
    const float rl = __fdividef(1.0f, l.x);
#pragma unroll
    for (int J = 0; J < NJ; J++) {
        ob[3 * J][0] = pack_bf16(v[J][0].x * rl, v[J][1].x * rl);     ob[3 * J][1] = pack_bf16(v[J][2].x * rl, v[J][3].x * rl);
        ob[3 * J + 1][0] = pack_bf16(v[J][0].y * rl, v[J][1].y * rl); ob[3 * J + 1][1] = pack_bf16(v[J][2].y * rl, v[J][3].y * rl);
        ob[3 * J + 2][0] = pack_bf16(v[J][0].z * rl, v[J][1].z * rl); ob[3 * J + 2][1] = pack_bf16(v[J][2].z * rl, v[J][3].z * rl);
    }
}
__device__ __forceinline__ int near_side(uint32_t sb) {
    uint32_t v;
    asm volatile("ld.volatile.shared.u32 %0, [%1];" : "=r"(v) : "r"(sb + SM_SIDE) : "memory");
    return v;
}
__device__ __forceinline__ void aux_sync() { asm volatile("bar.sync 1, 256;" ::: "memory"); }

__global__ void __launch_bounds__(NTHREADS, 1)
fused_decode_kernel(const __grid_constant__ Params p) {
    extern __shared__ __align__(1024) unsigned char smem[];
    const uint32_t sb = s2u(smem);
    const int tid = threadIdx.x, warp = __shfl_sync(0xffffffffu, tid >> 5, 0), lane = tid & 31;
    const int cta = blockIdx.x;
    constexpr int grid = NCTAS;
    const int g = lane >> 2, j = lane & 3;

    TS(0);
    if (tid == 128) {
        mbar_init(sb + BAR_WQ, 1);
        asm volatile("fence.mbarrier_init.release.cluster;" ::: "memory");
        asm volatile("fence.proxy.async.shared::cta;" ::: "memory");
        if (cta < NQ_CTAS) {
            mbar_expect_tx(sb + BAR_WQ, 61440);
#pragma unroll 1
            for (int i = 0; i < 4; i++) tma_box(sb + SM_WQ + i * 15360, &p.wq, cta * 48, i * 160, sb + BAR_WQ);
        }
    } else if (tid == 160) {
        mbar_init(sb + BAR_WO, 1);
        sts32f(sb + SM_SIDE, 0.f);
        asm volatile("fence.mbarrier_init.release.cluster;" ::: "memory");
        asm volatile("fence.proxy.async.shared::cta;" ::: "memory");
    } else if (tid >= 192 && tid < 208 + NWORK * NPART) {
        mbar_init(sb + BAR_GU + (tid - 192) * 8, 1);
        asm volatile("fence.mbarrier_init.release.cluster;" ::: "memory");
        asm volatile("fence.proxy.async.shared::cta;" ::: "memory");
    }
    __syncthreads();
    if (warp == NAUX + NWORK + 1) {
        asm volatile("bar.sync 2, %0;" :: "n"((NWORK + 2) * 32) : "memory");
        if (lane == 0) {
            uint32_t* ctr = &g_st.hx.w[0][PROBE];
            uint32_t best[2] = {~0u, ~0u};
#pragma unroll 1
            for (int i = 0; i < NPROBE; i++) {
#pragma unroll
                for (int c = 0; c < 2; c++) {
                    uint32_t t0 = clock(), t1 = t0, v;
                    asm volatile("atom.relaxed.gpu.global.inc.u32 %0, [%1], 0x7fffffff;" : "=r"(v) : "l"(ctr + c * 1024) : "memory");
                    asm volatile("{\n.reg .pred p;\nsetp.ne.u32 p, %1, 0xffffffff;\n@p mov.u32 %0, %%clock;\n}" : "+r"(t1) : "r"(v) : "memory");
                    best[c] = min(best[c], t1 - t0);
                }
                __nanosleep(1000);
            }
            sts32f(sb + SM_SIDE, __uint_as_float((best[1] < best[0]) ^ SIDE_XOR));
        }
        asm volatile("bar.sync 8, 64;" ::: "memory");
        if (lane == 0) {
            uint32_t t0 = 0, now;
#pragma unroll 1
            for (int it = 0; it < SPIN_MAX; it++) {
                t0 = ld_relaxed_u32(g_st.fw_time);
                if (t0) break;
                __nanosleep(400);
            }
            asm volatile("fence.proxy.async.shared::cta;" ::: "memory");
            auto load_wd = [&](uint32_t t, int gap) {
#pragma unroll 1
                for (int i = 0; i < 8; i++, t += gap) {
                    mbar_expect_tx(sb + BAR_WD + i * 8, 6144);
                    while ((int)(clock() - t) < 0) {}
                    asm volatile("cp.async.bulk.tensor.4d.shared::cluster.global.mbarrier::complete_tx::bytes [%0], [%1, {%3, %4, %4, %5}], [%2];"
                                 :: "r"(sb + SM_D + i * 6144), "l"(&p.wd), "r"(sb + BAR_WD + i * 8), "r"((cta - G0_CTA) * 16), "r"(0), "r"(i * 12) : "memory");
                }
            };
            if (cta >= G0_CTA && cta < NF_CTAS) load_wd(clock(), 0);
#pragma unroll 1
            for (int it = 0; it < SPIN_MAX; it++) {
                asm volatile("mov.u32 %0, %%globaltimer_lo;" : "=r"(now));
                if ((int)(now - t0) >= FW_AT_NS) break;
            }
            TS2(9);
            if (cta < NF_CTAS) {
                uint32_t t = clock() + (cta & 3) * (FW_GAP / 4);
#pragma unroll 1
                for (int i = 0; i < 8; i++, t += FW_GAP) {
                    mbar_expect_tx(sb + BAR_GU + i * 8, 5120);
                    while ((int)(clock() - t) < 0) {}
                    tma_box(sb + SM_G + (i & 1) * 20480 + (i >> 1) * 5120, (i & 1) ? &p.wu : &p.wg, cta * 16, (i >> 1) * 160, sb + BAR_GU + i * 8);
                }
            } else {
                const int gap = cta >= NE_CTAS ? FW_GAP2L : FW_GAP2;
                load_wd(clock() + (cta >= NE_CTAS ? FW_MIDL : FW_MID) + (cta & 3) * (gap / 4), gap);
            }
        }
        return;
    }
    if (warp == NAUX + NWORK) {
        if (cta < NQ_CTAS) {
#pragma unroll
            for (int i = lane; i < STATE_V4; i += 32)
                if (cta * STATE_V4 + i < (int)(sizeof(State) / 16)) reinterpret_cast<uint4*>(&g_st)[cta * STATE_V4 + i] = make_uint4(0u, 0u, 0u, 0u);
            __syncwarp();
            if (lane == 0) red_release(g_cnt_z);
        }
        if (lane == 0) { TS2(2); wait_count(g_cnt_z, NQ_CTAS); TS2(29); }
        __syncwarp();
        asm volatile("bar.arrive 2, %0;" :: "n"((NWORK + 2) * 32) : "memory");
        fin_arrive<3>();
        int job = cta;
        auto sum_rows = [&](int row_end) {
#pragma unroll 1
            for (; job < 8 * min(row_end, RED0); job += NCTAS) {
                const int row = job >> 3, grp = (job & 7) * 8 + (lane & 7);
                if (lane == 0) wait_row(row, UPB);
                __syncwarp();
                const float4* src = &g_ring[row % RING][lane >> 3][grp];
                float sx = 0.f, sy = 0.f, sz = 0.f;
#pragma unroll 1
                for (int i = 0; i < 2; i++, src += 64 * 64) {
                    float4 v[16];
#pragma unroll 1
                    for (int it = 0; it < SPIN_MAX; it++) {
                        bool ok = true;
#pragma unroll
                        for (int k = 0; k < 16; k++) v[k] = ld_relaxed_b128(src + k * 4 * 64);
#pragma unroll
                        for (int k = 0; k < 16; k++) ok &= v[k].w == (float)(row + 1);
                        if (__all_sync(0xffffffffu, ok)) break;
                    }
#pragma unroll
                    for (int k = 0; k < 16; k++) { sx += v[k].x; sy += v[k].y; sz += v[k].z; }
                }
#pragma unroll
                for (int o = 8; o < 32; o <<= 1) {
                    sx += __shfl_xor_sync(0xffffffffu, sx, o); sy += __shfl_xor_sync(0xffffffffu, sy, o); sz += __shfl_xor_sync(0xffffffffu, sz, o);
                }
                if (lane < 8) st_relaxed_b128(&g_st.oacc[oidx(row, grp)], sx, sy, sz, UPB);
            }
        };
        uint32_t wr[10];
        float wsum = 0.f;
#pragma unroll
        for (int i = 0; i < 10; i++) {
            const int w = 4 * lane + 128 * (i >> 2) + (i & 3) - (i >= 8 ? 2 * lane : 0);
            wr[i] = *reinterpret_cast<const uint32_t*>(p.wr + (w >> 4) * 32 + (w & 3) * 8 + ((w >> 1) & 6));
            wsum += lo_f(wr[i]) + hi_f(wr[i]);
        }
        wsum = warp_sum(wsum);
        const int fb = lane >> 3, fg = lane & 7;
#pragma unroll
        for (int i = lane; i < DM / 2; i += 32) sts32f(sb + SM_X + 4 * HPITCH + i * 4, __uint_as_float(0x3f803f80u));
        float nmean = 0.f, rden = 0.f, sig = 0.f;
#pragma unroll 1
        for (int b = 0; b < NB; b++) {
            sum_rows((b + 1) * NH);
            if (b == NB - 1) asm volatile("bar.arrive 8, 64;" ::: "memory");
            if (cta >= NE_CTAS) {
                const int col = (cta - NE_CTAS) * 32 + 2 * (lane & 15);
                const uint32_t xv = *reinterpret_cast<const uint32_t*>(p.x + b * DM + col);
                const int hw = (col >> 5) * 16 + (col & 6) * 2 + ((col >> 3) & 3);
                uint32_t* dst = &g_st.hx.w[(~b & 2) + (lane >> 4)][(b & 1) * 128 + (hw >> 7) * 256 + (hw & 127)];
                uint32_t part = sb + SM_RED + (lane & 15) * 8;
                if (lane == 0) wait_row(b * NH + 28, 1);
                __syncwarp();
                float4 early;
#pragma unroll 1
                for (int it = 0; it < SPIN_MAX; it++) {
                    early = ld_relaxed_f4(&g_st.attn[b][col]);
                    if (__all_sync(0xffffffffu, early.y == NE_CTAS / 4 && early.w == NE_CTAS / 4)) break;
                }
                if (early.x != 1.2345f && lane == 0) TS2(6);
                CK(1, __float_as_uint(early.x));
                float x0 = lo_f(xv), x1 = hi_f(xv);
                pin(dst); pin(part); pin(x0); pin(x1);
                fin_sync<4>();
                CK(2, lds32(sb + SM_RED));
                const float2 late = sum8(part);
                const uint32_t hv = pack_neg(x0 + bf16r(early.x + late.x), x1 + bf16r(early.z + late.y));
                st_relaxed(dst, hv);
                CK(3, 0);
                fin_arrive<5>();
            } else {
                if (lane == 0) wait_row(b * NH + NH - 1, 1);
                __syncwarp();
            }
            const bool ffn = b >= NB - 2;
            const uint32_t* src = &g_st.hx.w[(~b & 2) + near_side(sb)][(b & 1) * 128];
            const uint32_t hrow = sb + SM_X + b * HPITCH;
            const int ks = cta % 12;
            uint32_t* dst = &g_st.ax[ks >> 2].w[(~b & 1) * 2][((cta / 12) * 32 + ((ks & 1) * 4 + fb) * 4 + (fg & 3)) * 4 + (ks & 2) + (fg >> 2)];
            uint32_t part = sb + SM_RED + fb * 128 + ((fg + (fb & 2)) & 7) * 16;
            uint32_t psum = sb + SM_RED + 4 * 128 + ((fg + 4) & 7) * 16;
            pin(dst); pin(part); pin(psum);
            uint4 h0, h1;
            uint2 h2;
#pragma unroll 1
            for (int it = 0; it < SPIN_MAX; it++) {
                h0 = ld_relaxed_v4(src + 4 * lane);
                h1 = ld_relaxed_v4(src + 256 + 4 * lane);
                h2 = ld_relaxed_v2(src + 512 + 2 * lane);
                asm volatile("st.shared.v4.u32 [%0], {%1,%2,%3,%4};" :: "r"(hrow + lane * 16), "r"(h0.x), "r"(h0.y), "r"(h0.z), "r"(h0.w) : "memory");
                asm volatile("st.shared.v4.u32 [%0], {%1,%2,%3,%4};" :: "r"(hrow + 512 + lane * 16), "r"(h1.x), "r"(h1.y), "r"(h1.z), "r"(h1.w) : "memory");
                asm volatile("st.shared.v2.u32 [%0], {%1,%2};" :: "r"(hrow + 1024 + lane * 8), "r"(h2.x), "r"(h2.y) : "memory");
                const uint32_t lo = min(min(min(h0.x, h0.y), min(h0.z, h0.w)), min(min(min(h1.x, h1.y), min(h1.z, h1.w)), min(h2.x, h2.y)));
                const bool ok = __all_sync(0xffffffffu, lo != 0) || it == SPIN_MAX - 1;
                asm volatile("{\n.reg .pred p;\nsetp.ne.u32 p, %0, 0;\n@p bar.arrive 7, 288;\n}" :: "r"((uint32_t)(ok && ffn)) : "memory");
                if (ok) break;
                if (b < NB - 1) __nanosleep(500);
            }
            CK(4, h0.x);
            if (h0.x != 0x12345 && lane == 0) TS2(12);
            const uint32_t hw[10] = {h0.x, h0.y, h0.z, h0.w, h1.x, h1.y, h1.z, h1.w, h2.x, h2.y};
            float s1[2] = {}, s2[2] = {};
#pragma unroll
            for (int i = 0; i < 10; i++) {
                const float v0 = lo_f(hw[i]), v1 = hi_f(hw[i]);
                s1[i & 1] += v0 + v1;
                s2[i & 1] = fmaf(v0, v0, fmaf(v1, v1, s2[i & 1]));
            }
            float m1 = s1[0] + s1[1], m2 = s2[0] + s2[1];
#pragma unroll
            for (int o = 16; o; o >>= 1) { m1 += __shfl_xor_sync(0xffffffffu, m1, o); m2 += __shfl_xor_sync(0xffffffffu, m2, o); }
            auto moments = [&]() {
                m1 *= 1.0f / DM;
                const float var = bf16r(fmaxf(fmaf(-m1, m1, m2 * (1.0f / DM)), 0.f));
                const float rd = rcp_approx(bf16r(sqrt_approx(bf16r(var + 1e-5f))));
                if (fb == b) { nmean = bf16r(m1); rden = rd; }
            };
            if (ffn && cta < NF_CTAS) {
                CK(5, __float_as_uint(m2));
                fin_sync<4>(after(288, m2));
                CK(6, lds32(part));
                const float4 d = sum4x4(part, 640), cs = sum4x4(psum, 640);
                moments();
                const float g0 = bf16r(fmaf(nmean, cs.x, -d.x) * rden), g1 = bf16r(fmaf(nmean, cs.y, -d.y) * rden);
                const float u0 = bf16r(fmaf(nmean, cs.z, -d.z) * rden), u1 = bf16r(fmaf(nmean, cs.w, -d.w) * rden);
                const uint32_t av = pack_neg(bf16r(g0 * sigmoid_approx(g0)) * u0, bf16r(g1 * sigmoid_approx(g1)) * u1);
                st_relaxed(dst, av);
                st_relaxed(dst + 1024, av);
                CK(7, 0);
            } else {
                moments();
            }
            if (cta >= G0_CTA) {
                float rr = 0.f;
#pragma unroll
                for (int i = 0; i < 10; i++) rr = fmaf(lo_f(hw[i]), lo_f(wr[i]), fmaf(hi_f(hw[i]), hi_f(wr[i]), rr));
                const float sg = bf16r(sigmoid_approx(bf16r((nmean * wsum - warp_sum(rr)) * rden)));
                if (fb == b) sig = sg;
                if (ffn) {
                    const int gi = cta - G0_CTA, yj = 2 * (fb & 1) + (fb >> 1);
                    uint32_t ypart = sb + SM_RED2 + yj * 128 + ((fg + 2 * yj) & 7) * 16;
                    __nv_bfloat16* out = p.out + fb * DM + gi * 16 + fg;
                    __syncwarp();
                    const float2 hw2 = lds64f(sb + SM_X + fb * HPITCH + ((gi >> 1) * 16 + (fg & 6) * 2 + (gi & 1) * 2) * 4);
                    const uint32_t w0 = __float_as_uint(hw2.x), w1 = __float_as_uint(hw2.y);
                    float nh0 = (fg & 1) ? hi_f(w0) : lo_f(w0), nh1 = (fg & 1) ? hi_f(w1) : lo_f(w1);
                    float ln0 = bf16r(bf16r(nmean - nh0) * rden), ln1 = bf16r(bf16r(nmean - nh1) * rden);
                    pin(ypart); pin(out);
                    fin_sync<6>(after(after(after(288, sig), ln0), ln1));
                    CK(10, lds32(ypart));
                    const float4 ya = sum4x4(ypart, 512), yb = sum4x4(ypart + 2048, 512);
                    const float4 y = make_float4(ya.x + yb.x, ya.y + yb.y, ya.z + yb.z, ya.w + yb.w);
                    const float y0 = -(((fb & 1) ? y.y : y.x) + __shfl_xor_sync(0xffffffffu, (fb & 1) ? y.x : y.y, 8));
                    const float y1 = -(((fb & 1) ? y.w : y.z) + __shfl_xor_sync(0xffffffffu, (fb & 1) ? y.z : y.w, 8));
                    const uint32_t ov = pack_bf16(bf16r(ln0 + bf16r(bf16r(y0) * sig)) - nh0, bf16r(ln1 + bf16r(bf16r(y1) * sig)) - nh1);
                    if (b == NB - 1) {
                        asm volatile("st.global.u16 [%0], %1;" :: "l"(out), "h"((unsigned short)(ov & 0xffffu)) : "memory");
                        asm volatile("st.global.u16 [%0], %1;" :: "l"(out + 8), "h"((unsigned short)(ov >> 16)) : "memory");
                    } else {
                        fin_arrive<3>();
                    }
                    CK(11, 0);
                    if (lane == 0) TS2(13);
                }
            }
        }
        if (cta == 0 && lane == 0) { g_work[0] = 0; g_work[32] = 0; g_cnt_z[0] = 0; }
        return;
    }
    if (warp >= NAUX) {
        const int wk = warp - NAUX;
        const uint32_t bar = sb + BAR_KV + wk * (NPART * 8);
        const uint32_t buf = sb + SM_KV + wk * TILE_BYTES;
        uint64_t pol;
        asm volatile("createpolicy.fractional.L2::evict_first.b64 %0, 1.0;" : "=l"(pol));
        const int nstatic = NWORK * grid;
        constexpr int POOL0 = NUNITS - NPOOL;
        int uk = wk * grid + cta;
        if (K0_DELAY_NS) spin_ns(K0_DELAY_NS);
        __syncwarp();
        request_tile(buf, &p.k, uk, bar, pol);
        if (lane == 0) {
            if (wk == 0) {
                const uint32_t wbar = sb + BAR_WO;
                spin_ns(WO_AT_NS - K0_DELAY_NS);
                mbar_expect_tx(wbar, cta < NE_CTAS ? 61440 : 49152);
#pragma unroll 1
                for (int i = 0; i < (cta < NE_CTAS ? 5 : 4); i++) {
                    if (cta < NE_CTAS) tma_box(sb + SM_A + i * 12288, &p.wo, (cta & 3) * 160 + i * 32, (cta >> 2) * DH, wbar);
                    else tma_box(sb + SM_A + i * 12288, &p.wo, (cta - NE_CTAS) * 32, (28 + i) * DH, wbar);
                }
            }
        }
        __syncwarp();
        uint32_t koff[3], voff[3];
        {
            const int r = lane & 7, hf = (lane >> 3) & 1;
            const int kkey = hf ? 8 + (r ^ 1) : r;
            const int vh = lane >> 4;
            const int vkey = ((r & 1) ? 8 : 0) + (vh ? (r ^ 1) : r);
#pragma unroll
            for (int b = 0; b < 3; b++) {
                const int rk = 3 * kkey + b, rv = 3 * vkey + b;
                koff[b] = buf + rk * 128 + (((lane >> 4) ^ (rk & 7)) << 4);
                voff[b] = buf + rv * 128 + ((hf ^ (rv & 7)) << 4);
            }
        }
        uint32_t phase = 0;
        uint4 qf[6];
        auto load_q = [&](int u) {
            const uint32_t* q = &g_early[u / UPB].q[j * 4];
#pragma unroll
            for (int i = 0; i < 6; i++) qf[i] = ld_relaxed_v4(q + i * 16);
        };
        load_q(uk);
        int uq[LAG];
        uint32_t sq[LAG];
#pragma unroll
        for (int i = 0; i < LAG; i++) { uq[i] = -1; sq[i] = 0; }
        uint4 mv = make_uint4(0u, 0u, 0u, 0u);
        float freed = UPB;
        while (true) {
            const int uv = uq[0];
            uint32_t sv = sq[0];
#pragma unroll
            for (int i = 0; i + 1 < LAG; i++) { uq[i] = uq[i + 1]; sq[i] = sq[i + 1]; }
            uq[LAG - 1] = uk;
            if (uk < NUNITS) {
                PH(7);
#pragma unroll 1
                for (int it = 0; it < SPIN_MAX; it++) {
                    uint32_t lo = 0xffffffffu;
#pragma unroll
                    for (int i = 0; i < 6; i++) lo = min(min(lo, min(qf[i].x, qf[i].y)), min(qf[i].z, qf[i].w));
                    if (__all_sync(0xffffffffu, lo != 0)) break;
                    __nanosleep(250);
                    load_q(uk);
                }
#pragma unroll
                for (int t = 0; t < NPART; t++) mbar_wait(bar + t * 8, phase);
                phase ^= 1;
                PH(0); ARR();
                TSI(0, 16); TSI(1, 18);
                float acc[2][4][4] = {};
#pragma unroll
                for (int ks = 0; ks < 12; ks++) {
                    const uint4 qq = qf[ks >> 1];
                    const uint32_t b0 = (ks & 1) ? qq.z : qq.x, b1 = (ks & 1) ? qq.w : qq.y;
#pragma unroll
                    for (int mt = 0; mt < 4; mt++) {
                        uint32_t a[4];
                        ldsm4(a, (koff[ks >> 2] ^ ((ks & 3) << 5)) + mt * 6144);
                        mma16816(acc[ks & 1][mt], a, b0, b1);
                    }
                }
                PH(1);
                TSI(0, 17); TSI(1, 19);
                if (uv < NUNITS) request_tile(buf, uv >= 0 ? &p.v : &p.k, uv >= 0 ? uv : uk + nstatic, bar, pol);
                const float sa = sel4(j, acc[0][0][0], acc[0][1][0], acc[0][2][0], acc[0][3][0]) + sel4(j, acc[1][0][0], acc[1][1][0], acc[1][2][0], acc[1][3][0]);
                const float sc = sel4(j, acc[0][0][2], acc[0][1][2], acc[0][2][2], acc[0][3][2]) + sel4(j, acc[1][0][2], acc[1][1][2], acc[1][2][2], acc[1][3][2]);
                const uint32_t raw = pack_bf16(sa, sc);
                const float scale = -0.07216878364870322f;
                const uint32_t sk = pack_bf16(lo_f(raw) * scale, hi_f(raw) * scale);
                sq[LAG - 1] = sk;
                if (uk >= POOL0) st_relaxed(&g_st.score[uk - POOL0][lane], sk ? sk : 0x80008000u);
                int a = (int)(sk << 16), b = (int)(sk & 0xffff0000u);
                a ^= (a >> 31) & 0x7fff0000; b ^= (b >> 31) & 0x7fff0000;
                const int mx = __reduce_max_sync(0xffffffffu, max(a, b));
                if (lane == 0) st_relaxed(&g_early[uk / UPB].umax[uk % UPB], (uint32_t)mx | 1u);
            }
            if (uv < 0) {
                uk += nstatic;
                load_q(uk);
                continue;
            }
            if (uv >= NUNITS) break;
            const int bh = uv / UPB;
#pragma unroll 1
            for (int it = 0; it < SPIN_MAX; it++) {
                if (__all_sync(0xffffffffu, (mv.x & mv.y & mv.z & mv.w & 1u) && (uv < POOL0 || sv != 0) && freed == UPB)) break;
                mv = ld_relaxed_v4(&g_early[bh].umax[lane * 4]);
                if (bh >= RING && bh < RED0) freed = __uint_as_float(ld_relaxed_u32(&g_st.oacc[oidx(bh - RING, (lane & 7) * 8)].w));
                if (uv >= POOL0) sv = ld_relaxed_u32(&g_st.score[uv - POOL0][lane]);
            }
            PH(2);
            int un = NUNITS, vn = 0;
            draw(un, g_work, uk < NUNITS && lane == 0);
            uint32_t tdraw;
            asm volatile("mov.u32 %0, %%globaltimer_lo;" : "=r"(tdraw));
            draw(vn, g_work + 32, uq[0] >= POOL0 && lane == 0);
            int mx = __reduce_max_sync(0xffffffffu, max(max((int)mv.x, (int)mv.y), max((int)mv.z, (int)mv.w))) & 0xffff0000;
            mx ^= (mx >> 31) & 0x7fff0000;
            const float m = __int_as_float(mx);
            const float l2e = 1.4426950408889634f;
            const uint32_t pp = pack_bf16(exp2f((lo_f(sv) - m) * l2e), exp2f((hi_f(sv) - m) * l2e));
            uint32_t pb[8];
#pragma unroll
            for (int t = 0; t < 4; t++) {
                pb[2 * t] = __shfl_sync(0xffffffffu, pp, 8 * j + t);
                pb[2 * t + 1] = __shfl_sync(0xffffffffu, pp, 8 * j + 4 + t);
            }
            float lacc[4] = {};
            const uint32_t ones[4] = {0x3f803f80u, 0x3f803f80u, 0x3f803f80u, 0x3f803f80u};
#pragma unroll
            for (int t = 0; t < 4; t++) mma16816(lacc, ones, pb[2 * t], pb[2 * t + 1]);
            if (uv < nstatic) {
                asm volatile("bar.sync 2, %0;" :: "n"((NWORK + 2) * 32) : "memory");
                TSW(3);
            }
            const int grp = 16 * j + 4 * (g & 1) + (g >> 1);
            uint32_t mode = (bh >= RED0) + (bh >= NBH - 4);
            float tag = mode ? 1.f : (float)(bh + 1), tag2 = tag;
            void* dst = mode == 0 ? (void*)&g_ring[bh % RING][uv % UPB][grp] :
                        mode == 1 ? (void*)&g_st.oacc[oidx(bh, grp)] : (void*)&g_st.ox[uv % OREP].w[0][oidx(bh & 3, grp) * 4];
            if (mode == 2 && lane < 2) red_f2(reinterpret_cast<float*>(&g_st.lx.w[lane][(bh & 3) * 256 + (uv % OREP) * 32]), lacc[0], 1.f);
            un = __shfl_sync(0xffffffffu, un, 0) + (LAG + 1) * nstatic;
            vn = __shfl_sync(0xffffffffu, vn, 0);
            if (uq[0] >= POOL0) uq[0] = POOL0 + vn;
            if (vn == FW_TICKET && lane == 0) st_relaxed(g_st.fw_time, tdraw | 1u);
            pin(dst); pin(mode); pin(tag); pin(tag2); pin(voff[0]); pin(voff[1]); pin(voff[2]);
            PH(3);
            float acc[12][4] = {};
#pragma unroll
            for (int t = 0; t < 4; t++) {
                if (t % (4 / NPART) == 0) mbar_wait(bar + t / (4 / NPART) * 8, phase);
                if (t == 4 - 4 / NPART) { PH(4); ARR(); CK(12, lds32(buf)); }
#pragma unroll
                for (int mt = 0; mt < 12; mt++) {
                    uint32_t a[4];
                    ldsm4t(a, (voff[mt >> 2] ^ ((mt & 3) << 5)) + t * 6144);
                    mma16816(acc[mt], a, pb[2 * t], pb[2 * t + 1]);
                }
            }
            phase ^= 1;
            PH(5);
            if (lane == 0) PROG(un);
            if (un < NUNITS || uq[0] < NUNITS) request_tile(buf, un < NUNITS ? &p.k : &p.v, un < NUNITS ? un : uq[0], bar, pol);
            float o[6];
#pragma unroll
            for (int e = 0; e < 6; e++) {
                const int q = e % 3, c = (e / 3) * 2;
                o[e] = sel4(j, acc[q][c], acc[3 + q][c], acc[6 + q][c], acc[9 + q][c]);
            }
            put_groups(dst, mode, o, tag, tag2);
            CK(13, 0);
            if (un < NUNITS) load_q(un);
            if (lane == 0) red_f2(&g_st.lsum[bh][0].x, lacc[0], 1.f);
            PH(6);
            if (uq[0] >= NUNITS && un >= NUNITS) break;
            uk = un;
            if (uq[0] < NUNITS) {
                const int nb = uq[0] / UPB;
                mv = ld_relaxed_v4(&g_early[nb].umax[lane * 4]);
                freed = nb >= RING && nb < RED0 ? __uint_as_float(ld_relaxed_u32(&g_st.oacc[oidx(nb - RING, (lane & 7) * 8)].w)) : UPB;
                if (uq[0] >= POOL0) sq[0] = ld_relaxed_u32(&g_st.score[uq[0] - POOL0][lane]);
            }
        }
        TSW(4 + wk);
        return;
    }

    __nv_bfloat16* xs = reinterpret_cast<__nv_bfloat16*>(smem + SM_X);
    float* red = reinterpret_cast<float*>(smem + SM_RED);
    const int frow = (lane & 7) + ((lane >> 4) << 3), fcol = (lane >> 3) & 1;
    const uint32_t f32b = sb + (frow * 2 + (fcol ^ ((frow >> 2) & 1))) * 16;
    const uint32_t f64b = sb + (frow * 4 + (fcol ^ ((frow >> 1) & 3))) * 16;
    if (cta < NQ_CTAS) {
        uint2 xr[5];
        if (warp < NB) {
#pragma unroll
            for (int i = 0; i < 5; i++) xr[i] = *reinterpret_cast<const uint2*>(p.x + warp * DM + i * 128 + lane * 4);
        }
        TS(26);
        if (warp < NB) {
            float v[20];
#pragma unroll
            for (int i = 0; i < 5; i++) {
                v[4 * i] = lo_f(xr[i].x); v[4 * i + 1] = hi_f(xr[i].x); v[4 * i + 2] = lo_f(xr[i].y); v[4 * i + 3] = hi_f(xr[i].y);
            }
            layernorm20(v);
#pragma unroll
            for (int i = 0; i < 5; i++)
                *reinterpret_cast<uint2*>(xs + warp * XPITCH + i * 128 + lane * 4) =
                    make_uint2(pack_bf16(v[4 * i], v[4 * i + 1]), pack_bf16(v[4 * i + 2], v[4 * i + 3]));
        }
        TS(27);
        aux_sync();
        mbar_wait(sb + BAR_WQ, 0);
        TS(1);
        const uint32_t xfrag = sb + SM_X + ((g & 3) * XPITCH + 2 * j) * 2;
        float acc[3][4] = {};
#pragma unroll
        for (int s = 0; s < 5; s++) {
            const int ks = warp * 5 + s;
            const uint32_t b0 = lds32(xfrag + ks * 32), b1 = lds32(xfrag + ks * 32 + 16);
            const int row = ks * 16 + frow;
#pragma unroll
            for (int mt = 0; mt < 3; mt++) {
                uint32_t a[4];
                ldsm4t(a, sb + SM_WQ + (row * 6 + 2 * mt + fcol) * 16);
                mma16816(acc[mt], a, b0, b1);
            }
        }
        if (j < 2) {
#pragma unroll
            for (int mt = 0; mt < 3; mt++) {
                *reinterpret_cast<float2*>(red + (warp * 48 + mt * 16 + g) * 4 + 2 * j) = make_float2(acc[mt][0], acc[mt][1]);
                *reinterpret_cast<float2*>(red + (warp * 48 + mt * 16 + 8 + g) * 4 + 2 * j) = make_float2(acc[mt][2], acc[mt][3]);
            }
        }
        aux_sync();
        if (tid < 96) {
            const int b = tid & 3, cp = tid >> 2;
            float s0 = 0.f, s1 = 0.f;
#pragma unroll
            for (int w = 0; w < 8; w++) { s0 += red[(w * 48 + 2 * cp) * 4 + b]; s1 += red[(w * 48 + 2 * cp + 1) * 4 + b]; }
            const int h = cta >> 2, d = (cta & 3) * 48 + 2 * cp;
            const int ch = d >> 3, jj = (d & 7) >> 1;
            st_relaxed(&g_early[b * NH + h].q[(ch >> 2) * 16 + jj * 4 + (ch & 3)], pack_neg(s0, s1));
        }
        TS(28);
    }
    fin_sync<3>();
    mbar_wait(sb + BAR_WO, 0);
    TS(7);
    uint32_t part = sb + SM_RED + (warp * 32 + 8 * j + g) * 4;

#pragma unroll 1
    for (int b = 0; b < NB; b++) {
        if (cta >= NE_CTAS) {
            uint32_t a[6][2][4];
#pragma unroll
            for (int s = 0; s < 6; s++) {
#pragma unroll
                for (int mt = 0; mt < 2; mt++) ldsm4t(a[s][mt], (f64b ^ (mt * 32)) + SM_A + (warp * 6 + s) * 1024);
            }
            const int bh = b * NH + 28 + (warp >> 1);
            const int side = near_side(sb) ^ 1;
            const void *osrc[OREP], *lsrc[OREP];
#pragma unroll
            for (int c = 0; c < OREP; c++) {
                osrc[c] = b == NB - 1 ? (const void*)&g_st.ox[c].w[side][oidx(bh & 3, (warp & 1) * 32 + lane) * 4] : &g_st.oacc[oidx(bh, (warp & 1) * 32 + lane)];
                lsrc[c] = b == NB - 1 ? (const void*)&g_st.lx.w[side][(bh & 3) * 256 + c * 32] : g_st.lsum[bh];
            }
            if (lane == 0) wait_row_o(bh, UPB * 3 / 4);
            __syncwarp();
            float4 ov;
            float2 lv;
            pin(part);
#pragma unroll 1
            for (int it = 0; it < SPIN_MAX; it++) {
                float4 oc[OREP];
                float2 lc[OREP];
#pragma unroll
                for (int c = 0; c < OREP; c++) { oc[c] = ld_relaxed_f4(osrc[c]); lc[c] = ld_relaxed_f2(lsrc[c]); }
                ov = oc[0]; lv = lc[0];
                if (b == NB - 1) {
#pragma unroll
                    for (int c = 1; c < OREP; c++) {
                        ov.x += oc[c].x; ov.y += oc[c].y; ov.z += oc[c].z; ov.w += oc[c].w; lv.x += lc[c].x; lv.y += lc[c].y;
                    }
                }
                if (__all_sync(0xffffffffu, ov.w == UPB && lv.y == UPB)) break;
            }
            CK(0, __float_as_uint(ov.x));
            if (ov.x != 1.2345f && warp == 7) TSW(14);
            const float rl = rcp_approx(lv.x);
            const float px = __shfl_xor_sync(0xffffffffu, ov.x, 4), py = __shfl_xor_sync(0xffffffffu, ov.y, 4),
                        pz = __shfl_xor_sync(0xffffffffu, ov.z, 4);
            const uint32_t w[3] = {pack_bf16(ov.x * rl, px * rl), pack_bf16(ov.y * rl, py * rl), pack_bf16(ov.z * rl, pz * rl)};
            float acc[2][2][4] = {};
#pragma unroll
            for (int s = 0; s < 6; s++) {
                const uint32_t b0 = __shfl_sync(0xffffffffu, w[s % 3], (s / 3) * 16 + j);
                const uint32_t b1 = __shfl_sync(0xffffffffu, w[s % 3], (s / 3) * 16 + 8 + j);
#pragma unroll
                for (int mt = 0; mt < 2; mt++) mma16816(acc[mt][s & 1], a[s][mt], b0, b1);
            }
            sts32f(part, sel4(j, acc[0][0][0] + acc[0][1][0], acc[0][0][2] + acc[0][1][2], acc[1][0][0] + acc[1][1][0], acc[1][0][2] + acc[1][1][2]));
            CK(1, 0);
            fin_arrive<4>();
            fin_sync<5>();
            if (cta < NE_CTAS + 4 && tid < 56) reinterpret_cast<uint4*>(&g_early[b * NH + 28 + cta - NE_CTAS])[tid] = make_uint4(0u, 0u, 0u, 0u);
        } else {
            const int bh = b * NH + (cta >> 2);
            if (tid == 0) wait_row_o(bh, UPB);
            aux_sync();
            if (warp < 5) {
                uint32_t ob[12][2];
                load_o<4>(ob, bh, 0, j);
                float acc[2][2][4] = {};
#pragma unroll
                for (int ks = 0; ks < 12; ks++) {
#pragma unroll
                    for (int mt = 0; mt < 2; mt++) {
                        uint32_t a[4];
                        ldsm4t(a, (f64b ^ (mt * 32)) + SM_A + warp * 12288 + ks * 1024);
                        mma16816(acc[mt][ks & 1], a, ob[ks][0], ob[ks][1]);
                    }
                }
                red_f2(&g_st.attn[b][(cta & 3) * 160 + warp * 32 + 8 * j + g].x,
                       sel4(j, acc[0][0][0] + acc[0][1][0], acc[0][0][2] + acc[0][1][2], acc[1][0][0] + acc[1][1][0], acc[1][0][2] + acc[1][1][2]), 1.f);
                TS(8);
            } else if (warp > 5 && (cta & 3) == 0 && tid - 192 < 56) {
                reinterpret_cast<uint4*>(&g_early[bh])[tid - 192] = make_uint4(0u, 0u, 0u, 0u);
            }
        }
        if (b < NB - 2) continue;

        const uint32_t* asrc = &g_st.ax[0].w[(~b & 1) * 2 + near_side(sb)][(warp * 32 + lane) * 4];
        uint4 va[3];
        auto poll_act = [&]() {
            uint32_t lo = 0xffffffffu;
#pragma unroll
            for (int i = 0; i < 3; i++) va[i] = ld_relaxed_v4(asrc + i * 4096);
#pragma unroll
            for (int i = 0; i < 3; i++) lo = min(min(lo, min(va[i].x, va[i].y)), min(va[i].z, va[i].w));
            return __all_sync(0xffffffffu, lo != 0);
        };
        bool have_act = false;
        uint32_t wb[12][4];
        if (cta >= G0_CTA) {
            if (cta >= NF_CTAS) {
                fin_sync<7>();
#pragma unroll 1
                for (int it = 0; it < SPIN_MAX && !have_act; it++) {
                    if (mbar_test(sb + BAR_WD + warp * 8, b == NB - 1 ? 0 : it & 1)) break;
                    have_act = poll_act();
                }
            }
            if (b == NB - 1) mbar_wait(sb + BAR_WD + warp * 8, 0);
            if (warp == 7) TSW(11);
            CK(13, lds32(sb + SM_D));
#pragma unroll
            for (int s = 0; s < 12; s++) ldsm4t(wb[s], f32b + SM_D + (warp * 12 + s) * 512);
        }
        if (cta < NF_CTAS) {
            uint32_t ga[10][4];
            uint4 hv[5] = {};
            uint32_t hfrag = sb + SM_X + min(g, 4) * HPITCH + ((warp >> 1) * 80 + 4 * j) * 4;
#pragma unroll
            for (int s = 0; s < 5; s++) lds128_if(hv[s], hfrag + s * 64, b == NB - 1);
            if (b == NB - 1) mbar_wait(sb + BAR_GU + warp * 8, 0);
            if (warp == 7) TSW(10);
            CK(12, lds32(sb + SM_G));
#pragma unroll
            for (int s = 0; s < 10; s++) ldsm4t(ga[s], f32b + SM_G + (warp & 1) * 20480 + ((warp >> 1) * 10 + s) * 512);
            uint32_t gpart = sb + SM_RED + (warp >> 1) * 640 + j * 256 + ((g + 2 * j) & 7) * 16 + (warp & 1) * 8;
            pin(gpart); pin(hfrag);
            fin_sync<7>();
#pragma unroll
            for (int s = 0; s < 5; s++) lds128_if(hv[s], hfrag + s * 64, g == b);
            float acc[4][4] = {};
#pragma unroll
            for (int s = 0; s < 10; s++) mma16816(acc[s & 3], ga[s], (s & 1) ? hv[s >> 1].z : hv[s >> 1].x, (s & 1) ? hv[s >> 1].w : hv[s >> 1].y);
            float c[4];
#pragma unroll
            for (int e = 0; e < 4; e++) c[e] = (acc[2][e] + acc[3][e]) + (acc[0][e] + acc[1][e]);
            if (j < 3) sts64f(gpart, c[0], c[2]);
            if (j < 2) sts64f(gpart + 128, c[1], c[3]);
            CK(5, 0);
            fin_arrive<4>();
        }
        if (cta >= G0_CTA) {
            uint32_t ypart = sb + SM_RED2 + warp * 512 + j * 128 + ((g + 2 * j) & 7) * 16;
            pin(ypart);
#pragma unroll 1
            for (int it = 0; it < SPIN_MAX && !have_act; it++) have_act = poll_act();
            CK(8, va[0].x);
            if (va[0].x != 0x12345 && warp == 7) TSW(15);
            float acc[4][4] = {};
#pragma unroll
            for (int s = 0; s < 12; s++) {
                const uint4 v = va[s >> 2];
                mma16816(acc[s & 3], wb[s], (s & 2) ? v.z : v.x, (s & 2) ? v.w : v.y);
            }
            float y[4];
#pragma unroll
            for (int e = 0; e < 4; e++) y[e] = j < 2 ? acc[0][e] + acc[2][e] : acc[1][e] + acc[3][e];
            sts128f(ypart, y[0], y[1], y[2], y[3]);
            CK(9, 0);
            fin_arrive<6>();
            if (b < NB - 1) fin_sync<3>();
        }
    }
}

typedef CUresult (*EncodeFn)(CUtensorMap*, CUtensorMapDataType, cuuint32_t, void*, const cuuint64_t*, const cuuint64_t*,
                             const cuuint32_t*, const cuuint32_t*, CUtensorMapInterleave, CUtensorMapSwizzle,
                             CUtensorMapL2promotion, CUtensorMapFloatOOBfill);

CUtensorMap make_map(EncodeFn enc, void* ptr, uint64_t cols, uint64_t rows, uint32_t bcols, uint32_t brows,
                     CUtensorMapSwizzle sw, CUtensorMapL2promotion promo) {
    CUtensorMap m;
    const cuuint64_t dims[2] = {cols, rows};
    const cuuint64_t strides[1] = {cols * 2};
    const cuuint32_t box[2] = {bcols, brows};
    const cuuint32_t es[2] = {1, 1};
    enc(&m, CU_TENSOR_MAP_DATA_TYPE_BFLOAT16, 2, ptr, dims, strides, box, es, CU_TENSOR_MAP_INTERLEAVE_NONE, sw, promo,
        CU_TENSOR_MAP_FLOAT_OOB_FILL_NONE);
    return m;
}

}

extern "C" void kernel_launch(void* const* d_in, const int* in_sizes, int n_in, void* d_out, int out_size) {
    (void)in_sizes; (void)n_in; (void)out_size;
    static EncodeFn enc = nullptr;
    static int sms = 0;
    if (!enc) {
        cudaDriverEntryPointQueryResult qr;
        cudaGetDriverEntryPoint("cuTensorMapEncodeTiled", (void**)&enc, cudaEnableDefault, &qr);
        int dev = 0;
        cudaGetDevice(&dev);
        cudaDeviceGetAttribute(&sms, cudaDevAttrMultiProcessorCount, dev);
        cudaFuncSetAttribute(fused_decode_kernel, cudaFuncAttributeMaxDynamicSharedMemorySize, SM_TOTAL);
    }
    if (sms < NCTAS) return;
    const CUtensorMapL2promotion WPROMO = CU_TENSOR_MAP_L2_PROMOTION_L2_128B;
    Params p;
    p.k = make_map(enc, d_in[1], 64, (uint64_t)NBH * SK * 3, 64, TILE_ROWS / NPART, CU_TENSOR_MAP_SWIZZLE_128B, CU_TENSOR_MAP_L2_PROMOTION_NONE);
    p.v = make_map(enc, d_in[2], 64, (uint64_t)NBH * SK * 3, 64, TILE_ROWS / NPART, CU_TENSOR_MAP_SWIZZLE_128B, CU_TENSOR_MAP_L2_PROMOTION_NONE);
    p.wq = make_map(enc, d_in[3], NH * DH, DM, 48, 160, CU_TENSOR_MAP_SWIZZLE_NONE, WPROMO);
    p.wo = make_map(enc, d_in[4], DM, NH * DH, 32, DH, CU_TENSOR_MAP_SWIZZLE_64B, WPROMO);
    p.wg = make_map(enc, d_in[7], FF, DM, 16, 160, CU_TENSOR_MAP_SWIZZLE_32B, WPROMO);
    p.wu = make_map(enc, d_in[8], FF, DM, 16, 160, CU_TENSOR_MAP_SWIZZLE_32B, WPROMO);
    {
        const cuuint64_t dims[4] = {DM, 2, 8, FF / 16}, strides[3] = {8 * DM * 2, DM * 2, 16 * DM * 2};
        const cuuint32_t box[4] = {16, 2, 8, 12}, es[4] = {1, 1, 1, 1};
        enc(&p.wd, CU_TENSOR_MAP_DATA_TYPE_BFLOAT16, 4, d_in[9], dims, strides, box, es, CU_TENSOR_MAP_INTERLEAVE_NONE,
            CU_TENSOR_MAP_SWIZZLE_32B, WPROMO, CU_TENSOR_MAP_FLOAT_OOB_FILL_NONE);
    }
    p.x = (const __nv_bfloat16*)d_in[0];
    p.wr = (const __nv_bfloat16*)d_in[6];
    p.out = (__nv_bfloat16*)d_out;
    fused_decode_kernel<<<NCTAS, NTHREADS, SM_TOTAL, cudaStreamPerThread>>>(p);
}
```

```cpp
#include <cuda_runtime.h>
#include <cuda_bf16.h>
#include <cuda.h>
#include <stdint.h>

namespace {

constexpr int NB = 4, NH = 32, SK = 8192, DH = 192, DM = 640, FF = 1536;
constexpr int NBH = NB * NH;
constexpr int TILE = 64;
constexpr int UPB = SK / TILE;
constexpr int NUNITS = NBH * UPB;
constexpr int TILE_BYTES = TILE * DH * 2;
constexpr int TILE_ROWS = TILE * 3;
constexpr int NCTAS = 132;
constexpr int NQ_CTAS = 128;
constexpr int NE_CTAS = 112;
#define ROLES 1
__host__ __device__ constexpr bool is_f(int cta) { return cta < 96 && !(cta & 2); }
__host__ __device__ constexpr bool is_g(int cta) { return cta < 80 && (cta & 2); }
__host__ __device__ constexpr int ffn_slice(int cta) { return (cta >> 2) * 2 + (cta & 1); }

#define NWORK 2
#define NPART 1
#define LAG 2
#define NPOOL 640
#define RED0 116
#define RING 12
#define OREP 3
#define K0_DELAY_NS 1000
#define WO_AT_NS 3800
#define FW_TICKET 400
#define FW_AT_NS 3840
#define FW_GAP 400
#define FW_GAP2 400
#define GRAM_AT 2
#define HPOLL2 4
#define FW_STAG (FW_GAP / 2)
#define HGATE 0
#define NPROBE 24
#define SIDE_XOR 0
#define FW_MID 1000
constexpr int NAUX = 8;
constexpr int NTHREADS = (NAUX + NWORK + 2) * 32;
constexpr int SPIN_MAX = 1 << 22;

constexpr int SM_KV = 0;
constexpr int SM_A = SM_KV + NWORK * TILE_BYTES;
constexpr int SM_W = SM_A + 61440;
constexpr int SM_X = SM_W + 81920;
constexpr int XPITCH = 648;
constexpr int HPITCH = 1344;
constexpr int SM_RED = SM_X + 5 * HPITCH + 64;
constexpr int SM_RED2 = SM_RED + 8 * 48 * 4 * 4;
constexpr int SM_MISC = SM_RED2 + 4096;
constexpr int BAR_WQ = SM_MISC + 32, BAR_WO = SM_MISC + 40, SM_SIDE = SM_MISC + 48, BAR_FW = SM_MISC + 64;
constexpr int BAR_KV = BAR_FW + 64;
constexpr int SM_TOTAL = BAR_KV + NWORK * NPART * 8;
static_assert(NB * XPITCH * 2 <= 4 * HPITCH && SM_RED % 128 == 0, "smem layout");

struct Params {
    CUtensorMap k, v;
    CUtensorMap wq;
    CUtensorMap wo;
    CUtensorMap wg, wu;
    CUtensorMap wd;
    const __nv_bfloat16 *x, *wr;
    __nv_bfloat16* out;
};

struct Early {
    uint32_t q[96];
    uint32_t umax[UPB];
};
struct Twin { uint32_t w[4][1024]; };
constexpr int PROBE = 1024 - 32;
#define LSTRIDE 16
struct State {
    Twin ax[3];
    Twin hx;
    Twin ox[OREP];
    Twin lx;
    float4 oacc[NBH * 64];
    float2 attn[NB][DM];
    uint32_t fw_time[32];
    float2 lsum[NBH][LSTRIDE];
    uint32_t score[NPOOL][32];
};
__host__ __device__ constexpr int oidx(int row, int grp) {
    return (row >> 2) * 256 + ((row & 1) * 2 + (grp >> 5)) * 64 + (row & 2) * 16 + (grp & 31);
}
constexpr int STATE_V4 = ((sizeof(State) / 32 + NQ_CTAS - 1) / NQ_CTAS) * 2;
static_assert(sizeof(State) % 32 == 0, "State is cleared in whole sectors");
static_assert(sizeof(Early) == 56 * 16, "an Early entry is cleared by 56 threads");
struct Scratch {
    State st;
    unsigned work[64];
    unsigned cnt_z[32];
    Early early[NBH];
    alignas(4096) float4 ring[RING][UPB][64];
};
constexpr size_t PAGE = 2u << 20;
static_assert(sizeof(Scratch) <= PAGE, "scratch must fit one page");
__device__ __align__(128) unsigned char g_raw[2 * PAGE];
__device__ __forceinline__ Scratch* scratch() {
    return reinterpret_cast<Scratch*>((reinterpret_cast<uintptr_t>(g_raw) + PAGE - 1) & ~(uintptr_t)(PAGE - 1));
}
#define g_early scratch()->early
#define g_st scratch()->st
#define g_ring scratch()->ring
#define g_cnt_z scratch()->cnt_z
#define g_work scratch()->work
#define TS(i)
#define TSW(i)
#define TS2(i)
#define TSI(n, i)
#define PH(i)
#define CK(i, dep)
#define ARR()
#define PROG(u)

__device__ __forceinline__ uint32_t s2u(const void* p) { return (uint32_t)__cvta_generic_to_shared(p); }
__device__ __forceinline__ void mbar_init(uint32_t bar, int cnt) {
    asm volatile("mbarrier.init.shared::cta.b64 [%0], %1;" :: "r"(bar), "r"(cnt) : "memory");
}
__device__ __forceinline__ void mbar_expect_tx(uint32_t bar, uint32_t bytes) {
    asm volatile("mbarrier.arrive.expect_tx.shared::cta.b64 _, [%0], %1;" :: "r"(bar), "r"(bytes) : "memory");
}
__device__ __forceinline__ void mbar_wait(uint32_t bar, uint32_t parity) {
    asm volatile("{\n.reg .pred p;\n.reg .u32 n;\nmov.u32 n, 0;\nWAIT_LOOP:\n"
                 "mbarrier.try_wait.parity.shared::cta.b64 p, [%0], %1;\n"
                 "@p bra WAIT_DONE;\nadd.u32 n, n, 1;\nsetp.lt.u32 p, n, %2;\n@p bra WAIT_LOOP;\nWAIT_DONE:\n}"
                 :: "r"(bar), "r"(parity), "n"(SPIN_MAX) : "memory");
}
__device__ __forceinline__ bool mbar_test(uint32_t bar, uint32_t parity) {
    uint32_t ok;
    asm volatile("{\n.reg .pred p;\nmbarrier.test_wait.parity.shared::cta.b64 p, [%1], %2;\nselp.u32 %0, 1, 0, p;\n}" : "=r"(ok) : "r"(bar), "r"(parity) : "memory");
    return __all_sync(0xffffffffu, ok);
}
__device__ __forceinline__ void request_tile(uint32_t dst, const CUtensorMap* tm, int unit, uint32_t bar, uint64_t pol) {
#pragma unroll
    for (int i = 0; i < NPART; i++)
        asm volatile("{\n.reg .pred p;\nelect.sync _|p, 0xffffffff;\n"
                     "@p mbarrier.arrive.expect_tx.shared::cta.b64 _, [%2], %6;\n"
                     "@p cp.async.bulk.tensor.2d.shared::cluster.global.mbarrier::complete_tx::bytes.L2::cache_hint "
                     "[%0], [%1, {%3, %4}], [%2], %5;\n}"
                     :: "r"(dst + i * (TILE_BYTES / NPART)), "l"(tm), "r"(bar + i * 8), "r"(0), "r"(unit * TILE_ROWS + i * (TILE_ROWS / NPART)),
                        "l"(pol), "n"(TILE_BYTES / NPART) : "memory");
}
__device__ __forceinline__ void put_groups(void* dst, int mode, const float (&o)[6], float tag, float tag2) {
    asm volatile("{\n.reg .pred s, r, t;\n.reg .b128 u, v;\n.reg .b64 a, b;\n"
                 "setp.eq.s32 s|r, %1, 0;\nsetp.eq.s32 t, %1, 2;\n"
                 "@r red.relaxed.gpu.global.add.v4.f32 [%0], {%2,%3,%4,%8};\n"
                 "@t red.relaxed.gpu.global.add.v4.f32 [%0+4096], {%2,%3,%4,%8};\n"
                 "@r red.relaxed.gpu.global.add.v4.f32 [%0+128], {%5,%6,%7,%9};\n"
                 "@t red.relaxed.gpu.global.add.v4.f32 [%0+4224], {%5,%6,%7,%9};\n"
                 "mov.b64 a, {%2, %3};\nmov.b64 b, {%4, %8};\nmov.b128 u, {a, b};\n"
                 "mov.b64 a, {%5, %6};\nmov.b64 b, {%7, %9};\nmov.b128 v, {a, b};\n"
                 "@s st.relaxed.gpu.global.b128 [%0], u;\n@s st.relaxed.gpu.global.b128 [%0+128], v;\n}"
                 :: "l"(dst), "r"(mode), "f"(o[0]), "f"(o[1]), "f"(o[2]), "f"(o[3]), "f"(o[4]), "f"(o[5]), "f"(tag), "f"(tag2) : "memory");
}
__device__ __forceinline__ void tma_box(uint32_t dst, const CUtensorMap* tm, int col, int row, uint32_t bar) {
    asm volatile("cp.async.bulk.tensor.2d.shared::cluster.global.mbarrier::complete_tx::bytes [%0], [%1, {%3, %4}], [%2];"
                 :: "r"(dst), "l"(tm), "r"(bar), "r"(col), "r"(row) : "memory");
}
__device__ __forceinline__ uint32_t lds32(uint32_t addr) {
    uint32_t v;
    asm volatile("ld.shared.u32 %0, [%1];" : "=r"(v) : "r"(addr) : "memory");
    return v;
}
__device__ __forceinline__ void ldsm4(uint32_t (&r)[4], uint32_t addr) {
    asm volatile("ldmatrix.sync.aligned.m8n8.x4.shared.b16 {%0,%1,%2,%3}, [%4];"
                 : "=r"(r[0]), "=r"(r[1]), "=r"(r[2]), "=r"(r[3]) : "r"(addr) : "memory");
}
__device__ __forceinline__ void ldsm4t(uint32_t (&r)[4], uint32_t addr) {
    asm volatile("ldmatrix.sync.aligned.m8n8.x4.trans.shared.b16 {%0,%1,%2,%3}, [%4];"
                 : "=r"(r[0]), "=r"(r[1]), "=r"(r[2]), "=r"(r[3]) : "r"(addr) : "memory");
}
__device__ __forceinline__ void mma16816(float (&c)[4], const uint32_t (&a)[4], uint32_t b0, uint32_t b1) {
    asm volatile("mma.sync.aligned.m16n8k16.row.col.f32.bf16.bf16.f32 {%0,%1,%2,%3}, {%4,%5,%6,%7}, {%8,%9}, {%0,%1,%2,%3};"
                 : "+f"(c[0]), "+f"(c[1]), "+f"(c[2]), "+f"(c[3])
                 : "r"(a[0]), "r"(a[1]), "r"(a[2]), "r"(a[3]), "r"(b0), "r"(b1));
}
__device__ __forceinline__ void mma1688(float (&c)[4], uint32_t a0, uint32_t a1, uint32_t b0) {
    asm volatile("mma.sync.aligned.m16n8k8.row.col.f32.bf16.bf16.f32 {%0,%1,%2,%3}, {%4,%5}, {%6}, {%0,%1,%2,%3};"
                 : "+f"(c[0]), "+f"(c[1]), "+f"(c[2]), "+f"(c[3]) : "r"(a0), "r"(a1), "r"(b0));
}
__device__ __forceinline__ uint4 ld_relaxed_v4(const void* p) {
    uint4 v;
    asm volatile("ld.relaxed.gpu.global.v4.u32 {%0,%1,%2,%3}, [%4];" : "=r"(v.x), "=r"(v.y), "=r"(v.z), "=r"(v.w) : "l"(p) : "memory");
    return v;
}
__device__ __forceinline__ float4 ld_relaxed_f4(const void* p) {
    float4 v;
    asm volatile("ld.relaxed.gpu.global.v4.f32 {%0,%1,%2,%3}, [%4];" : "=f"(v.x), "=f"(v.y), "=f"(v.z), "=f"(v.w) : "l"(p) : "memory");
    return v;
}
__device__ __forceinline__ float2 ld_relaxed_f2(const void* p) {
    float2 v;
    asm volatile("ld.relaxed.gpu.global.v2.f32 {%0,%1}, [%2];" : "=f"(v.x), "=f"(v.y) : "l"(p) : "memory");
    return v;
}
__device__ __forceinline__ float4 ld_relaxed_b128(const void* p) {
    float4 v;
    asm volatile("{\n.reg .b128 t;\n.reg .b64 a, b;\nld.relaxed.gpu.global.b128 t, [%4];\nmov.b128 {a, b}, t;\n"
                 "mov.b64 {%0, %1}, a;\nmov.b64 {%2, %3}, b;\n}" : "=f"(v.x), "=f"(v.y), "=f"(v.z), "=f"(v.w) : "l"(p) : "memory");
    return v;
}
__device__ __forceinline__ void st_relaxed_b128(void* p, float x, float y, float z, float w) {
    asm volatile("{\n.reg .b128 t;\n.reg .b64 a, b;\nmov.b64 a, {%1, %2};\nmov.b64 b, {%3, %4};\nmov.b128 t, {a, b};\n"
                 "st.relaxed.gpu.global.b128 [%0], t;\n}" :: "l"(p), "f"(x), "f"(y), "f"(z), "f"(w) : "memory");
}
__device__ __forceinline__ unsigned ld_acquire(const unsigned* p) {
    unsigned v;
    asm volatile("ld.acquire.gpu.global.u32 %0, [%1];" : "=r"(v) : "l"(p) : "memory");
    return v;
}
__device__ __forceinline__ void st_relaxed(void* p, uint32_t v) {
    asm volatile("st.relaxed.gpu.global.u32 [%0], %1;" :: "l"(p), "r"(v) : "memory");
}
__device__ __forceinline__ void red_f2(float* p, float a, float b) {
    asm volatile("red.relaxed.gpu.global.add.v2.f32 [%0], {%1,%2};" :: "l"(p), "f"(a), "f"(b) : "memory");
}
__device__ __forceinline__ void draw(int& ticket, unsigned* ctr, bool pred) {
    asm volatile("{\n.reg .pred p;\nsetp.ne.u32 p, %2, 0;\n@p atom.relaxed.gpu.global.inc.u32 %0, [%1], 0x7fffffff;\n}"
                 : "+r"(ticket) : "l"(ctr), "r"((uint32_t)pred) : "memory");
}
__device__ __forceinline__ void red_release(unsigned* p) {
    asm volatile("red.release.gpu.global.add.u32 [%0], 1;" :: "l"(p) : "memory");
}
__device__ __forceinline__ uint32_t ld_relaxed_u32(const void* p) {
    uint32_t v;
    asm volatile("ld.relaxed.gpu.global.u32 %0, [%1];" : "=r"(v) : "l"(p) : "memory");
    return v;
}
__device__ __forceinline__ float rcp_approx(float v) {
    float r;
    asm("rcp.approx.ftz.f32 %0, %1;" : "=f"(r) : "f"(v));
    return r;
}
__device__ __forceinline__ float sigmoid_approx(float v) {
    float e;
    asm("ex2.approx.ftz.f32 %0, %1;" : "=f"(e) : "f"(v * -1.4426950408889634f));
    return rcp_approx(1.0f + e);
}
__device__ __forceinline__ float sqrt_approx(float v) {
    float r;
    asm("sqrt.approx.ftz.f32 %0, %1;" : "=f"(r) : "f"(v));
    return r;
}
__device__ __forceinline__ uint2 ld_relaxed_v2(const void* p) {
    uint2 v;
    asm volatile("ld.relaxed.gpu.global.v2.u32 {%0,%1}, [%2];" : "=r"(v.x), "=r"(v.y) : "l"(p) : "memory");
    return v;
}
__device__ __forceinline__ void wait_count(const unsigned* p, unsigned target) {
#pragma unroll 1
    for (int it = 0; it < SPIN_MAX; it++) {
        if (ld_acquire(p) >= target) break;
        __nanosleep(400);
    }
}
__device__ __forceinline__ void wait_row(int bh, float n) {
#pragma unroll 1
    for (int it = 0; it < SPIN_MAX; it++) {
        const float c = ld_relaxed_f2(g_st.lsum[bh]).y;
        if (c >= n) break;
        if (c == 0.f) __nanosleep(600);
    }
}
__device__ __forceinline__ void wait_row_o(int bh, float n) {
    wait_row(bh, n);
    if (bh >= RED0) return;
#pragma unroll 1
    for (int it = 0; it < SPIN_MAX; it++) {
        if (__uint_as_float(ld_relaxed_u32(&g_st.oacc[oidx(bh, 0)].w)) == UPB) break;
        __nanosleep(300);
    }
}
__device__ __forceinline__ void spin_ns(int ns) {
    const long long t0 = clock64();
    while (clock64() - t0 < (long long)ns * 2) {}
}
__device__ __forceinline__ uint32_t pack_bf16(float lo, float hi) {
    uint32_t r;
    asm("cvt.rn.bf16x2.f32 %0, %1, %2;" : "=r"(r) : "f"(hi), "f"(lo));
    return r;
}
__device__ __forceinline__ float bf16r(float v) { return __uint_as_float(pack_bf16(0.f, v)); }
__device__ __forceinline__ uint32_t pack_neg(float lo, float hi) {
    const uint32_t w = pack_bf16(-lo, -hi);
    return w ? w : 0x80008000u;
}
__device__ __forceinline__ float lo_f(uint32_t v) { return __uint_as_float(v << 16); }
__device__ __forceinline__ float hi_f(uint32_t v) { return __uint_as_float(v & 0xffff0000u); }
__device__ __forceinline__ float warp_sum(float v) {
#pragma unroll
    for (int o = 16; o; o >>= 1) v += __shfl_xor_sync(0xffffffffu, v, o);
    return v;
}
__device__ __forceinline__ void layernorm20(float (&v)[20]) {
    float s = 0.f;
#pragma unroll
    for (int i = 0; i < 20; i++) s += v[i];
    const float mean = warp_sum(s) * (1.0f / DM);
    float q = 0.f;
#pragma unroll
    for (int i = 0; i < 20; i++) { const float d = v[i] - mean; q += d * d; }
    const float var = bf16r(warp_sum(q) * (1.0f / DM));
    const float m = bf16r(mean);
    const float rden = 1.0f / bf16r(sqrtf(bf16r(var + 1e-5f)));
#pragma unroll
    for (int i = 0; i < 20; i++) v[i] = bf16r(bf16r(v[i] - m) * rden);
}

__device__ __forceinline__ void moments(float m1, float m2, float& nmean, float& rden) {
    m1 *= 1.0f / DM;
    const float var = bf16r(fmaxf(fmaf(-m1, m1, m2 * (1.0f / DM)), 0.f));
    nmean = bf16r(m1);
    rden = rcp_approx(bf16r(sqrt_approx(bf16r(var + 1e-5f))));
}
__device__ __forceinline__ float sel4(int j, float a, float b, float c, float d) {
    float lo, hi, r;
    asm("{\n.reg .pred p;\nsetp.ne.s32 p, %3, 0;\nselp.f32 %0, %2, %1, p;\n}" : "=f"(lo) : "f"(a), "f"(b), "r"(j & 1));
    asm("{\n.reg .pred p;\nsetp.ne.s32 p, %3, 0;\nselp.f32 %0, %2, %1, p;\n}" : "=f"(hi) : "f"(c), "f"(d), "r"(j & 1));
    asm("{\n.reg .pred p;\nsetp.ne.s32 p, %3, 0;\nselp.f32 %0, %2, %1, p;\n}" : "=f"(r) : "f"(lo), "f"(hi), "r"(j & 2));
    return r;
}
template <typename T> __device__ __forceinline__ void pin(T*& p) { asm volatile("" : "+l"(p)); }
__device__ __forceinline__ void pin(uint32_t& v) { asm volatile("" : "+r"(v)); }
__device__ __forceinline__ void pin(float& v) { asm volatile("" : "+f"(v)); }
__device__ __forceinline__ uint32_t after(uint32_t n, float v) {
    asm volatile("{\n.reg .pred p;\nsetp.eq.u32 p, %1, 0x7fc1a5a5;\n@p add.u32 %0, %0, 32;\n}" : "+r"(n) : "r"(__float_as_uint(v)));
    return n;
}
__device__ __forceinline__ float2 lds64f(uint32_t addr) {
    float2 v;
    asm volatile("ld.shared.v2.f32 {%0,%1}, [%2];" : "=f"(v.x), "=f"(v.y) : "r"(addr) : "memory");
    return v;
}
__device__ __forceinline__ void sts32f(uint32_t addr, float v) { asm volatile("st.shared.f32 [%0], %1;" :: "r"(addr), "f"(v) : "memory"); }
template <int ID> __device__ __forceinline__ void fin_arrive() { asm volatile("bar.arrive %0, 288;" :: "n"(ID) : "memory"); }
template <int ID> __device__ __forceinline__ void fin_sync() { asm volatile("bar.sync %0, 288;" :: "n"(ID) : "memory"); }
template <int ID> __device__ __forceinline__ void fin_sync(uint32_t n) { asm volatile("bar.sync %0, %1;" :: "n"(ID), "r"(n) : "memory"); }
__device__ __forceinline__ float2 sum8(uint32_t addr) {
    float2 t[8];
#pragma unroll
    for (int w = 0; w < 8; w++) t[w] = lds64f(addr + w * 128);
    return make_float2(((t[0].x + t[1].x) + (t[2].x + t[3].x)) + ((t[4].x + t[5].x) + (t[6].x + t[7].x)),
                       ((t[0].y + t[1].y) + (t[2].y + t[3].y)) + ((t[4].y + t[5].y) + (t[6].y + t[7].y)));
}
__device__ __forceinline__ float4 sum4x4(uint32_t addr, int pitch) {
    float4 t[4];
#pragma unroll
    for (int w = 0; w < 4; w++)
        asm volatile("ld.shared.v4.f32 {%0,%1,%2,%3}, [%4];" : "=f"(t[w].x), "=f"(t[w].y), "=f"(t[w].z), "=f"(t[w].w) : "r"(addr + w * pitch) : "memory");
    return make_float4((t[0].x + t[1].x) + (t[2].x + t[3].x), (t[0].y + t[1].y) + (t[2].y + t[3].y),
                       (t[0].z + t[1].z) + (t[2].z + t[3].z), (t[0].w + t[1].w) + (t[2].w + t[3].w));
}
__device__ __forceinline__ void sts64f(uint32_t addr, float x, float y) {
    asm volatile("st.shared.v2.f32 [%0], {%1,%2};" :: "r"(addr), "f"(x), "f"(y) : "memory");
}
__device__ __forceinline__ uint4 lds128(uint32_t addr) {
    uint4 v;
    asm volatile("ld.shared.v4.u32 {%0,%1,%2,%3}, [%4];" : "=r"(v.x), "=r"(v.y), "=r"(v.z), "=r"(v.w) : "r"(addr) : "memory");
    return v;
}
__device__ __forceinline__ void ld_relaxed_v4_if(uint4& v, const void* p, bool pred) {
    asm volatile("{\n.reg .pred p;\nsetp.ne.u32 p, %5, 0;\n@p ld.relaxed.gpu.global.v4.u32 {%0,%1,%2,%3}, [%4];\n}"
                 : "+r"(v.x), "+r"(v.y), "+r"(v.z), "+r"(v.w) : "l"(p), "r"((uint32_t)pred) : "memory");
}
__device__ __forceinline__ void sts128f(uint32_t addr, float x, float y, float z, float w) {
    asm volatile("st.shared.v4.f32 [%0], {%1,%2,%3,%4};" :: "r"(addr), "f"(x), "f"(y), "f"(z), "f"(w) : "memory");
}
template <int NJ>
__device__ __forceinline__ void load_o(uint32_t (&ob)[3 * NJ][2], int bh, int J0, int j) {
    float4 v[NJ][4];
    float2 l;
#pragma unroll 1
    for (int it = 0; it < SPIN_MAX; it++) {
#pragma unroll
        for (int J = 0; J < NJ; J++) {
#pragma unroll
            for (int e = 0; e < 4; e++) v[J][e] = ld_relaxed_f4(&g_st.oacc[oidx(bh, j)] + oidx(0, (J0 + J) * 16 + e * 4));
        }
        l = ld_relaxed_f2(g_st.lsum[bh]);
        bool ok = l.y == UPB;
#pragma unroll
        for (int J = 0; J < NJ; J++) {
#pragma unroll
            for (int e = 0; e < 4; e++) ok &= v[J][e].w == UPB;
        }
        if (__all_sync(0xffffffffu, ok)) break;
    }
    const float rl = __fdividef(1.0f, l.x);
#pragma unroll
    for (int J = 0; J < NJ; J++) {
        ob[3 * J][0] = pack_bf16(v[J][0].x * rl, v[J][1].x * rl);     ob[3 * J][1] = pack_bf16(v[J][2].x * rl, v[J][3].x * rl);
        ob[3 * J + 1][0] = pack_bf16(v[J][0].y * rl, v[J][1].y * rl); ob[3 * J + 1][1] = pack_bf16(v[J][2].y * rl, v[J][3].y * rl);
        ob[3 * J + 2][0] = pack_bf16(v[J][0].z * rl, v[J][1].z * rl); ob[3 * J + 2][1] = pack_bf16(v[J][2].z * rl, v[J][3].z * rl);
    }
}
__device__ __forceinline__ int near_side(uint32_t sb) {
    uint32_t v;
    asm volatile("ld.volatile.shared.u32 %0, [%1];" : "=r"(v) : "r"(sb + SM_SIDE) : "memory");
    return v;
}
__device__ __forceinline__ void aux_sync() { asm volatile("bar.sync 1, 256;" ::: "memory"); }

__global__ void __launch_bounds__(NTHREADS, 1)
fused_decode_kernel(const __grid_constant__ Params p) {
    extern __shared__ __align__(1024) unsigned char smem[];
    const uint32_t sb = s2u(smem);
    const int tid = threadIdx.x, warp = __shfl_sync(0xffffffffu, tid >> 5, 0), lane = tid & 31;
    const int cta = blockIdx.x;
    constexpr int grid = NCTAS;
    const int g = lane >> 2, j = lane & 3;

    TS(0);
    if (tid == 128) {
        mbar_init(sb + BAR_WQ, 1);
        asm volatile("fence.mbarrier_init.release.cluster;" ::: "memory");
        asm volatile("fence.proxy.async.shared::cta;" ::: "memory");
        if (cta < NQ_CTAS) {
            mbar_expect_tx(sb + BAR_WQ, 61440);
#pragma unroll 1
            for (int i = 0; i < 4; i++) tma_box(sb + SM_W + i * 15360, &p.wq, cta * 48, i * 160, sb + BAR_WQ);
        }
    } else if (tid == 160) {
        mbar_init(sb + BAR_WO, 1);
        sts32f(sb + SM_SIDE, 0.f);
        asm volatile("fence.mbarrier_init.release.cluster;" ::: "memory");
        asm volatile("fence.proxy.async.shared::cta;" ::: "memory");
    } else if (tid >= 192 && tid < 200 + NWORK * NPART) {
        mbar_init(sb + BAR_FW + (tid - 192) * 8, 1);
        asm volatile("fence.mbarrier_init.release.cluster;" ::: "memory");
        asm volatile("fence.proxy.async.shared::cta;" ::: "memory");
    }
    __syncthreads();
    if (warp >= NAUX + NWORK) {
        const int fw = warp - (NAUX + NWORK), fi = ffn_slice(cta);
        if (fw == 0) {
            if (cta < NQ_CTAS) {
#pragma unroll
                for (int i = lane; i < STATE_V4; i += 32)
                    if (cta * STATE_V4 + i < (int)(sizeof(State) / 16)) reinterpret_cast<uint4*>(&g_st)[cta * STATE_V4 + i] = make_uint4(0u, 0u, 0u, 0u);
                __syncwarp();
                if (lane == 0) red_release(g_cnt_z);
            }
            if (lane == 0) { TS2(2); wait_count(g_cnt_z, NQ_CTAS); TS2(29); }
            __syncwarp();
            asm volatile("bar.arrive 2, %0;" :: "n"((NWORK + 2) * 32) : "memory");
            fin_arrive<3>();
        } else {
            asm volatile("bar.sync 2, %0;" :: "n"((NWORK + 2) * 32) : "memory");
            if (lane == 0) {
                uint32_t* ctr = &g_st.hx.w[0][PROBE];
                uint32_t best[2] = {~0u, ~0u};
#pragma unroll 1
                for (int i = 0; i < NPROBE; i++) {
#pragma unroll
                    for (int c = 0; c < 2; c++) {
                        uint32_t t0 = clock(), t1 = t0, v;
                        asm volatile("atom.relaxed.gpu.global.inc.u32 %0, [%1], 0x7fffffff;" : "=r"(v) : "l"(ctr + c * 1024) : "memory");
                        asm volatile("{\n.reg .pred p;\nsetp.ne.u32 p, %1, 0xffffffff;\n@p mov.u32 %0, %%clock;\n}" : "+r"(t1) : "r"(v) : "memory");
                        best[c] = min(best[c], t1 - t0);
                    }
                    __nanosleep(1000);
                }
                sts32f(sb + SM_SIDE, __uint_as_float((best[1] < best[0]) ^ SIDE_XOR));
            }
            __syncwarp();
        }
        int job = cta;
        auto sum_rows = [&](int row_end) {
#pragma unroll 1
            for (; job < 8 * min(row_end, RED0); job += NCTAS) {
                const int row = job >> 3, grp = (job & 7) * 8 + (lane & 7);
                if (lane == 0) wait_row(row, UPB);
                __syncwarp();
                const float4* src = &g_ring[row % RING][lane >> 3][grp];
                float sx = 0.f, sy = 0.f, sz = 0.f;
#pragma unroll 1
                for (int i = 0; i < 2; i++, src += 64 * 64) {
                    float4 v[16];
#pragma unroll 1
                    for (int it = 0; it < SPIN_MAX; it++) {
                        bool ok = true;
#pragma unroll
                        for (int k = 0; k < 16; k++) v[k] = ld_relaxed_b128(src + k * 4 * 64);
#pragma unroll
                        for (int k = 0; k < 16; k++) ok &= v[k].w == (float)(row + 1);
                        if (__all_sync(0xffffffffu, ok)) break;
                    }
#pragma unroll
                    for (int k = 0; k < 16; k++) { sx += v[k].x; sy += v[k].y; sz += v[k].z; }
                }
#pragma unroll
                for (int o = 8; o < 32; o <<= 1) {
                    sx += __shfl_xor_sync(0xffffffffu, sx, o); sy += __shfl_xor_sync(0xffffffffu, sy, o); sz += __shfl_xor_sync(0xffffffffu, sz, o);
                }
                if (lane < 8) st_relaxed_b128(&g_st.oacc[oidx(row, grp)], sx, sy, sz, UPB);
            }
        };
        const int ho0 = lane / 20 * 256 + lane % 20 * 4, ho1 = (lane + 32) / 20 * 256 + (lane + 32) % 20 * 4, ho2 = 3 * 256 + 16 + 2 * lane;
        uint32_t wr[10] = {};
        float wsum = 0.f;
        if (is_g(cta) && fw == 0) {
#pragma unroll
            for (int i = 0; i < 10; i++) {
                const int w = 4 * lane + 128 * (i >> 2) + (i & 3) - (i >= 8 ? 2 * lane : 0);
                wr[i] = *reinterpret_cast<const uint32_t*>(p.wr + (w >> 4) * 32 + (w & 3) * 8 + ((w >> 1) & 6));
                wsum += lo_f(wr[i]) + hi_f(wr[i]);
            }
            wsum = warp_sum(wsum);
        }
        const int fb = lane >> 3, fg = lane & 7;
        if (fw == 0) {
#pragma unroll
            for (int i = lane; i < DM / 2; i += 32) sts32f(sb + SM_X + 4 * HPITCH + i * 4, __uint_as_float(0x3f803f80u));
        }
        float nmean = 0.f, rden = 0.f, sig = 0.f;
#pragma unroll 1
        for (int b = 0; b < NB; b++) {
            const bool ffn = b >= NB - 2;
            if (fw == 0) {
                sum_rows((b + 1) * NH);
                if (b == NB - 1) asm volatile("bar.arrive 8, 64;" ::: "memory");
            } else if (b == NB - 1) {
                asm volatile("bar.sync 8, 64;" ::: "memory");
                if (lane == 0) {
                    uint32_t t0 = 0, now;
#pragma unroll 1
                    for (int it = 0; it < SPIN_MAX; it++) {
                        t0 = ld_relaxed_u32(g_st.fw_time);
                        if (t0) break;
                        __nanosleep(400);
                    }
                    asm volatile("fence.proxy.async.shared::cta;" ::: "memory");
#pragma unroll 1
                    for (int it = 0; it < SPIN_MAX; it++) {
                        asm volatile("mov.u32 %0, %%globaltimer_lo;" : "=r"(now));
                        if ((int)(now - t0) >= FW_AT_NS) break;
                    }
                    TS2(9);
                    uint32_t t = clock() + (is_f(cta) ? (fi & 1) * FW_STAG : FW_MID + (fi & 3) * (FW_GAP2 / 4));
#pragma unroll 1
                    for (int i = 0; i < 8; i++) {
                        const uint32_t bar = sb + BAR_FW + i * 8;
                        while ((int)(clock() - t) < 0) {}
                        if (is_f(cta)) {
                            mbar_expect_tx(bar, 10240);
                            tma_box(sb + SM_W + i * 10240, (i & 1) ? &p.wu : &p.wg, fi * 32, (i >> 1) * 160, bar);
                            t += FW_GAP;
                        } else if (is_g(cta)) {
                            mbar_expect_tx(bar, 6144);
                            asm volatile("cp.async.bulk.tensor.4d.shared::cluster.global.mbarrier::complete_tx::bytes [%0], [%1, {%3, %4, %4, %5}], [%2];"
                                         :: "r"(sb + SM_W + i * 6144), "l"(&p.wd), "r"(bar), "r"(fi * 16), "r"(0), "r"(i * 12) : "memory");
                            t += FW_GAP2;
                        }
                    }
                }
                __syncwarp();
            }
            if (fw == 0 && cta >= NE_CTAS) {
                const int lc = cta - NE_CTAS, col = lc * 32 + 2 * (lane & 15);
                const uint32_t xv = *reinterpret_cast<const uint32_t*>(p.x + b * DM + col);
                uint32_t* dst = &(ffn ? g_st.hx.w : g_st.lx.w + 2)[lane >> 4][(b & 1) * 128 + lc / 5 * 256 + lc % 5 * 16 + (col & 6) * 2 + ((col >> 3) & 3)];
                uint32_t part = sb + SM_RED + (lane & 15) * 8;
                if (lane == 0) wait_row(b * NH + 28, 1);
                __syncwarp();
                float4 early;
#pragma unroll 1
                for (int it = 0; it < SPIN_MAX; it++) {
                    early = ld_relaxed_f4(&g_st.attn[b][col]);
                    if (__all_sync(0xffffffffu, early.y == NE_CTAS / 4 && early.w == NE_CTAS / 4)) break;
                }
                if (early.x != 1.2345f && lane == 0) TS2(6);
                CK(1, __float_as_uint(early.x));
                float x0 = lo_f(xv), x1 = hi_f(xv);
                pin(dst); pin(part); pin(x0); pin(x1);
                fin_sync<4>();
                CK(2, lds32(sb + SM_RED));
                const float2 late = sum8(part);
                const uint32_t hv = pack_neg(x0 + bf16r(early.x + late.x), x1 + bf16r(early.z + late.y));
                st_relaxed(dst, hv);
                if (ffn) st_relaxed(dst + 2048, hv);
                CK(3, 0);
                fin_arrive<5>();
            }
            if (fw == 0 && (is_g(cta) || (is_f(cta) && b < NB - 1))) {
                const uint32_t* src = &(ffn ? g_st.hx.w : g_st.lx.w + 2)[near_side(sb) ^ (ffn && (fi & 1) ? 3 : 0)][(b & 1) * 128];
                const uint32_t hrow = sb + SM_X + b * HPITCH;
                if (lane == 0) wait_row(b * NH + NH - 1, UPB);
                __syncwarp();
                uint4 h0, h1;
                uint2 h2;
#pragma unroll 1
                for (int it = 0; it < SPIN_MAX; it++) {
                    h0 = ld_relaxed_v4(src + ho0);
                    h1 = ld_relaxed_v4(src + ho1);
                    h2 = ld_relaxed_v2(src + ho2);
                    const uint32_t lo = min(min(min(h0.x, h0.y), min(h0.z, h0.w)), min(min(min(h1.x, h1.y), min(h1.z, h1.w)), min(h2.x, h2.y)));
                    if (__all_sync(0xffffffffu, lo != 0)) break;
                    if (b < NB - 1) __nanosleep(500);
                }
                asm volatile("st.shared.v4.u32 [%0], {%1,%2,%3,%4};" :: "r"(hrow + lane * 16), "r"(h0.x), "r"(h0.y), "r"(h0.z), "r"(h0.w) : "memory");
                asm volatile("st.shared.v4.u32 [%0], {%1,%2,%3,%4};" :: "r"(hrow + 512 + lane * 16), "r"(h1.x), "r"(h1.y), "r"(h1.z), "r"(h1.w) : "memory");
                asm volatile("st.shared.v2.u32 [%0], {%1,%2};" :: "r"(hrow + 1024 + lane * 8), "r"(h2.x), "r"(h2.y) : "memory");
                if (ffn) fin_arrive<7>();
                CK(4, h0.x);
                if (is_g(cta)) {
                    const uint32_t hw[10] = {h0.x, h0.y, h0.z, h0.w, h1.x, h1.y, h1.z, h1.w, h2.x, h2.y};
                    float m1 = 0.f, m2 = 0.f, rr = 0.f;
#pragma unroll
                    for (int i = 0; i < 10; i++) {
                        const float v0 = lo_f(hw[i]), v1 = hi_f(hw[i]);
                        m1 += v0 + v1;
                        m2 = fmaf(v0, v0, fmaf(v1, v1, m2));
                        rr = fmaf(v0, lo_f(wr[i]), fmaf(v1, hi_f(wr[i]), rr));
                    }
                    m1 = warp_sum(m1); m2 = warp_sum(m2); rr = warp_sum(rr);
                    if (fb == b) {
                        moments(m1, m2, nmean, rden);
                        sig = bf16r(sigmoid_approx(bf16r((nmean * wsum - rr) * rden)));
                    }
                    __syncwarp();
                    if (ffn) {
                        const int gi = fi, yj = 2 * (fb & 1) + (fb >> 1);
                        uint32_t ypart = sb + SM_RED2 + yj * 128 + ((fg + 2 * yj) & 7) * 16;
                        __nv_bfloat16* out = p.out + fb * DM + gi * 16 + fg;
                        const float2 hw2 = lds64f(sb + SM_X + fb * HPITCH + ((gi >> 1) * 16 + (fg & 6) * 2 + (gi & 1) * 2) * 4);
                        const uint32_t w0 = __float_as_uint(hw2.x), w1 = __float_as_uint(hw2.y);
                        float nh0 = (fg & 1) ? hi_f(w0) : lo_f(w0), nh1 = (fg & 1) ? hi_f(w1) : lo_f(w1);
                        float ln0 = bf16r(bf16r(nmean - nh0) * rden), ln1 = bf16r(bf16r(nmean - nh1) * rden);
                        pin(ypart); pin(out);
                        fin_sync<6>(after(after(after(288, sig), ln0), ln1));
                        CK(10, lds32(ypart));
                        const float4 ya = sum4x4(ypart, 512), yb = sum4x4(ypart + 2048, 512);
                        const float4 y = make_float4(ya.x + yb.x, ya.y + yb.y, ya.z + yb.z, ya.w + yb.w);
                        const float y0 = -(((fb & 1) ? y.y : y.x) + __shfl_xor_sync(0xffffffffu, (fb & 1) ? y.x : y.y, 8));
                        const float y1 = -(((fb & 1) ? y.w : y.z) + __shfl_xor_sync(0xffffffffu, (fb & 1) ? y.z : y.w, 8));
                        const uint32_t ov = pack_bf16(bf16r(ln0 + bf16r(bf16r(y0) * sig)) - nh0, bf16r(ln1 + bf16r(bf16r(y1) * sig)) - nh1);
                        if (b == NB - 1) {
                            asm volatile("st.global.u16 [%0], %1;" :: "l"(out), "h"((unsigned short)(ov & 0xffffu)) : "memory");
                            asm volatile("st.global.u16 [%0], %1;" :: "l"(out + 8), "h"((unsigned short)(ov >> 16)) : "memory");
                        }
                        CK(11, 0);
                        if (lane == 0) TS2(13);
                    }
                }
            }
            if (is_f(cta) && ffn) {
                const int ks = (2 * fi + fw) % 12;
                uint32_t* dst = &g_st.ax[ks >> 2].w[(~b & 1) * 2][((fi / 6) * 32 + ((ks & 1) * 4 + fb) * 4 + (fg & 3)) * 4 + (ks & 2) + (fg >> 2)];
                uint32_t part = sb + SM_RED + fw * 2560 + fb * 128 + ((fg + (fb & 2)) & 7) * 16;
                uint32_t psum = sb + SM_RED + fw * 2560 + 4 * 128 + ((fg + 4) & 7) * 16;
                pin(dst); pin(part); pin(psum);
                asm volatile("bar.sync 9, 320;" ::: "memory");
                const float4 m = sum4x4(sb + SM_RED + 5120 + fb * 64, 16);
                moments(m.x + m.z, m.y + m.w, nmean, rden);
                CK(5, __float_as_uint(rden));
                fin_sync<4>(after(320, rden));
                CK(6, lds32(part));
                const float4 d = sum4x4(part, 640), cs = sum4x4(psum, 640);
                const float g0 = bf16r(fmaf(nmean, cs.x, -d.x) * rden), g1 = bf16r(fmaf(nmean, cs.y, -d.y) * rden);
                const float u0 = bf16r(fmaf(nmean, cs.z, -d.z) * rden), u1 = bf16r(fmaf(nmean, cs.w, -d.w) * rden);
                const uint32_t av = pack_neg(bf16r(g0 * sigmoid_approx(g0)) * u0, bf16r(g1 * sigmoid_approx(g1)) * u1);
                st_relaxed(dst, av);
                st_relaxed(dst + 1024, av);
                CK(7, 0);
            }
        }
        if (cta == 0 && tid == (NAUX + NWORK) * 32) { g_work[0] = 0; g_work[32] = 0; g_cnt_z[0] = 0; }
        return;
    }
    if (warp >= NAUX) {
        const int wk = warp - NAUX;
        const uint32_t bar = sb + BAR_KV + wk * (NPART * 8);
        const uint32_t buf = sb + SM_KV + wk * TILE_BYTES;
        uint64_t pol;
        asm volatile("createpolicy.fractional.L2::evict_first.b64 %0, 1.0;" : "=l"(pol));
        const int nstatic = NWORK * grid;
        constexpr int POOL0 = NUNITS - NPOOL;
        int uk = wk * grid + cta;
        if (K0_DELAY_NS) spin_ns(K0_DELAY_NS);
        __syncwarp();
        request_tile(buf, &p.k, uk, bar, pol);
        if (lane == 0) {
            if (wk == 0) {
                const uint32_t wbar = sb + BAR_WO;
                spin_ns(WO_AT_NS - K0_DELAY_NS);
                mbar_expect_tx(wbar, cta < NE_CTAS ? 61440 : 49152);
#pragma unroll 1
                for (int i = 0; i < (cta < NE_CTAS ? 5 : 4); i++) {
                    if (cta < NE_CTAS) tma_box(sb + SM_A + i * 12288, &p.wo, (cta & 3) * 160 + i * 32, (cta >> 2) * DH, wbar);
                    else tma_box(sb + SM_A + i * 12288, &p.wo, (cta - NE_CTAS) * 32, (28 + i) * DH, wbar);
                }
            }
        }
        __syncwarp();
        uint32_t koff[3], voff[3];
        {
            const int r = lane & 7, hf = (lane >> 3) & 1;
            const int kkey = hf ? 8 + (r ^ 1) : r;
            const int vh = lane >> 4;
            const int vkey = ((r & 1) ? 8 : 0) + (vh ? (r ^ 1) : r);
#pragma unroll
            for (int b = 0; b < 3; b++) {
                const int rk = 3 * kkey + b, rv = 3 * vkey + b;
                koff[b] = buf + rk * 128 + (((lane >> 4) ^ (rk & 7)) << 4);
                voff[b] = buf + rv * 128 + ((hf ^ (rv & 7)) << 4);
            }
        }
        uint32_t phase = 0;
        uint4 qf[6];
        auto load_q = [&](int u) {
            const uint32_t* q = &g_early[u / UPB].q[j * 4];
#pragma unroll
            for (int i = 0; i < 6; i++) qf[i] = ld_relaxed_v4(q + i * 16);
        };
        load_q(uk);
        int uq[LAG];
        uint32_t sq[LAG];
#pragma unroll
        for (int i = 0; i < LAG; i++) { uq[i] = -1; sq[i] = 0; }
        uint4 mv = make_uint4(0u, 0u, 0u, 0u);
        float freed = UPB;
        while (true) {
            const int uv = uq[0];
            uint32_t sv = sq[0];
#pragma unroll
            for (int i = 0; i + 1 < LAG; i++) { uq[i] = uq[i + 1]; sq[i] = sq[i + 1]; }
            uq[LAG - 1] = uk;
            if (uk < NUNITS) {
                PH(7);
#pragma unroll 1
                for (int it = 0; it < SPIN_MAX; it++) {
                    uint32_t lo = 0xffffffffu;
#pragma unroll
                    for (int i = 0; i < 6; i++) lo = min(min(lo, min(qf[i].x, qf[i].y)), min(qf[i].z, qf[i].w));
                    if (__all_sync(0xffffffffu, lo != 0)) break;
                    __nanosleep(250);
                    load_q(uk);
                }
#pragma unroll
                for (int t = 0; t < NPART; t++) mbar_wait(bar + t * 8, phase);
                phase ^= 1;
                PH(0); ARR();
                TSI(0, 16); TSI(1, 18);
                float acc[2][4][4] = {};
#pragma unroll
                for (int ks = 0; ks < 12; ks++) {
                    const uint4 qq = qf[ks >> 1];
                    const uint32_t b0 = (ks & 1) ? qq.z : qq.x, b1 = (ks & 1) ? qq.w : qq.y;
#pragma unroll
                    for (int mt = 0; mt < 4; mt++) {
                        uint32_t a[4];
                        ldsm4(a, (koff[ks >> 2] ^ ((ks & 3) << 5)) + mt * 6144);
                        mma16816(acc[ks & 1][mt], a, b0, b1);
                    }
                }
                PH(1);
                TSI(0, 17); TSI(1, 19);
                if (uv < NUNITS) request_tile(buf, uv >= 0 ? &p.v : &p.k, uv >= 0 ? uv : uk + nstatic, bar, pol);
                const float sa = sel4(j, acc[0][0][0], acc[0][1][0], acc[0][2][0], acc[0][3][0]) + sel4(j, acc[1][0][0], acc[1][1][0], acc[1][2][0], acc[1][3][0]);
                const float sc = sel4(j, acc[0][0][2], acc[0][1][2], acc[0][2][2], acc[0][3][2]) + sel4(j, acc[1][0][2], acc[1][1][2], acc[1][2][2], acc[1][3][2]);
                const uint32_t raw = pack_bf16(sa, sc);
                const float scale = -0.07216878364870322f;
                const uint32_t sk = pack_bf16(lo_f(raw) * scale, hi_f(raw) * scale);
                sq[LAG - 1] = sk;
                if (uk >= POOL0) st_relaxed(&g_st.score[uk - POOL0][lane], sk ? sk : 0x80008000u);
                int a = (int)(sk << 16), b = (int)(sk & 0xffff0000u);
                a ^= (a >> 31) & 0x7fff0000; b ^= (b >> 31) & 0x7fff0000;
                const int mx = __reduce_max_sync(0xffffffffu, max(a, b));
                if (lane == 0) st_relaxed(&g_early[uk / UPB].umax[uk % UPB], (uint32_t)mx | 1u);
            }
            if (uv < 0) {
                uk += nstatic;
                load_q(uk);
                continue;
            }
            if (uv >= NUNITS) break;
            const int bh = uv / UPB;
#pragma unroll 1
            for (int it = 0; it < SPIN_MAX; it++) {
                if (__all_sync(0xffffffffu, (mv.x & mv.y & mv.z & mv.w & 1u) && (uv < POOL0 || sv != 0) && freed == UPB)) break;
                mv = ld_relaxed_v4(&g_early[bh].umax[lane * 4]);
                if (bh >= RING && bh < RED0) freed = __uint_as_float(ld_relaxed_u32(&g_st.oacc[oidx(bh - RING, (lane & 7) * 8)].w));
                if (uv >= POOL0) sv = ld_relaxed_u32(&g_st.score[uv - POOL0][lane]);
            }
            PH(2);
            int un = NUNITS, vn = 0;
            draw(un, g_work, uk < NUNITS && lane == 0);
            uint32_t tdraw;
            asm volatile("mov.u32 %0, %%globaltimer_lo;" : "=r"(tdraw));
            draw(vn, g_work + 32, uq[0] >= POOL0 && lane == 0);
            int mx = __reduce_max_sync(0xffffffffu, max(max((int)mv.x, (int)mv.y), max((int)mv.z, (int)mv.w))) & 0xffff0000;
            mx ^= (mx >> 31) & 0x7fff0000;
            const float m = __int_as_float(mx);
            const float l2e = 1.4426950408889634f;
            const uint32_t pp = pack_bf16(exp2f((lo_f(sv) - m) * l2e), exp2f((hi_f(sv) - m) * l2e));
            uint32_t pb[8];
#pragma unroll
            for (int t = 0; t < 4; t++) {
                pb[2 * t] = __shfl_sync(0xffffffffu, pp, 8 * j + t);
                pb[2 * t + 1] = __shfl_sync(0xffffffffu, pp, 8 * j + 4 + t);
            }
            float lacc[4] = {};
            const uint32_t ones[4] = {0x3f803f80u, 0x3f803f80u, 0x3f803f80u, 0x3f803f80u};
#pragma unroll
            for (int t = 0; t < 4; t++) mma16816(lacc, ones, pb[2 * t], pb[2 * t + 1]);
            if (uv < nstatic) {
                asm volatile("bar.sync 2, %0;" :: "n"((NWORK + 2) * 32) : "memory");
                TSW(3);
            }
            const int grp = 16 * j + 4 * (g & 1) + (g >> 1);
            uint32_t mode = (bh >= RED0) + (bh >= NBH - 4);
            float tag = mode ? 1.f : (float)(bh + 1), tag2 = tag;
            void* dst = mode == 0 ? (void*)&g_ring[bh % RING][uv % UPB][grp] :
                        mode == 1 ? (void*)&g_st.oacc[oidx(bh, grp)] : (void*)&g_st.ox[uv % OREP].w[0][oidx(bh & 3, grp) * 4];
            if (mode == 2 && lane < 2) red_f2(reinterpret_cast<float*>(&g_st.lx.w[lane][(bh & 3) * 256]), lacc[0], 1.f);
            un = __shfl_sync(0xffffffffu, un, 0) + (LAG + 1) * nstatic;
            vn = __shfl_sync(0xffffffffu, vn, 0);
            if (uq[0] >= POOL0) uq[0] = POOL0 + vn;
            if (vn == FW_TICKET && lane == 0) st_relaxed(g_st.fw_time, tdraw | 1u);
            pin(dst); pin(mode); pin(tag); pin(tag2); pin(voff[0]); pin(voff[1]); pin(voff[2]);
            PH(3);
            float acc[12][4] = {};
#pragma unroll
            for (int t = 0; t < 4; t++) {
                if (t % (4 / NPART) == 0) mbar_wait(bar + t / (4 / NPART) * 8, phase);
                if (t == 4 - 4 / NPART) { PH(4); ARR(); CK(12, lds32(buf)); }
#pragma unroll
                for (int mt = 0; mt < 12; mt++) {
                    uint32_t a[4];
                    ldsm4t(a, (voff[mt >> 2] ^ ((mt & 3) << 5)) + t * 6144);
                    mma16816(acc[mt], a, pb[2 * t], pb[2 * t + 1]);
                }
            }
            phase ^= 1;
            PH(5);
            if (lane == 0) PROG(un);
            if (un < NUNITS || uq[0] < NUNITS) request_tile(buf, un < NUNITS ? &p.k : &p.v, un < NUNITS ? un : uq[0], bar, pol);
            float o[6];
#pragma unroll
            for (int e = 0; e < 6; e++) {
                const int q = e % 3, c = (e / 3) * 2;
                o[e] = sel4(j, acc[q][c], acc[3 + q][c], acc[6 + q][c], acc[9 + q][c]);
            }
            put_groups(dst, mode, o, tag, tag2);
            CK(13, 0);
            if (un < NUNITS) load_q(un);
            if (lane == 0) red_f2(&g_st.lsum[bh][0].x, lacc[0], 1.f);
            PH(6);
            if (uq[0] >= NUNITS && un >= NUNITS) break;
            uk = un;
            if (uq[0] < NUNITS) {
                const int nb = uq[0] / UPB;
                mv = ld_relaxed_v4(&g_early[nb].umax[lane * 4]);
                freed = nb >= RING && nb < RED0 ? __uint_as_float(ld_relaxed_u32(&g_st.oacc[oidx(nb - RING, (lane & 7) * 8)].w)) : UPB;
                if (uq[0] >= POOL0) sq[0] = ld_relaxed_u32(&g_st.score[uq[0] - POOL0][lane]);
            }
        }
        TSW(4 + wk);
        return;
    }

    __nv_bfloat16* xs = reinterpret_cast<__nv_bfloat16*>(smem + SM_X);
    float* red = reinterpret_cast<float*>(smem + SM_RED);
    const int frow = (lane & 7) + ((lane >> 4) << 3), fcol = (lane >> 3) & 1;
    const uint32_t f32b = sb + (frow * 2 + (fcol ^ ((frow >> 2) & 1))) * 16;
    const uint32_t f64b = sb + (frow * 4 + (fcol ^ ((frow >> 1) & 3))) * 16;
    if (cta < NQ_CTAS) {
        uint2 xr[5];
        if (warp < NB) {
#pragma unroll
            for (int i = 0; i < 5; i++) xr[i] = *reinterpret_cast<const uint2*>(p.x + warp * DM + i * 128 + lane * 4);
        }
        TS(26);
        if (warp < NB) {
            float v[20];
#pragma unroll
            for (int i = 0; i < 5; i++) {
                v[4 * i] = lo_f(xr[i].x); v[4 * i + 1] = hi_f(xr[i].x); v[4 * i + 2] = lo_f(xr[i].y); v[4 * i + 3] = hi_f(xr[i].y);
            }
            layernorm20(v);
#pragma unroll
            for (int i = 0; i < 5; i++)
                *reinterpret_cast<uint2*>(xs + warp * XPITCH + i * 128 + lane * 4) =
                    make_uint2(pack_bf16(v[4 * i], v[4 * i + 1]), pack_bf16(v[4 * i + 2], v[4 * i + 3]));
        }
        TS(27);
        aux_sync();
        mbar_wait(sb + BAR_WQ, 0);
        TS(1);
        const uint32_t xfrag = sb + SM_X + ((g & 3) * XPITCH + 2 * j) * 2;
        float acc[3][4] = {};
#pragma unroll
        for (int s = 0; s < 5; s++) {
            const int ks = warp * 5 + s;
            const uint32_t b0 = lds32(xfrag + ks * 32), b1 = lds32(xfrag + ks * 32 + 16);
            const int row = ks * 16 + frow;
#pragma unroll
            for (int mt = 0; mt < 3; mt++) {
                uint32_t a[4];
                ldsm4t(a, sb + SM_W + (row * 6 + 2 * mt + fcol) * 16);
                mma16816(acc[mt], a, b0, b1);
            }
        }
        if (j < 2) {
#pragma unroll
            for (int mt = 0; mt < 3; mt++) {
                *reinterpret_cast<float2*>(red + (warp * 48 + mt * 16 + g) * 4 + 2 * j) = make_float2(acc[mt][0], acc[mt][1]);
                *reinterpret_cast<float2*>(red + (warp * 48 + mt * 16 + 8 + g) * 4 + 2 * j) = make_float2(acc[mt][2], acc[mt][3]);
            }
        }
        aux_sync();
        if (tid < 96) {
            const int b = tid & 3, cp = tid >> 2;
            float s0 = 0.f, s1 = 0.f;
#pragma unroll
            for (int w = 0; w < 8; w++) { s0 += red[(w * 48 + 2 * cp) * 4 + b]; s1 += red[(w * 48 + 2 * cp + 1) * 4 + b]; }
            const int h = cta >> 2, d = (cta & 3) * 48 + 2 * cp;
            const int ch = d >> 3, jj = (d & 7) >> 1;
            st_relaxed(&g_early[b * NH + h].q[(ch >> 2) * 16 + jj * 4 + (ch & 3)], pack_neg(s0, s1));
        }
        TS(28);
    }
    fin_sync<3>();
    mbar_wait(sb + BAR_WO, 0);
    TS(7);
    uint32_t part = sb + SM_RED + (warp * 32 + 8 * j + g) * 4;

#pragma unroll 1
    for (int b = 0; b < NB; b++) {
        if (cta >= NE_CTAS) {
            uint32_t a[6][2][4];
#pragma unroll
            for (int s = 0; s < 6; s++) {
#pragma unroll
                for (int mt = 0; mt < 2; mt++) ldsm4t(a[s][mt], (f64b ^ (mt * 32)) + SM_A + (warp * 6 + s) * 1024);
            }
            const int bh = b * NH + 28 + (warp >> 1);
            const int side = near_side(sb) ^ 1;
            const void* osrc[OREP];
#pragma unroll
            for (int c = 0; c < OREP; c++)
                osrc[c] = b == NB - 1 ? (const void*)&g_st.ox[c].w[side][oidx(bh & 3, (warp & 1) * 32 + lane) * 4] : &g_st.oacc[oidx(bh, (warp & 1) * 32 + lane)];
            const void* lsrc = b == NB - 1 ? (const void*)&g_st.lx.w[side][(bh & 3) * 256] : g_st.lsum[bh];
            if (lane == 0) wait_row_o(bh, 1);
            __syncwarp();
            float2 lv;
#pragma unroll 1
            for (int it = 0; it < SPIN_MAX; it++) {
                lv = ld_relaxed_f2(lsrc);
                if (lv.y == UPB) break;
            }
            __syncwarp();
            float rl = rcp_approx(lv.x) * (b == NB - 1 ? 1.f : 1.f / OREP), full = b == NB - 1 ? UPB : UPB * OREP;
            float4 ov;
            pin(part); pin(rl); pin(full);
#pragma unroll 1
            for (int it = 0; it < SPIN_MAX; it++) {
                float4 oc[OREP];
#pragma unroll
                for (int c = 0; c < OREP; c++) oc[c] = ld_relaxed_f4(osrc[c]);
                ov = oc[0];
#pragma unroll
                for (int c = 1; c < OREP; c++) { ov.x += oc[c].x; ov.y += oc[c].y; ov.z += oc[c].z; ov.w += oc[c].w; }
                if (__all_sync(0xffffffffu, ov.w == full)) break;
            }
            CK(0, __float_as_uint(ov.x));
            if (ov.x != 1.2345f && warp == 7) TSW(14);
            const float px = __shfl_xor_sync(0xffffffffu, ov.x, 4), py = __shfl_xor_sync(0xffffffffu, ov.y, 4),
                        pz = __shfl_xor_sync(0xffffffffu, ov.z, 4);
            const uint32_t w[3] = {pack_bf16(ov.x * rl, px * rl), pack_bf16(ov.y * rl, py * rl), pack_bf16(ov.z * rl, pz * rl)};
            float acc[2][2][4] = {};
#pragma unroll
            for (int s = 0; s < 6; s++) {
                const uint32_t b0 = __shfl_sync(0xffffffffu, w[s % 3], (s / 3) * 16 + j);
                const uint32_t b1 = __shfl_sync(0xffffffffu, w[s % 3], (s / 3) * 16 + 8 + j);
#pragma unroll
                for (int mt = 0; mt < 2; mt++) mma16816(acc[mt][s & 1], a[s][mt], b0, b1);
            }
            sts32f(part, sel4(j, acc[0][0][0] + acc[0][1][0], acc[0][0][2] + acc[0][1][2], acc[1][0][0] + acc[1][1][0], acc[1][0][2] + acc[1][1][2]));
            CK(1, 0);
            fin_arrive<4>();
            fin_sync<5>();
            if (cta < NE_CTAS + 4 && tid < 56) reinterpret_cast<uint4*>(&g_early[b * NH + 28 + cta - NE_CTAS])[tid] = make_uint4(0u, 0u, 0u, 0u);
        } else {
            const int bh = b * NH + (cta >> 2);
            if (tid == 0) wait_row_o(bh, UPB);
            aux_sync();
            if (warp < 5) {
                uint32_t ob[12][2];
                load_o<4>(ob, bh, 0, j);
                float acc[2][2][4] = {};
#pragma unroll
                for (int ks = 0; ks < 12; ks++) {
#pragma unroll
                    for (int mt = 0; mt < 2; mt++) {
                        uint32_t a[4];
                        ldsm4t(a, (f64b ^ (mt * 32)) + SM_A + warp * 12288 + ks * 1024);
                        mma16816(acc[mt][ks & 1], a, ob[ks][0], ob[ks][1]);
                    }
                }
                red_f2(&g_st.attn[b][(cta & 3) * 160 + warp * 32 + 8 * j + g].x,
                       sel4(j, acc[0][0][0] + acc[0][1][0], acc[0][0][2] + acc[0][1][2], acc[1][0][0] + acc[1][1][0], acc[1][0][2] + acc[1][1][2]), 1.f);
                TS(8);
            } else if (warp > 5 && (cta & 3) == 0 && tid - 192 < 56) {
                reinterpret_cast<uint4*>(&g_early[bh])[tid - 192] = make_uint4(0u, 0u, 0u, 0u);
            }
        }
        if (b < NB - 2) continue;

        if (is_f(cta)) {
            uint32_t ga[10][2][4];
            uint4 hv[5];
            if (b < NB - 1) fin_sync<7>();
#pragma unroll
            for (int s = 0; s < 5; s++) hv[s] = lds128(sb + SM_X + min(g, 4) * HPITCH + ((warp >> 1) * 80 + s * 16 + 4 * j) * 4);
            const uint32_t* hsrc = &g_st.hx.w[near_side(sb) ^ ((warp & 1) * 3)][(b & 1) * 128 + (warp >> 1) * 256 + 4 * j];
            uint32_t gpart = sb + SM_RED + (warp >> 1) * 640 + j * 256 + ((g + 2 * j) & 7) * 16 + (warp & 1) * 8;
            uint32_t mpart = sb + SM_RED + 5120 + (g < 4 && (j == 2 || j == g >> 1) ? g * 64 + warp * 8 + (j < 2 ? 4 : 0) : 256);
            uint32_t msel = (g & 1) && j < 2;
            uint32_t need = g == b;
            pin(gpart); pin(mpart); pin(msel); pin(need);
            auto poll_h = [&]() {
                uint32_t lo = 0xffffffffu;
#pragma unroll
                for (int s = 0; s < 5; s++) ld_relaxed_v4_if(hv[s], hsrc + s * 16, g == b);
#pragma unroll
                for (int s = 0; s < 5; s++) lo = min(min(lo, min(hv[s].x, hv[s].y)), min(hv[s].z, hv[s].w));
                return __all_sync(0xffffffffu, lo >= need);
            };
            bool have_h = false;
            if (b == NB - 1) mbar_wait(sb + BAR_FW + min(warp, HPOLL2) * 8, 0);
#pragma unroll 1
            for (int it = 0; it < SPIN_MAX && !have_h; it++) {
                if (mbar_test(sb + BAR_FW + warp * 8, b == NB - 1 ? 0 : ~warp & 1)) break;
                have_h = poll_h();
            }
            if (b == NB - 1) mbar_wait(sb + BAR_FW + warp * 8, 0);
            if (warp == 7) TSW(10);
            CK(12, lds32(sb + SM_W));
#pragma unroll
            for (int s = 0; s < 10; s++) {
#pragma unroll
                for (int mt = 0; mt < 2; mt++) ldsm4t(ga[s][mt], (f64b ^ (mt * 32)) + SM_W + (warp * 10 + s) * 1024);
            }
            if (HGATE && b == NB - 1) mbar_wait(sb + BAR_FW + HGATE * 8, 0);
#pragma unroll 1
            for (int it = 0; it < SPIN_MAX && !have_h; it++) have_h = poll_h();
            CK(4, hv[0].x);
            float gram[4][4] = {};
#pragma unroll
            for (int s = 0; s < 5; s++) {
                const uint32_t b0 = (warp & 1) ? hv[s].z : hv[s].x, b1 = (warp & 1) ? hv[s].w : hv[s].y;
                mma1688(gram[s & 1], b0, b1, b0);
                mma1688(gram[2 + (s & 1)], b0, b1, b1);
            }
            float acc[2][2][4] = {};
#pragma unroll
            for (int s = 0; s < 10; s++) {
#pragma unroll
                for (int mt = 0; mt < 2; mt++)
                    mma16816(acc[mt][s & 1], ga[s][mt], (s & 1) ? hv[s >> 1].z : hv[s >> 1].x, (s & 1) ? hv[s >> 1].w : hv[s >> 1].y);
                if (s == GRAM_AT) {
                    const float e0 = (gram[0][0] + gram[1][0]) + (gram[2][2] + gram[3][2]), e1 = (gram[0][1] + gram[1][1]) + (gram[2][3] + gram[3][3]);
                    sts32f(mpart, msel ? e1 : e0);
                    asm volatile("{\n.reg .pred p;\nAGAIN:\nbar.arrive 9, 320;\nsetp.eq.u32 p, %0, 77;\n@p bra.uni AGAIN;\n}" :: "r"(warp) : "memory");
                }
            }
#pragma unroll
            for (int mt = 0; mt < 2; mt++) {
                if (j < 3) sts64f(gpart + mt * 2560, acc[mt][0][0] + acc[mt][1][0], acc[mt][0][2] + acc[mt][1][2]);
                if (j < 2) sts64f(gpart + mt * 2560 + 128, acc[mt][0][1] + acc[mt][1][1], acc[mt][0][3] + acc[mt][1][3]);
            }
            CK(5, 0);
            asm volatile("bar.arrive 4, 320;" ::: "memory");
        } else if (is_g(cta)) {
            uint32_t wb[12][4];
            if (b == NB - 1) mbar_wait(sb + BAR_FW + warp * 8, 0);
            if (warp == 7) TSW(11);
            CK(13, lds32(sb + SM_W));
#pragma unroll
            for (int s = 0; s < 12; s++) ldsm4t(wb[s], f32b + SM_W + (warp * 12 + s) * 512);
            const uint32_t* asrc = &g_st.ax[0].w[(~b & 1) * 2 + near_side(sb)][(warp * 32 + lane) * 4];
            uint32_t ypart = sb + SM_RED2 + warp * 512 + j * 128 + ((g + 2 * j) & 7) * 16;
            pin(ypart);
            fin_sync<7>();
            uint4 va[3];
#pragma unroll 1
            for (int it = 0; it < SPIN_MAX; it++) {
                uint32_t lo = 0xffffffffu;
#pragma unroll
                for (int i = 0; i < 3; i++) va[i] = ld_relaxed_v4(asrc + i * 4096);
#pragma unroll
                for (int i = 0; i < 3; i++) lo = min(min(lo, min(va[i].x, va[i].y)), min(va[i].z, va[i].w));
                if (__all_sync(0xffffffffu, lo != 0)) break;
            }
            CK(8, va[0].x);
            if (va[0].x != 0x12345 && warp == 7) TSW(15);
            float acc[4][4] = {};
#pragma unroll
            for (int s = 0; s < 12; s++) {
                const uint4 v = va[s >> 2];
                mma16816(acc[s & 3], wb[s], (s & 2) ? v.z : v.x, (s & 2) ? v.w : v.y);
            }
            float y[4];
#pragma unroll
            for (int e = 0; e < 4; e++) y[e] = j < 2 ? acc[0][e] + acc[2][e] : acc[1][e] + acc[3][e];
            sts128f(ypart, y[0], y[1], y[2], y[3]);
            CK(9, 0);
            fin_arrive<6>();
        }
    }
}

typedef CUresult (*EncodeFn)(CUtensorMap*, CUtensorMapDataType, cuuint32_t, void*, const cuuint64_t*, const cuuint64_t*,
                             const cuuint32_t*, const cuuint32_t*, CUtensorMapInterleave, CUtensorMapSwizzle,
                             CUtensorMapL2promotion, CUtensorMapFloatOOBfill);

CUtensorMap make_map(EncodeFn enc, void* ptr, uint64_t cols, uint64_t rows, uint32_t bcols, uint32_t brows,
                     CUtensorMapSwizzle sw, CUtensorMapL2promotion promo) {
    CUtensorMap m;
    const cuuint64_t dims[2] = {cols, rows};
    const cuuint64_t strides[1] = {cols * 2};
    const cuuint32_t box[2] = {bcols, brows};
    const cuuint32_t es[2] = {1, 1};
    enc(&m, CU_TENSOR_MAP_DATA_TYPE_BFLOAT16, 2, ptr, dims, strides, box, es, CU_TENSOR_MAP_INTERLEAVE_NONE, sw, promo,
        CU_TENSOR_MAP_FLOAT_OOB_FILL_NONE);
    return m;
}

}

extern "C" void kernel_launch(void* const* d_in, const int* in_sizes, int n_in, void* d_out, int out_size) {
    (void)in_sizes; (void)n_in; (void)out_size;
    static EncodeFn enc = nullptr;
    static int sms = 0;
    if (!enc) {
        cudaDriverEntryPointQueryResult qr;
        cudaGetDriverEntryPoint("cuTensorMapEncodeTiled", (void**)&enc, cudaEnableDefault, &qr);
        int dev = 0;
        cudaGetDevice(&dev);
        cudaDeviceGetAttribute(&sms, cudaDevAttrMultiProcessorCount, dev);
        cudaFuncSetAttribute(fused_decode_kernel, cudaFuncAttributeMaxDynamicSharedMemorySize, SM_TOTAL);
    }
    if (sms < NCTAS) return;
    const CUtensorMapL2promotion WPROMO = CU_TENSOR_MAP_L2_PROMOTION_L2_128B;
#define GPROMO 2
#define DPROMO 2
    Params p;
    p.k = make_map(enc, d_in[1], 64, (uint64_t)NBH * SK * 3, 64, TILE_ROWS / NPART, CU_TENSOR_MAP_SWIZZLE_128B, CU_TENSOR_MAP_L2_PROMOTION_NONE);
    p.v = make_map(enc, d_in[2], 64, (uint64_t)NBH * SK * 3, 64, TILE_ROWS / NPART, CU_TENSOR_MAP_SWIZZLE_128B, CU_TENSOR_MAP_L2_PROMOTION_NONE);
    p.wq = make_map(enc, d_in[3], NH * DH, DM, 48, 160, CU_TENSOR_MAP_SWIZZLE_NONE, WPROMO);
    p.wo = make_map(enc, d_in[4], DM, NH * DH, 32, DH, CU_TENSOR_MAP_SWIZZLE_64B, WPROMO);
    p.wg = make_map(enc, d_in[7], FF, DM, 32, 160, CU_TENSOR_MAP_SWIZZLE_64B, (CUtensorMapL2promotion)GPROMO);
    p.wu = make_map(enc, d_in[8], FF, DM, 32, 160, CU_TENSOR_MAP_SWIZZLE_64B, (CUtensorMapL2promotion)GPROMO);
    {
        const cuuint64_t dims[4] = {DM, 2, 8, FF / 16}, strides[3] = {8 * DM * 2, DM * 2, 16 * DM * 2};
        const cuuint32_t box[4] = {16, 2, 8, 12}, es[4] = {1, 1, 1, 1};
        enc(&p.wd, CU_TENSOR_MAP_DATA_TYPE_BFLOAT16, 4, d_in[9], dims, strides, box, es, CU_TENSOR_MAP_INTERLEAVE_NONE,
            CU_TENSOR_MAP_SWIZZLE_32B, (CUtensorMapL2promotion)DPROMO, CU_TENSOR_MAP_FLOAT_OOB_FILL_NONE);
    }
    p.x = (const __nv_bfloat16*)d_in[0];
    p.wr = (const __nv_bfloat16*)d_in[6];
    p.out = (__nv_bfloat16*)d_out;
    fused_decode_kernel<<<NCTAS, NTHREADS, SM_TOTAL, cudaStreamPerThread>>>(p);
}
```

```cpp
#include <cuda_runtime.h>
#include <cuda_bf16.h>
#include <cuda.h>
#include <stdint.h>

namespace {

constexpr int NB = 4, NH = 32, SK = 8192, DH = 192, DM = 640, FF = 1536;
constexpr int NBH = NB * NH;
constexpr int TILE = 64;
constexpr int UPB = SK / TILE;
constexpr int NUNITS = NBH * UPB;
constexpr int TILE_BYTES = TILE * DH * 2;
constexpr int TILE_ROWS = TILE * 3;
constexpr int NCTAS = 132;
constexpr int NQ_CTAS = 128;
constexpr int NE_CTAS = 112;
#define ROLES 1
__host__ __device__ constexpr bool is_f(int cta) { return cta < 96 && !(cta & 2); }
__host__ __device__ constexpr bool is_g(int cta) { return cta < 80 && (cta & 2); }
__host__ __device__ constexpr int ffn_slice(int cta) { return (cta >> 2) * 2 + (cta & 1); }

#define NWORK 2
#define NPART 1
#define LAG 2
#define NPOOL 640
#define RED0 116
#define RING 12
#define OREP 3
#define K0_DELAY_NS 1000
#define WO_AT_NS 3800
#define FW_TICKET 400
#define FW_AT_NS 3840
#define FW_GAP 320
#define FW_GAP2 200
#define FW_STAG (FW_GAP / 2)
#define HREP2 1
#define LSTAT 1
#define NPROBE 24
#define SIDE_XOR 0
#define FW_MID 2300
constexpr int NAUX = 8;
constexpr int NTHREADS = (NAUX + NWORK + 2) * 32;
constexpr int SPIN_MAX = 1 << 22;

constexpr int SM_KV = 0;
constexpr int SM_A = SM_KV + NWORK * TILE_BYTES;
constexpr int SM_W = SM_A + 61440;
constexpr int SM_X = SM_W + 81920;
constexpr int XPITCH = 648;
constexpr int HPITCH = 1344;
constexpr int SM_RED = SM_X + 5 * HPITCH + 64;
constexpr int SM_RED2 = SM_RED + 8 * 48 * 4 * 4;
constexpr int SM_MISC = SM_RED2 + 4096;
constexpr int BAR_WQ = SM_MISC + 32, BAR_WO = SM_MISC + 40, SM_SIDE = SM_MISC + 48, BAR_FW = SM_MISC + 64;
constexpr int BAR_KV = BAR_FW + 64;
constexpr int SM_TOTAL = BAR_KV + NWORK * NPART * 8;
static_assert(NB * XPITCH * 2 <= 4 * HPITCH && SM_RED % 128 == 0, "smem layout");

struct Params {
    CUtensorMap k, v;
    CUtensorMap wq;
    CUtensorMap wo;
    CUtensorMap wg, wu;
    CUtensorMap wd;
    const __nv_bfloat16 *x, *wr;
    __nv_bfloat16* out;
};

struct Early {
    uint32_t q[96];
    uint32_t umax[UPB];
};
struct Twin { uint32_t w[4][1024]; };
constexpr int PROBE = 1024 - 32;
#define LSTRIDE 16
struct State {
    Twin ax[3];
    Twin hx;
    Twin ox[OREP];
    Twin lx;
    float4 oacc[NBH * 64];
    float2 attn[NB][DM];
    uint32_t fw_time[32];
    float2 lsum[NBH][LSTRIDE];
    uint32_t score[NPOOL][32];
};
__host__ __device__ constexpr int oidx(int row, int grp) {
    return (row >> 2) * 256 + ((row & 1) * 2 + (grp >> 5)) * 64 + (row & 2) * 16 + (grp & 31);
}
constexpr int STATE_V4 = ((sizeof(State) / 32 + NQ_CTAS - 1) / NQ_CTAS) * 2;
static_assert(sizeof(State) % 32 == 0, "State is cleared in whole sectors");
static_assert(sizeof(Early) == 56 * 16, "an Early entry is cleared by 56 threads");
struct Scratch {
    State st;
    unsigned work[64];
    unsigned cnt_z[32];
    Early early[NBH];
    alignas(4096) float4 ring[RING][UPB][64];
};
constexpr size_t PAGE = 2u << 20;
static_assert(sizeof(Scratch) <= PAGE, "scratch must fit one page");
__device__ __align__(128) unsigned char g_raw[2 * PAGE];
__device__ __forceinline__ Scratch* scratch() {
    return reinterpret_cast<Scratch*>((reinterpret_cast<uintptr_t>(g_raw) + PAGE - 1) & ~(uintptr_t)(PAGE - 1));
}
#define g_early scratch()->early
#define g_st scratch()->st
#define g_ring scratch()->ring
#define g_cnt_z scratch()->cnt_z
#define g_work scratch()->work
#define TS(i)
#define TSW(i)
#define TS2(i)
#define TSI(n, i)
#define PH(i)
#define CK(i, dep)
#define ARR()
#define PROG(u)

__device__ __forceinline__ uint32_t s2u(const void* p) { return (uint32_t)__cvta_generic_to_shared(p); }
__device__ __forceinline__ void mbar_init(uint32_t bar, int cnt) {
    asm volatile("mbarrier.init.shared::cta.b64 [%0], %1;" :: "r"(bar), "r"(cnt) : "memory");
}
__device__ __forceinline__ void mbar_expect_tx(uint32_t bar, uint32_t bytes) {
    asm volatile("mbarrier.arrive.expect_tx.shared::cta.b64 _, [%0], %1;" :: "r"(bar), "r"(bytes) : "memory");
}
__device__ __forceinline__ void mbar_wait(uint32_t bar, uint32_t parity) {
    asm volatile("{\n.reg .pred p;\n.reg .u32 n;\nmov.u32 n, 0;\nWAIT_LOOP:\n"
                 "mbarrier.try_wait.parity.shared::cta.b64 p, [%0], %1;\n"
                 "@p bra WAIT_DONE;\nadd.u32 n, n, 1;\nsetp.lt.u32 p, n, %2;\n@p bra WAIT_LOOP;\nWAIT_DONE:\n}"
                 :: "r"(bar), "r"(parity), "n"(SPIN_MAX) : "memory");
}
__device__ __forceinline__ void request_tile(uint32_t dst, const CUtensorMap* tm, int unit, uint32_t bar, uint64_t pol) {
#pragma unroll
    for (int i = 0; i < NPART; i++)
        asm volatile("{\n.reg .pred p;\nelect.sync _|p, 0xffffffff;\n"
                     "@p mbarrier.arrive.expect_tx.shared::cta.b64 _, [%2], %6;\n"
                     "@p cp.async.bulk.tensor.2d.shared::cluster.global.mbarrier::complete_tx::bytes.L2::cache_hint "
                     "[%0], [%1, {%3, %4}], [%2], %5;\n}"
                     :: "r"(dst + i * (TILE_BYTES / NPART)), "l"(tm), "r"(bar + i * 8), "r"(0), "r"(unit * TILE_ROWS + i * (TILE_ROWS / NPART)),
                        "l"(pol), "n"(TILE_BYTES / NPART) : "memory");
}
__device__ __forceinline__ void put_groups(void* dst, int mode, const float (&o)[6], float tag, float tag2) {
    asm volatile("{\n.reg .pred s, r, t;\n.reg .b128 u, v;\n.reg .b64 a, b;\n"
                 "setp.eq.s32 s|r, %1, 0;\nsetp.eq.s32 t, %1, 2;\n"
                 "@r red.relaxed.gpu.global.add.v4.f32 [%0], {%2,%3,%4,%8};\n"
                 "@t red.relaxed.gpu.global.add.v4.f32 [%0+4096], {%2,%3,%4,%8};\n"
                 "@r red.relaxed.gpu.global.add.v4.f32 [%0+128], {%5,%6,%7,%9};\n"
                 "@t red.relaxed.gpu.global.add.v4.f32 [%0+4224], {%5,%6,%7,%9};\n"
                 "mov.b64 a, {%2, %3};\nmov.b64 b, {%4, %8};\nmov.b128 u, {a, b};\n"
                 "mov.b64 a, {%5, %6};\nmov.b64 b, {%7, %9};\nmov.b128 v, {a, b};\n"
                 "@s st.relaxed.gpu.global.b128 [%0], u;\n@s st.relaxed.gpu.global.b128 [%0+128], v;\n}"
                 :: "l"(dst), "r"(mode), "f"(o[0]), "f"(o[1]), "f"(o[2]), "f"(o[3]), "f"(o[4]), "f"(o[5]), "f"(tag), "f"(tag2) : "memory");
}
__device__ __forceinline__ void tma_box(uint32_t dst, const CUtensorMap* tm, int col, int row, uint32_t bar) {
    asm volatile("cp.async.bulk.tensor.2d.shared::cluster.global.mbarrier::complete_tx::bytes [%0], [%1, {%3, %4}], [%2];"
                 :: "r"(dst), "l"(tm), "r"(bar), "r"(col), "r"(row) : "memory");
}
__device__ __forceinline__ uint32_t lds32(uint32_t addr) {
    uint32_t v;
    asm volatile("ld.shared.u32 %0, [%1];" : "=r"(v) : "r"(addr) : "memory");
    return v;
}
__device__ __forceinline__ void ldsm4(uint32_t (&r)[4], uint32_t addr) {
    asm volatile("ldmatrix.sync.aligned.m8n8.x4.shared.b16 {%0,%1,%2,%3}, [%4];"
                 : "=r"(r[0]), "=r"(r[1]), "=r"(r[2]), "=r"(r[3]) : "r"(addr) : "memory");
}
__device__ __forceinline__ void ldsm4t(uint32_t (&r)[4], uint32_t addr) {
    asm volatile("ldmatrix.sync.aligned.m8n8.x4.trans.shared.b16 {%0,%1,%2,%3}, [%4];"
                 : "=r"(r[0]), "=r"(r[1]), "=r"(r[2]), "=r"(r[3]) : "r"(addr) : "memory");
}
__device__ __forceinline__ void mma16816(float (&c)[4], const uint32_t (&a)[4], uint32_t b0, uint32_t b1) {
    asm volatile("mma.sync.aligned.m16n8k16.row.col.f32.bf16.bf16.f32 {%0,%1,%2,%3}, {%4,%5,%6,%7}, {%8,%9}, {%0,%1,%2,%3};"
                 : "+f"(c[0]), "+f"(c[1]), "+f"(c[2]), "+f"(c[3])
                 : "r"(a[0]), "r"(a[1]), "r"(a[2]), "r"(a[3]), "r"(b0), "r"(b1));
}
__device__ __forceinline__ uint4 ld_relaxed_v4(const void* p) {
    uint4 v;
    asm volatile("ld.relaxed.gpu.global.v4.u32 {%0,%1,%2,%3}, [%4];" : "=r"(v.x), "=r"(v.y), "=r"(v.z), "=r"(v.w) : "l"(p) : "memory");
    return v;
}
__device__ __forceinline__ float4 ld_relaxed_f4(const void* p) {
    float4 v;
    asm volatile("ld.relaxed.gpu.global.v4.f32 {%0,%1,%2,%3}, [%4];" : "=f"(v.x), "=f"(v.y), "=f"(v.z), "=f"(v.w) : "l"(p) : "memory");
    return v;
}
__device__ __forceinline__ float2 ld_relaxed_f2(const void* p) {
    float2 v;
    asm volatile("ld.relaxed.gpu.global.v2.f32 {%0,%1}, [%2];" : "=f"(v.x), "=f"(v.y) : "l"(p) : "memory");
    return v;
}
__device__ __forceinline__ float4 ld_relaxed_b128(const void* p) {
    float4 v;
    asm volatile("{\n.reg .b128 t;\n.reg .b64 a, b;\nld.relaxed.gpu.global.b128 t, [%4];\nmov.b128 {a, b}, t;\n"
                 "mov.b64 {%0, %1}, a;\nmov.b64 {%2, %3}, b;\n}" : "=f"(v.x), "=f"(v.y), "=f"(v.z), "=f"(v.w) : "l"(p) : "memory");
    return v;
}
__device__ __forceinline__ void st_relaxed_b128(void* p, float x, float y, float z, float w) {
    asm volatile("{\n.reg .b128 t;\n.reg .b64 a, b;\nmov.b64 a, {%1, %2};\nmov.b64 b, {%3, %4};\nmov.b128 t, {a, b};\n"
                 "st.relaxed.gpu.global.b128 [%0], t;\n}" :: "l"(p), "f"(x), "f"(y), "f"(z), "f"(w) : "memory");
}
__device__ __forceinline__ unsigned ld_acquire(const unsigned* p) {
    unsigned v;
    asm volatile("ld.acquire.gpu.global.u32 %0, [%1];" : "=r"(v) : "l"(p) : "memory");
    return v;
}
__device__ __forceinline__ void st_relaxed(void* p, uint32_t v) {
    asm volatile("st.relaxed.gpu.global.u32 [%0], %1;" :: "l"(p), "r"(v) : "memory");
}
__device__ __forceinline__ void red_f2(float* p, float a, float b) {
    asm volatile("red.relaxed.gpu.global.add.v2.f32 [%0], {%1,%2};" :: "l"(p), "f"(a), "f"(b) : "memory");
}
__device__ __forceinline__ void draw(int& ticket, unsigned* ctr, bool pred) {
    asm volatile("{\n.reg .pred p;\nsetp.ne.u32 p, %2, 0;\n@p atom.relaxed.gpu.global.inc.u32 %0, [%1], 0x7fffffff;\n}"
                 : "+r"(ticket) : "l"(ctr), "r"((uint32_t)pred) : "memory");
}
__device__ __forceinline__ void red_release(unsigned* p) {
    asm volatile("red.release.gpu.global.add.u32 [%0], 1;" :: "l"(p) : "memory");
}
__device__ __forceinline__ uint32_t ld_relaxed_u32(const void* p) {
    uint32_t v;
    asm volatile("ld.relaxed.gpu.global.u32 %0, [%1];" : "=r"(v) : "l"(p) : "memory");
    return v;
}
__device__ __forceinline__ float rcp_approx(float v) {
    float r;
    asm("rcp.approx.ftz.f32 %0, %1;" : "=f"(r) : "f"(v));
    return r;
}
__device__ __forceinline__ float sigmoid_approx(float v) {
    float e;
    asm("ex2.approx.ftz.f32 %0, %1;" : "=f"(e) : "f"(v * -1.4426950408889634f));
    return rcp_approx(1.0f + e);
}
__device__ __forceinline__ float sqrt_approx(float v) {
    float r;
    asm("sqrt.approx.ftz.f32 %0, %1;" : "=f"(r) : "f"(v));
    return r;
}
__device__ __forceinline__ void wait_count(const unsigned* p, unsigned target) {
#pragma unroll 1
    for (int it = 0; it < SPIN_MAX; it++) {
        if (ld_acquire(p) >= target) break;
        __nanosleep(400);
    }
}
__device__ __forceinline__ void wait_row(int bh, float n) {
#pragma unroll 1
    for (int it = 0; it < SPIN_MAX; it++) {
        const float c = ld_relaxed_f2(g_st.lsum[bh]).y;
        if (c >= n) break;
        if (c == 0.f) __nanosleep(600);
    }
}
__device__ __forceinline__ void wait_row_o(int bh, float n) {
    wait_row(bh, n);
    if (bh >= RED0) return;
#pragma unroll 1
    for (int it = 0; it < SPIN_MAX; it++) {
        if (__uint_as_float(ld_relaxed_u32(&g_st.oacc[oidx(bh, 0)].w)) == UPB) break;
        __nanosleep(300);
    }
}
__device__ __forceinline__ void spin_ns(int ns) {
    const long long t0 = clock64();
    while (clock64() - t0 < (long long)ns * 2) {}
}
__device__ __forceinline__ uint32_t pack_bf16(float lo, float hi) {
    uint32_t r;
    asm("cvt.rn.bf16x2.f32 %0, %1, %2;" : "=r"(r) : "f"(hi), "f"(lo));
    return r;
}
__device__ __forceinline__ float bf16r(float v) { return __uint_as_float(pack_bf16(0.f, v)); }
__device__ __forceinline__ uint32_t pack_neg(float lo, float hi) {
    const uint32_t w = pack_bf16(-lo, -hi);
    return w ? w : 0x80008000u;
}
__device__ __forceinline__ float lo_f(uint32_t v) { return __uint_as_float(v << 16); }
__device__ __forceinline__ float hi_f(uint32_t v) { return __uint_as_float(v & 0xffff0000u); }
__device__ __forceinline__ float warp_sum(float v) {
#pragma unroll
    for (int o = 16; o; o >>= 1) v += __shfl_xor_sync(0xffffffffu, v, o);
    return v;
}
__device__ __forceinline__ void layernorm20(float (&v)[20]) {
    float s = 0.f;
#pragma unroll
    for (int i = 0; i < 20; i++) s += v[i];
    const float mean = warp_sum(s) * (1.0f / DM);
    float q = 0.f;
#pragma unroll
    for (int i = 0; i < 20; i++) { const float d = v[i] - mean; q += d * d; }
    const float var = bf16r(warp_sum(q) * (1.0f / DM));
    const float m = bf16r(mean);
    const float rden = 1.0f / bf16r(sqrtf(bf16r(var + 1e-5f)));
#pragma unroll
    for (int i = 0; i < 20; i++) v[i] = bf16r(bf16r(v[i] - m) * rden);
}

__device__ __forceinline__ void moments(float m1, float m2, float& nmean, float& rden) {
    m1 *= 1.0f / DM;
    const float var = bf16r(fmaxf(fmaf(-m1, m1, m2 * (1.0f / DM)), 0.f));
    nmean = bf16r(m1);
    rden = rcp_approx(bf16r(sqrt_approx(bf16r(var + 1e-5f))));
}
__device__ __forceinline__ float sel4(int j, float a, float b, float c, float d) {
    float lo, hi, r;
    asm("{\n.reg .pred p;\nsetp.ne.s32 p, %3, 0;\nselp.f32 %0, %2, %1, p;\n}" : "=f"(lo) : "f"(a), "f"(b), "r"(j & 1));
    asm("{\n.reg .pred p;\nsetp.ne.s32 p, %3, 0;\nselp.f32 %0, %2, %1, p;\n}" : "=f"(hi) : "f"(c), "f"(d), "r"(j & 1));
    asm("{\n.reg .pred p;\nsetp.ne.s32 p, %3, 0;\nselp.f32 %0, %2, %1, p;\n}" : "=f"(r) : "f"(lo), "f"(hi), "r"(j & 2));
    return r;
}
template <typename T> __device__ __forceinline__ void pin(T*& p) { asm volatile("" : "+l"(p)); }
__device__ __forceinline__ void pin(uint32_t& v) { asm volatile("" : "+r"(v)); }
__device__ __forceinline__ void pin(float& v) { asm volatile("" : "+f"(v)); }
__device__ __forceinline__ uint32_t after(uint32_t n, float v) {
    asm volatile("{\n.reg .pred p;\nsetp.eq.u32 p, %1, 0x7fc1a5a5;\n@p add.u32 %0, %0, 32;\n}" : "+r"(n) : "r"(__float_as_uint(v)));
    return n;
}
__device__ __forceinline__ float2 lds64f(uint32_t addr) {
    float2 v;
    asm volatile("ld.shared.v2.f32 {%0,%1}, [%2];" : "=f"(v.x), "=f"(v.y) : "r"(addr) : "memory");
    return v;
}
__device__ __forceinline__ void sts32f(uint32_t addr, float v) { asm volatile("st.shared.f32 [%0], %1;" :: "r"(addr), "f"(v) : "memory"); }
template <int ID> __device__ __forceinline__ void fin_arrive() { asm volatile("bar.arrive %0, 288;" :: "n"(ID) : "memory"); }
template <int ID> __device__ __forceinline__ void fin_sync() { asm volatile("bar.sync %0, 288;" :: "n"(ID) : "memory"); }
template <int ID> __device__ __forceinline__ void fin_sync(uint32_t n) { asm volatile("bar.sync %0, %1;" :: "n"(ID), "r"(n) : "memory"); }
__device__ __forceinline__ float2 sum8(uint32_t addr) {
    float2 t[8];
#pragma unroll
    for (int w = 0; w < 8; w++) t[w] = lds64f(addr + w * 128);
    return make_float2(((t[0].x + t[1].x) + (t[2].x + t[3].x)) + ((t[4].x + t[5].x) + (t[6].x + t[7].x)),
                       ((t[0].y + t[1].y) + (t[2].y + t[3].y)) + ((t[4].y + t[5].y) + (t[6].y + t[7].y)));
}
__device__ __forceinline__ float4 sum4x4(uint32_t addr, int pitch) {
    float4 t[4];
#pragma unroll
    for (int w = 0; w < 4; w++)
        asm volatile("ld.shared.v4.f32 {%0,%1,%2,%3}, [%4];" : "=f"(t[w].x), "=f"(t[w].y), "=f"(t[w].z), "=f"(t[w].w) : "r"(addr + w * pitch) : "memory");
    return make_float4((t[0].x + t[1].x) + (t[2].x + t[3].x), (t[0].y + t[1].y) + (t[2].y + t[3].y),
                       (t[0].z + t[1].z) + (t[2].z + t[3].z), (t[0].w + t[1].w) + (t[2].w + t[3].w));
}
__device__ __forceinline__ void sts64f(uint32_t addr, float x, float y) {
    asm volatile("st.shared.v2.f32 [%0], {%1,%2};" :: "r"(addr), "f"(x), "f"(y) : "memory");
}
__device__ __forceinline__ void lds128_if(uint4& v, uint32_t addr, bool pred) {
    asm volatile("{\n.reg .pred p;\nsetp.ne.u32 p, %5, 0;\n@p ld.shared.v4.u32 {%0,%1,%2,%3}, [%4];\n}"
                 : "+r"(v.x), "+r"(v.y), "+r"(v.z), "+r"(v.w) : "r"(addr), "r"((uint32_t)pred) : "memory");
}
__device__ __forceinline__ void sts128f(uint32_t addr, float x, float y, float z, float w) {
    asm volatile("st.shared.v4.f32 [%0], {%1,%2,%3,%4};" :: "r"(addr), "f"(x), "f"(y), "f"(z), "f"(w) : "memory");
}
template <int NJ>
__device__ __forceinline__ void load_o(uint32_t (&ob)[3 * NJ][2], int bh, int J0, int j) {
    float4 v[NJ][4];
    float2 l;
#pragma unroll 1
    for (int it = 0; it < SPIN_MAX; it++) {
#pragma unroll
        for (int J = 0; J < NJ; J++) {
#pragma unroll
            for (int e = 0; e < 4; e++) v[J][e] = ld_relaxed_f4(&g_st.oacc[oidx(bh, j)] + oidx(0, (J0 + J) * 16 + e * 4));
        }
        l = ld_relaxed_f2(g_st.lsum[bh]);
        bool ok = l.y == UPB;
#pragma unroll
        for (int J = 0; J < NJ; J++) {
#pragma unroll
            for (int e = 0; e < 4; e++) ok &= v[J][e].w == UPB;
        }
        if (__all_sync(0xffffffffu, ok)) break;
    }
    const float rl = __fdividef(1.0f, l.x);
#pragma unroll
    for (int J = 0; J < NJ; J++) {
        ob[3 * J][0] = pack_bf16(v[J][0].x * rl, v[J][1].x * rl);     ob[3 * J][1] = pack_bf16(v[J][2].x * rl, v[J][3].x * rl);
        ob[3 * J + 1][0] = pack_bf16(v[J][0].y * rl, v[J][1].y * rl); ob[3 * J + 1][1] = pack_bf16(v[J][2].y * rl, v[J][3].y * rl);
        ob[3 * J + 2][0] = pack_bf16(v[J][0].z * rl, v[J][1].z * rl); ob[3 * J + 2][1] = pack_bf16(v[J][2].z * rl, v[J][3].z * rl);
    }
}
__device__ __forceinline__ int near_side(uint32_t sb) {
    uint32_t v;
    asm volatile("ld.volatile.shared.u32 %0, [%1];" : "=r"(v) : "r"(sb + SM_SIDE) : "memory");
    return v;
}
__device__ __forceinline__ void poll_row(uint4& a, uint4& b, uint2& c, const void* pa, const void* pb, const void* pc, uint32_t sa, uint32_t sc,
                                         bool arrive, bool nap) {
    asm volatile("{\n.reg .pred p, q, r, s;\n.reg .u32 m, n, it;\n"
                 "setp.ne.u32 r, %15, 0;\nsetp.ne.u32 s, %16, 0;\nmov.u32 it, 0;\n"
                 "POLL:\n"
                 "ld.relaxed.gpu.global.v4.u32 {%0,%1,%2,%3}, [%10];\n"
                 "ld.relaxed.gpu.global.v4.u32 {%4,%5,%6,%7}, [%11];\n"
                 "ld.relaxed.gpu.global.v2.u32 {%8,%9}, [%12];\n"
                 "add.u32 it, it, 1;\nsetp.ge.u32 q, it, %17;\n"
                 "st.shared.v4.u32 [%13], {%0,%1,%2,%3};\n"
                 "st.shared.v4.u32 [%13+512], {%4,%5,%6,%7};\n"
                 "st.shared.v2.u32 [%14], {%8,%9};\n"
                 "min.u32 m, %0, %1;\nmin.u32 m, m, %2;\nmin.u32 n, %3, %4;\nmin.u32 n, n, %5;\nmin.u32 m, m, %6;\nmin.u32 m, m, %7;\n"
                 "min.u32 n, n, m;\nmin.u32 m, %8, %9;\nmin.u32 m, m, n;\n"
                 "setp.ne.or.u32 p, m, 0, q;\n"
                 "vote.sync.all.pred p, p, 0xffffffff;\n"
                 "and.pred q, p, r;\n"
                 "@q bar.arrive 7, 288;\n"
                 "@p bra.uni DONE;\n"
                 "@s nanosleep.u32 500;\n"
                 "bra.uni POLL;\n"
                 "DONE:\n}"
                 : "=&r"(a.x), "=&r"(a.y), "=&r"(a.z), "=&r"(a.w), "=&r"(b.x), "=&r"(b.y), "=&r"(b.z), "=&r"(b.w), "=&r"(c.x), "=&r"(c.y)
                 : "l"(pa), "l"(pb), "l"(pc), "r"(sa), "r"(sc), "r"((uint32_t)arrive), "r"((uint32_t)nap), "n"(SPIN_MAX) : "memory");
}
__device__ __forceinline__ void aux_sync() { asm volatile("bar.sync 1, 256;" ::: "memory"); }

__global__ void __launch_bounds__(NTHREADS, 1)
fused_decode_kernel(const __grid_constant__ Params p) {
    extern __shared__ __align__(1024) unsigned char smem[];
    const uint32_t sb = s2u(smem);
    const int tid = threadIdx.x, warp = __shfl_sync(0xffffffffu, tid >> 5, 0), lane = tid & 31;
    const int cta = blockIdx.x;
    constexpr int grid = NCTAS;
    const int g = lane >> 2, j = lane & 3;

    TS(0);
    if (tid == 128) {
        mbar_init(sb + BAR_WQ, 1);
        asm volatile("fence.mbarrier_init.release.cluster;" ::: "memory");
        asm volatile("fence.proxy.async.shared::cta;" ::: "memory");
        if (cta < NQ_CTAS) {
            mbar_expect_tx(sb + BAR_WQ, 61440);
#pragma unroll 1
            for (int i = 0; i < 4; i++) tma_box(sb + SM_W + i * 15360, &p.wq, cta * 48, i * 160, sb + BAR_WQ);
        }
    } else if (tid == 160) {
        mbar_init(sb + BAR_WO, 1);
        sts32f(sb + SM_SIDE, 0.f);
        asm volatile("fence.mbarrier_init.release.cluster;" ::: "memory");
        asm volatile("fence.proxy.async.shared::cta;" ::: "memory");
    } else if (tid >= 192 && tid < 200 + NWORK * NPART) {
        mbar_init(sb + BAR_FW + (tid - 192) * 8, 1);
        asm volatile("fence.mbarrier_init.release.cluster;" ::: "memory");
        asm volatile("fence.proxy.async.shared::cta;" ::: "memory");
    }
    __syncthreads();
    if (warp >= NAUX + NWORK) {
        const int fw = warp - (NAUX + NWORK), fi = ffn_slice(cta);
        if (fw == 0) {
            if (cta < NQ_CTAS) {
#pragma unroll
                for (int i = lane; i < STATE_V4; i += 32)
                    if (cta * STATE_V4 + i < (int)(sizeof(State) / 16)) reinterpret_cast<uint4*>(&g_st)[cta * STATE_V4 + i] = make_uint4(0u, 0u, 0u, 0u);
                __syncwarp();
                if (lane == 0) red_release(g_cnt_z);
            }
            if (lane == 0) { TS2(2); wait_count(g_cnt_z, NQ_CTAS); TS2(29); }
            __syncwarp();
            asm volatile("bar.arrive 2, %0;" :: "n"((NWORK + 2) * 32) : "memory");
            fin_arrive<3>();
        } else {
            asm volatile("bar.sync 2, %0;" :: "n"((NWORK + 2) * 32) : "memory");
            if (lane == 0) {
                uint32_t* ctr = &g_st.hx.w[0][PROBE];
                uint32_t best[2] = {~0u, ~0u};
#pragma unroll 1
                for (int i = 0; i < NPROBE; i++) {
#pragma unroll
                    for (int c = 0; c < 2; c++) {
                        uint32_t t0 = clock(), t1 = t0, v;
                        asm volatile("atom.relaxed.gpu.global.inc.u32 %0, [%1], 0x7fffffff;" : "=r"(v) : "l"(ctr + c * 1024) : "memory");
                        asm volatile("{\n.reg .pred p;\nsetp.ne.u32 p, %1, 0xffffffff;\n@p mov.u32 %0, %%clock;\n}" : "+r"(t1) : "r"(v) : "memory");
                        best[c] = min(best[c], t1 - t0);
                    }
                    __nanosleep(1000);
                }
                sts32f(sb + SM_SIDE, __uint_as_float((best[1] < best[0]) ^ SIDE_XOR));
            }
            __syncwarp();
        }
        int job = cta;
        auto sum_rows = [&](int row_end) {
#pragma unroll 1
            for (; job < 8 * min(row_end, RED0); job += NCTAS) {
                const int row = job >> 3, grp = (job & 7) * 8 + (lane & 7);
                if (lane == 0) wait_row(row, UPB);
                __syncwarp();
                const float4* src = &g_ring[row % RING][lane >> 3][grp];
                float sx = 0.f, sy = 0.f, sz = 0.f;
#pragma unroll 1
                for (int i = 0; i < 2; i++, src += 64 * 64) {
                    float4 v[16];
#pragma unroll 1
                    for (int it = 0; it < SPIN_MAX; it++) {
                        bool ok = true;
#pragma unroll
                        for (int k = 0; k < 16; k++) v[k] = ld_relaxed_b128(src + k * 4 * 64);
#pragma unroll
                        for (int k = 0; k < 16; k++) ok &= v[k].w == (float)(row + 1);
                        if (__all_sync(0xffffffffu, ok)) break;
                    }
#pragma unroll
                    for (int k = 0; k < 16; k++) { sx += v[k].x; sy += v[k].y; sz += v[k].z; }
                }
#pragma unroll
                for (int o = 8; o < 32; o <<= 1) {
                    sx += __shfl_xor_sync(0xffffffffu, sx, o); sy += __shfl_xor_sync(0xffffffffu, sy, o); sz += __shfl_xor_sync(0xffffffffu, sz, o);
                }
                if (lane < 8) st_relaxed_b128(&g_st.oacc[oidx(row, grp)], sx, sy, sz, UPB);
            }
        };
        const int ho0 = lane / 20 * 256 + lane % 20 * 4, ho1 = (lane + 32) / 20 * 256 + (lane + 32) % 20 * 4, ho2 = 3 * 256 + 16 + 2 * lane;
        uint32_t wr[10] = {};
        float wsum = 0.f;
        if (is_g(cta) && fw == 0) {
#pragma unroll
            for (int i = 0; i < 10; i++) {
                const int w = 4 * lane + 128 * (i >> 2) + (i & 3) - (i >= 8 ? 2 * lane : 0);
                wr[i] = *reinterpret_cast<const uint32_t*>(p.wr + (w >> 4) * 32 + (w & 3) * 8 + ((w >> 1) & 6));
                wsum += lo_f(wr[i]) + hi_f(wr[i]);
            }
            wsum = warp_sum(wsum);
        }
        const int fb = lane >> 3, fg = lane & 7;
        if (fw == 0) {
#pragma unroll
            for (int i = lane; i < DM / 2; i += 32) sts32f(sb + SM_X + 4 * HPITCH + i * 4, __uint_as_float(0x3f803f80u));
        }
        float nmean = 0.f, rden = 0.f, sig = 0.f;
#pragma unroll 1
        for (int b = 0; b < NB; b++) {
            const bool ffn = b >= NB - 2;
            if (fw == 0) {
                sum_rows((b + 1) * NH);
                if (ffn) asm volatile("bar.arrive 8, 64;" ::: "memory");
            } else if (ffn) {
                asm volatile("bar.sync 8, 64;" ::: "memory");
                if (lane == 0 && b == NB - 1) {
                    uint32_t t0 = 0, now;
#pragma unroll 1
                    for (int it = 0; it < SPIN_MAX; it++) {
                        t0 = ld_relaxed_u32(g_st.fw_time);
                        if (t0) break;
                        __nanosleep(400);
                    }
                    asm volatile("fence.proxy.async.shared::cta;" ::: "memory");
#pragma unroll 1
                    for (int it = 0; it < SPIN_MAX; it++) {
                        asm volatile("mov.u32 %0, %%globaltimer_lo;" : "=r"(now));
                        if ((int)(now - t0) >= FW_AT_NS) break;
                    }
                    TS2(9);
                    uint32_t t = clock() + (is_f(cta) ? (fi & 1) * FW_STAG : FW_MID + (fi & 3) * (FW_GAP2 / 4));
#pragma unroll 1
                    for (int i = 0; i < 8; i++) {
                        const uint32_t bar = sb + BAR_FW + i * 8;
                        while ((int)(clock() - t) < 0) {}
                        if (is_f(cta)) {
                            mbar_expect_tx(bar, 10240);
                            tma_box(sb + SM_W + i * 10240, (i & 1) ? &p.wu : &p.wg, fi * 32, (i >> 1) * 160, bar);
                            t += FW_GAP;
                        } else if (is_g(cta)) {
                            mbar_expect_tx(bar, 6144);
                            asm volatile("cp.async.bulk.tensor.4d.shared::cluster.global.mbarrier::complete_tx::bytes [%0], [%1, {%3, %4, %4, %5}], [%2];"
                                         :: "r"(sb + SM_W + i * 6144), "l"(&p.wd), "r"(bar), "r"(fi * 16), "r"(0), "r"(i * 12) : "memory");
                            t += FW_GAP2;
                        }
                    }
                }
                __syncwarp();
                if (is_f(cta)) {
                    const uint32_t* src = &g_st.hx.w[near_side(sb)][min(fb, b) * 256 + 96];
                    float4 m;
#pragma unroll 1
                    for (int it = 0; it < SPIN_MAX; it++) {
                        m = ld_relaxed_f4(src);
                        if (__all_sync(0xffffffffu, m.y + m.w == 2 * (NCTAS - NE_CTAS))) break;
                        if (b < NB - 1) __nanosleep(500);
                    }
                    moments(m.x, m.z, m.x, m.z);
                    sts64f(sb + SM_RED + 5120 + fb * 8, m.x, m.z);
                }
            }
            if (fw == 0 && cta >= NE_CTAS) {
                const int lc = cta - NE_CTAS, col = lc * 32 + 2 * (lane & 15);
                const uint32_t xv = *reinterpret_cast<const uint32_t*>(p.x + b * DM + col);
                uint32_t* dst = &(ffn ? g_st.hx.w : g_st.lx.w + 2)[lane >> 4][(b & 1) * 128 + lc / 5 * 256 + lc % 5 * 16 + (col & 6) * 2 + ((col >> 3) & 3)];
                uint32_t part = sb + SM_RED + (lane & 15) * 8;
                if (lane == 0) wait_row(b * NH + 28, 1);
                __syncwarp();
                float4 early;
#pragma unroll 1
                for (int it = 0; it < SPIN_MAX; it++) {
                    early = ld_relaxed_f4(&g_st.attn[b][col]);
                    if (__all_sync(0xffffffffu, early.y == NE_CTAS / 4 && early.w == NE_CTAS / 4)) break;
                }
                if (early.x != 1.2345f && lane == 0) TS2(6);
                CK(1, __float_as_uint(early.x));
                float x0 = lo_f(xv), x1 = hi_f(xv);
                pin(dst); pin(part); pin(x0); pin(x1);
                fin_sync<4>();
                CK(2, lds32(sb + SM_RED));
                const float2 late = sum8(part);
                const uint32_t hv = pack_neg(x0 + bf16r(early.x + late.x), x1 + bf16r(early.z + late.y));
                st_relaxed(dst, hv);
                if (HREP2 && ffn) st_relaxed(dst + 2048, hv);
                CK(3, 0);
                float m = lane < 16 ? lo_f(hv) + hi_f(hv) : fmaf(lo_f(hv), lo_f(hv), hi_f(hv) * hi_f(hv));
#pragma unroll
                for (int o = 1; o < 16; o <<= 1) m += __shfl_xor_sync(0xffffffffu, m, o);
                if ((lane & 14) == 0) red_f2(reinterpret_cast<float*>(&g_st.hx.w[lane & 1][b * 256 + 96 + (lane >> 4) * 2]), m, 1.f);
                fin_arrive<5>();
            }
            if (fw == 0 && (is_g(cta) || is_f(cta))) {
                const uint32_t* src = &(ffn ? g_st.hx.w : g_st.lx.w + 2)[near_side(sb) ^ (HREP2 && ffn && (HREP2 == 1 ? (fi & 1) : is_g(cta)) ? 3 : 0)][(b & 1) * 128];
                const uint32_t hrow = sb + SM_X + b * HPITCH;
                if (lane == 0) wait_row(b * NH + NH - 1, UPB);
                __syncwarp();
                uint4 h0, h1;
                uint2 h2;
                poll_row(h0, h1, h2, src + ho0, src + ho1, src + ho2, hrow + lane * 16, hrow + 1024 + lane * 8, ffn, b < NB - 1);
                CK(4, h0.x);
                if (!LSTAT || is_g(cta)) {
                const uint32_t hw[10] = {h0.x, h0.y, h0.z, h0.w, h1.x, h1.y, h1.z, h1.w, h2.x, h2.y};
                float s1[2] = {}, s2[2] = {};
#pragma unroll
                for (int i = 0; i < 10; i++) {
                    const float v0 = lo_f(hw[i]), v1 = hi_f(hw[i]);
                    s1[i & 1] += v0 + v1;
                    s2[i & 1] = fmaf(v0, v0, fmaf(v1, v1, s2[i & 1]));
                }
                float m1 = s1[0] + s1[1], m2 = s2[0] + s2[1];
#pragma unroll
                for (int o = 16; o; o >>= 1) { m1 += __shfl_xor_sync(0xffffffffu, m1, o); m2 += __shfl_xor_sync(0xffffffffu, m2, o); }
                moments(m1, m2, m1, m2);
                {
                    float rr = 0.f;
#pragma unroll
                    for (int i = 0; i < 10; i++) rr = fmaf(lo_f(hw[i]), lo_f(wr[i]), fmaf(hi_f(hw[i]), hi_f(wr[i]), rr));
                    const float sg = bf16r(sigmoid_approx(bf16r((m1 * wsum - warp_sum(rr)) * m2)));
                    if (fb == b) { nmean = m1; rden = m2; sig = sg; }
                    __syncwarp();
                    if (ffn) {
                        const int gi = fi, yj = 2 * (fb & 1) + (fb >> 1);
                        uint32_t ypart = sb + SM_RED2 + yj * 128 + ((fg + 2 * yj) & 7) * 16;
                        __nv_bfloat16* out = p.out + fb * DM + gi * 16 + fg;
                        const float2 hw2 = lds64f(sb + SM_X + fb * HPITCH + ((gi >> 1) * 16 + (fg & 6) * 2 + (gi & 1) * 2) * 4);
                        const uint32_t w0 = __float_as_uint(hw2.x), w1 = __float_as_uint(hw2.y);
                        float nh0 = (fg & 1) ? hi_f(w0) : lo_f(w0), nh1 = (fg & 1) ? hi_f(w1) : lo_f(w1);
                        float ln0 = bf16r(bf16r(nmean - nh0) * rden), ln1 = bf16r(bf16r(nmean - nh1) * rden);
                        pin(ypart); pin(out);
                        fin_sync<6>(after(after(after(288, sig), ln0), ln1));
                        CK(10, lds32(ypart));
                        const float4 ya = sum4x4(ypart, 512), yb = sum4x4(ypart + 2048, 512);
                        const float4 y = make_float4(ya.x + yb.x, ya.y + yb.y, ya.z + yb.z, ya.w + yb.w);
                        const float y0 = -(((fb & 1) ? y.y : y.x) + __shfl_xor_sync(0xffffffffu, (fb & 1) ? y.x : y.y, 8));
                        const float y1 = -(((fb & 1) ? y.w : y.z) + __shfl_xor_sync(0xffffffffu, (fb & 1) ? y.z : y.w, 8));
                        const uint32_t ov = pack_bf16(bf16r(ln0 + bf16r(bf16r(y0) * sig)) - nh0, bf16r(ln1 + bf16r(bf16r(y1) * sig)) - nh1);
                        if (b == NB - 1) {
                            asm volatile("st.global.u16 [%0], %1;" :: "l"(out), "h"((unsigned short)(ov & 0xffffu)) : "memory");
                            asm volatile("st.global.u16 [%0], %1;" :: "l"(out + 8), "h"((unsigned short)(ov >> 16)) : "memory");
                        }
                        CK(11, 0);
                        if (lane == 0) TS2(13);
                    }
                }
                }
            }
            if (is_f(cta) && ffn) {
                const int ks = (2 * fi + fw) % 12;
                uint32_t* dst = &g_st.ax[ks >> 2].w[(~b & 1) * 2][((fi / 6) * 32 + ((ks & 1) * 4 + fb) * 4 + (fg & 3)) * 4 + (ks & 2) + (fg >> 2)];
                uint32_t part = sb + SM_RED + fw * 2560 + fb * 128 + ((fg + (fb & 2)) & 7) * 16;
                uint32_t psum = sb + SM_RED + fw * 2560 + 4 * 128 + ((fg + 4) & 7) * 16;
                pin(dst); pin(part); pin(psum);
                asm volatile("bar.sync 4, 320;" ::: "memory");
                CK(6, lds32(part));
                const float4 d = sum4x4(part, 640), cs = sum4x4(psum, 640);
                const float2 mo = lds64f(sb + SM_RED + 5120 + fb * 8);
                nmean = mo.x; rden = mo.y;
                const float g0 = bf16r(fmaf(nmean, cs.x, -d.x) * rden), g1 = bf16r(fmaf(nmean, cs.y, -d.y) * rden);
                const float u0 = bf16r(fmaf(nmean, cs.z, -d.z) * rden), u1 = bf16r(fmaf(nmean, cs.w, -d.w) * rden);
                const uint32_t av = pack_neg(bf16r(g0 * sigmoid_approx(g0)) * u0, bf16r(g1 * sigmoid_approx(g1)) * u1);
                st_relaxed(dst, av);
                st_relaxed(dst + 1024, av);
                CK(7, 0);
            }
        }
        if (cta == 0 && tid == (NAUX + NWORK) * 32) { g_work[0] = 0; g_work[32] = 0; g_cnt_z[0] = 0; }
        return;
    }
    if (warp >= NAUX) {
        const int wk = warp - NAUX;
        const uint32_t bar = sb + BAR_KV + wk * (NPART * 8);
        const uint32_t buf = sb + SM_KV + wk * TILE_BYTES;
        uint64_t pol;
        asm volatile("createpolicy.fractional.L2::evict_first.b64 %0, 1.0;" : "=l"(pol));
        const int nstatic = NWORK * grid;
        constexpr int POOL0 = NUNITS - NPOOL;
        int uk = wk * grid + cta;
        if (K0_DELAY_NS) spin_ns(K0_DELAY_NS);
        __syncwarp();
        request_tile(buf, &p.k, uk, bar, pol);
        if (lane == 0) {
            if (wk == 0) {
                const uint32_t wbar = sb + BAR_WO;
                spin_ns(WO_AT_NS - K0_DELAY_NS);
                mbar_expect_tx(wbar, cta < NE_CTAS ? 61440 : 49152);
#pragma unroll 1
                for (int i = 0; i < (cta < NE_CTAS ? 5 : 4); i++) {
                    if (cta < NE_CTAS) tma_box(sb + SM_A + i * 12288, &p.wo, (cta & 3) * 160 + i * 32, (cta >> 2) * DH, wbar);
                    else tma_box(sb + SM_A + i * 12288, &p.wo, (cta - NE_CTAS) * 32, (28 + i) * DH, wbar);
                }
            }
        }
        __syncwarp();
        uint32_t koff[3], voff[3];
        {
            const int r = lane & 7, hf = (lane >> 3) & 1;
            const int kkey = hf ? 8 + (r ^ 1) : r;
            const int vh = lane >> 4;
            const int vkey = ((r & 1) ? 8 : 0) + (vh ? (r ^ 1) : r);
#pragma unroll
            for (int b = 0; b < 3; b++) {
                const int rk = 3 * kkey + b, rv = 3 * vkey + b;
                koff[b] = buf + rk * 128 + (((lane >> 4) ^ (rk & 7)) << 4);
                voff[b] = buf + rv * 128 + ((hf ^ (rv & 7)) << 4);
            }
        }
        uint32_t phase = 0;
        uint4 qf[6];
        auto load_q = [&](int u) {
            const uint32_t* q = &g_early[u / UPB].q[j * 4];
#pragma unroll
            for (int i = 0; i < 6; i++) qf[i] = ld_relaxed_v4(q + i * 16);
        };
        load_q(uk);
        int uq[LAG];
        uint32_t sq[LAG];
#pragma unroll
        for (int i = 0; i < LAG; i++) { uq[i] = -1; sq[i] = 0; }
        uint4 mv = make_uint4(0u, 0u, 0u, 0u);
        float freed = UPB;
        while (true) {
            const int uv = uq[0];
            uint32_t sv = sq[0];
#pragma unroll
            for (int i = 0; i + 1 < LAG; i++) { uq[i] = uq[i + 1]; sq[i] = sq[i + 1]; }
            uq[LAG - 1] = uk;
            if (uk < NUNITS) {
                PH(7);
#pragma unroll 1
                for (int it = 0; it < SPIN_MAX; it++) {
                    uint32_t lo = 0xffffffffu;
#pragma unroll
                    for (int i = 0; i < 6; i++) lo = min(min(lo, min(qf[i].x, qf[i].y)), min(qf[i].z, qf[i].w));
                    if (__all_sync(0xffffffffu, lo != 0)) break;
                    __nanosleep(250);
                    load_q(uk);
                }
#pragma unroll
                for (int t = 0; t < NPART; t++) mbar_wait(bar + t * 8, phase);
                phase ^= 1;
                PH(0); ARR();
                TSI(0, 16); TSI(1, 18);
                float acc[2][4][4] = {};
#pragma unroll
                for (int ks = 0; ks < 12; ks++) {
                    const uint4 qq = qf[ks >> 1];
                    const uint32_t b0 = (ks & 1) ? qq.z : qq.x, b1 = (ks & 1) ? qq.w : qq.y;
#pragma unroll
                    for (int mt = 0; mt < 4; mt++) {
                        uint32_t a[4];
                        ldsm4(a, (koff[ks >> 2] ^ ((ks & 3) << 5)) + mt * 6144);
                        mma16816(acc[ks & 1][mt], a, b0, b1);
                    }
                }
                PH(1);
                TSI(0, 17); TSI(1, 19);
                if (uv < NUNITS) request_tile(buf, uv >= 0 ? &p.v : &p.k, uv >= 0 ? uv : uk + nstatic, bar, pol);
                const float sa = sel4(j, acc[0][0][0], acc[0][1][0], acc[0][2][0], acc[0][3][0]) + sel4(j, acc[1][0][0], acc[1][1][0], acc[1][2][0], acc[1][3][0]);
                const float sc = sel4(j, acc[0][0][2], acc[0][1][2], acc[0][2][2], acc[0][3][2]) + sel4(j, acc[1][0][2], acc[1][1][2], acc[1][2][2], acc[1][3][2]);
                const uint32_t raw = pack_bf16(sa, sc);
                const float scale = -0.07216878364870322f;
                const uint32_t sk = pack_bf16(lo_f(raw) * scale, hi_f(raw) * scale);
                sq[LAG - 1] = sk;
                if (uk >= POOL0) st_relaxed(&g_st.score[uk - POOL0][lane], sk ? sk : 0x80008000u);
                int a = (int)(sk << 16), b = (int)(sk & 0xffff0000u);
                a ^= (a >> 31) & 0x7fff0000; b ^= (b >> 31) & 0x7fff0000;
                const int mx = __reduce_max_sync(0xffffffffu, max(a, b));
                if (lane == 0) st_relaxed(&g_early[uk / UPB].umax[uk % UPB], (uint32_t)mx | 1u);
            }
            if (uv < 0) {
                uk += nstatic;
                load_q(uk);
                continue;
            }
            if (uv >= NUNITS) break;
            const int bh = uv / UPB;
#pragma unroll 1
            for (int it = 0; it < SPIN_MAX; it++) {
                if (__all_sync(0xffffffffu, (mv.x & mv.y & mv.z & mv.w & 1u) && (uv < POOL0 || sv != 0) && freed == UPB)) break;
                mv = ld_relaxed_v4(&g_early[bh].umax[lane * 4]);
                if (bh >= RING && bh < RED0) freed = __uint_as_float(ld_relaxed_u32(&g_st.oacc[oidx(bh - RING, (lane & 7) * 8)].w));
                if (uv >= POOL0) sv = ld_relaxed_u32(&g_st.score[uv - POOL0][lane]);
            }
            PH(2);
            int un = NUNITS, vn = 0;
            draw(un, g_work, uk < NUNITS && lane == 0);
            uint32_t tdraw;
            asm volatile("mov.u32 %0, %%globaltimer_lo;" : "=r"(tdraw));
            draw(vn, g_work + 32, uq[0] >= POOL0 && lane == 0);
            int mx = __reduce_max_sync(0xffffffffu, max(max((int)mv.x, (int)mv.y), max((int)mv.z, (int)mv.w))) & 0xffff0000;
            mx ^= (mx >> 31) & 0x7fff0000;
            const float m = __int_as_float(mx);
            const float l2e = 1.4426950408889634f;
            const uint32_t pp = pack_bf16(exp2f((lo_f(sv) - m) * l2e), exp2f((hi_f(sv) - m) * l2e));
            uint32_t pb[8];
#pragma unroll
            for (int t = 0; t < 4; t++) {
                pb[2 * t] = __shfl_sync(0xffffffffu, pp, 8 * j + t);
                pb[2 * t + 1] = __shfl_sync(0xffffffffu, pp, 8 * j + 4 + t);
            }
            float lacc[4] = {};
            const uint32_t ones[4] = {0x3f803f80u, 0x3f803f80u, 0x3f803f80u, 0x3f803f80u};
#pragma unroll
            for (int t = 0; t < 4; t++) mma16816(lacc, ones, pb[2 * t], pb[2 * t + 1]);
            if (uv < nstatic) {
                asm volatile("bar.sync 2, %0;" :: "n"((NWORK + 2) * 32) : "memory");
                TSW(3);
            }
            const int grp = 16 * j + 4 * (g & 1) + (g >> 1);
            uint32_t mode = (bh >= RED0) + (bh >= NBH - 4);
            float tag = mode ? 1.f : (float)(bh + 1), tag2 = tag;
            void* dst = mode == 0 ? (void*)&g_ring[bh % RING][uv % UPB][grp] :
                        mode == 1 ? (void*)&g_st.oacc[oidx(bh, grp)] : (void*)&g_st.ox[uv % OREP].w[0][oidx(bh & 3, grp) * 4];
            if (mode == 2 && lane < 2) red_f2(reinterpret_cast<float*>(&g_st.lx.w[lane][(bh & 3) * 256]), lacc[0], 1.f);
            un = __shfl_sync(0xffffffffu, un, 0) + (LAG + 1) * nstatic;
            vn = __shfl_sync(0xffffffffu, vn, 0);
            if (uq[0] >= POOL0) uq[0] = POOL0 + vn;
            if (vn == FW_TICKET && lane == 0) st_relaxed(g_st.fw_time, tdraw | 1u);
            pin(dst); pin(mode); pin(tag); pin(tag2); pin(voff[0]); pin(voff[1]); pin(voff[2]);
            PH(3);
            float acc[12][4] = {};
#pragma unroll
            for (int t = 0; t < 4; t++) {
                if (t % (4 / NPART) == 0) mbar_wait(bar + t / (4 / NPART) * 8, phase);
                if (t == 4 - 4 / NPART) { PH(4); ARR(); CK(12, lds32(buf)); }
#pragma unroll
                for (int mt = 0; mt < 12; mt++) {
                    uint32_t a[4];
                    ldsm4t(a, (voff[mt >> 2] ^ ((mt & 3) << 5)) + t * 6144);
                    mma16816(acc[mt], a, pb[2 * t], pb[2 * t + 1]);
                }
            }
            phase ^= 1;
            PH(5);
            if (lane == 0) PROG(un);
            if (un < NUNITS || uq[0] < NUNITS) request_tile(buf, un < NUNITS ? &p.k : &p.v, un < NUNITS ? un : uq[0], bar, pol);
            float o[6];
#pragma unroll
            for (int e = 0; e < 6; e++) {
                const int q = e % 3, c = (e / 3) * 2;
                o[e] = sel4(j, acc[q][c], acc[3 + q][c], acc[6 + q][c], acc[9 + q][c]);
            }
            put_groups(dst, mode, o, tag, tag2);
            CK(13, 0);
            if (un < NUNITS) load_q(un);
            if (lane == 0) red_f2(&g_st.lsum[bh][0].x, lacc[0], 1.f);
            PH(6);
            if (uq[0] >= NUNITS && un >= NUNITS) break;
            uk = un;
            if (uq[0] < NUNITS) {
                const int nb = uq[0] / UPB;
                mv = ld_relaxed_v4(&g_early[nb].umax[lane * 4]);
                freed = nb >= RING && nb < RED0 ? __uint_as_float(ld_relaxed_u32(&g_st.oacc[oidx(nb - RING, (lane & 7) * 8)].w)) : UPB;
                if (uq[0] >= POOL0) sq[0] = ld_relaxed_u32(&g_st.score[uq[0] - POOL0][lane]);
            }
        }
        TSW(4 + wk);
        return;
    }

    __nv_bfloat16* xs = reinterpret_cast<__nv_bfloat16*>(smem + SM_X);
    float* red = reinterpret_cast<float*>(smem + SM_RED);
    const int frow = (lane & 7) + ((lane >> 4) << 3), fcol = (lane >> 3) & 1;
    const uint32_t f32b = sb + (frow * 2 + (fcol ^ ((frow >> 2) & 1))) * 16;
    const uint32_t f64b = sb + (frow * 4 + (fcol ^ ((frow >> 1) & 3))) * 16;
    if (cta < NQ_CTAS) {
        uint2 xr[5];
        if (warp < NB) {
#pragma unroll
            for (int i = 0; i < 5; i++) xr[i] = *reinterpret_cast<const uint2*>(p.x + warp * DM + i * 128 + lane * 4);
        }
        TS(26);
        if (warp < NB) {
            float v[20];
#pragma unroll
            for (int i = 0; i < 5; i++) {
                v[4 * i] = lo_f(xr[i].x); v[4 * i + 1] = hi_f(xr[i].x); v[4 * i + 2] = lo_f(xr[i].y); v[4 * i + 3] = hi_f(xr[i].y);
            }
            layernorm20(v);
#pragma unroll
            for (int i = 0; i < 5; i++)
                *reinterpret_cast<uint2*>(xs + warp * XPITCH + i * 128 + lane * 4) =
                    make_uint2(pack_bf16(v[4 * i], v[4 * i + 1]), pack_bf16(v[4 * i + 2], v[4 * i + 3]));
        }
        TS(27);
        aux_sync();
        mbar_wait(sb + BAR_WQ, 0);
        TS(1);
        const uint32_t xfrag = sb + SM_X + ((g & 3) * XPITCH + 2 * j) * 2;
        float acc[3][4] = {};
#pragma unroll
        for (int s = 0; s < 5; s++) {
            const int ks = warp * 5 + s;
            const uint32_t b0 = lds32(xfrag + ks * 32), b1 = lds32(xfrag + ks * 32 + 16);
            const int row = ks * 16 + frow;
#pragma unroll
            for (int mt = 0; mt < 3; mt++) {
                uint32_t a[4];
                ldsm4t(a, sb + SM_W + (row * 6 + 2 * mt + fcol) * 16);
                mma16816(acc[mt], a, b0, b1);
            }
        }
        if (j < 2) {
#pragma unroll
            for (int mt = 0; mt < 3; mt++) {
                *reinterpret_cast<float2*>(red + (warp * 48 + mt * 16 + g) * 4 + 2 * j) = make_float2(acc[mt][0], acc[mt][1]);
                *reinterpret_cast<float2*>(red + (warp * 48 + mt * 16 + 8 + g) * 4 + 2 * j) = make_float2(acc[mt][2], acc[mt][3]);
            }
        }
        aux_sync();
        if (tid < 96) {
            const int b = tid & 3, cp = tid >> 2;
            float s0 = 0.f, s1 = 0.f;
#pragma unroll
            for (int w = 0; w < 8; w++) { s0 += red[(w * 48 + 2 * cp) * 4 + b]; s1 += red[(w * 48 + 2 * cp + 1) * 4 + b]; }
            const int h = cta >> 2, d = (cta & 3) * 48 + 2 * cp;
            const int ch = d >> 3, jj = (d & 7) >> 1;
            st_relaxed(&g_early[b * NH + h].q[(ch >> 2) * 16 + jj * 4 + (ch & 3)], pack_neg(s0, s1));
        }
        TS(28);
    }
    fin_sync<3>();
    mbar_wait(sb + BAR_WO, 0);
    TS(7);
    uint32_t part = sb + SM_RED + (warp * 32 + 8 * j + g) * 4;

#pragma unroll 1
    for (int b = 0; b < NB; b++) {
        if (cta >= NE_CTAS) {
            uint32_t a[6][2][4];
#pragma unroll
            for (int s = 0; s < 6; s++) {
#pragma unroll
                for (int mt = 0; mt < 2; mt++) ldsm4t(a[s][mt], (f64b ^ (mt * 32)) + SM_A + (warp * 6 + s) * 1024);
            }
            const int bh = b * NH + 28 + (warp >> 1);
            const int side = near_side(sb) ^ 1;
            const void* osrc[OREP];
#pragma unroll
            for (int c = 0; c < OREP; c++)
                osrc[c] = b == NB - 1 ? (const void*)&g_st.ox[c].w[side][oidx(bh & 3, (warp & 1) * 32 + lane) * 4] : &g_st.oacc[oidx(bh, (warp & 1) * 32 + lane)];
            const void* lsrc = b == NB - 1 ? (const void*)&g_st.lx.w[side][(bh & 3) * 256] : g_st.lsum[bh];
            if (lane == 0) wait_row_o(bh, 1);
            __syncwarp();
            float2 lv;
#pragma unroll 1
            for (int it = 0; it < SPIN_MAX; it++) {
                lv = ld_relaxed_f2(lsrc);
                if (lv.y == UPB) break;
            }
            __syncwarp();
            float rl = rcp_approx(lv.x) * (b == NB - 1 ? 1.f : 1.f / OREP), full = b == NB - 1 ? UPB : UPB * OREP;
            float4 ov;
            pin(part); pin(rl); pin(full);
#pragma unroll 1
            for (int it = 0; it < SPIN_MAX; it++) {
                float4 oc[OREP];
#pragma unroll
                for (int c = 0; c < OREP; c++) oc[c] = ld_relaxed_f4(osrc[c]);
                ov = oc[0];
#pragma unroll
                for (int c = 1; c < OREP; c++) { ov.x += oc[c].x; ov.y += oc[c].y; ov.z += oc[c].z; ov.w += oc[c].w; }
                if (__all_sync(0xffffffffu, ov.w == full)) break;
            }
            CK(0, __float_as_uint(ov.x));
            if (ov.x != 1.2345f && warp == 7) TSW(14);
            const float px = __shfl_xor_sync(0xffffffffu, ov.x, 4), py = __shfl_xor_sync(0xffffffffu, ov.y, 4),
                        pz = __shfl_xor_sync(0xffffffffu, ov.z, 4);
            const uint32_t w[3] = {pack_bf16(ov.x * rl, px * rl), pack_bf16(ov.y * rl, py * rl), pack_bf16(ov.z * rl, pz * rl)};
            float acc[2][2][4] = {};
#pragma unroll
            for (int s = 0; s < 6; s++) {
                const uint32_t b0 = __shfl_sync(0xffffffffu, w[s % 3], (s / 3) * 16 + j);
                const uint32_t b1 = __shfl_sync(0xffffffffu, w[s % 3], (s / 3) * 16 + 8 + j);
#pragma unroll
                for (int mt = 0; mt < 2; mt++) mma16816(acc[mt][s & 1], a[s][mt], b0, b1);
            }
            sts32f(part, sel4(j, acc[0][0][0] + acc[0][1][0], acc[0][0][2] + acc[0][1][2], acc[1][0][0] + acc[1][1][0], acc[1][0][2] + acc[1][1][2]));
            CK(1, 0);
            fin_arrive<4>();
            fin_sync<5>();
            if (cta < NE_CTAS + 4 && tid < 56) reinterpret_cast<uint4*>(&g_early[b * NH + 28 + cta - NE_CTAS])[tid] = make_uint4(0u, 0u, 0u, 0u);
        } else {
            const int bh = b * NH + (cta >> 2);
            if (tid == 0) wait_row_o(bh, UPB);
            aux_sync();
            if (warp < 5) {
                uint32_t ob[12][2];
                load_o<4>(ob, bh, 0, j);
                float acc[2][2][4] = {};
#pragma unroll
                for (int ks = 0; ks < 12; ks++) {
#pragma unroll
                    for (int mt = 0; mt < 2; mt++) {
                        uint32_t a[4];
                        ldsm4t(a, (f64b ^ (mt * 32)) + SM_A + warp * 12288 + ks * 1024);
                        mma16816(acc[mt][ks & 1], a, ob[ks][0], ob[ks][1]);
                    }
                }
                red_f2(&g_st.attn[b][(cta & 3) * 160 + warp * 32 + 8 * j + g].x,
                       sel4(j, acc[0][0][0] + acc[0][1][0], acc[0][0][2] + acc[0][1][2], acc[1][0][0] + acc[1][1][0], acc[1][0][2] + acc[1][1][2]), 1.f);
                TS(8);
            } else if (warp > 5 && (cta & 3) == 0 && tid - 192 < 56) {
                reinterpret_cast<uint4*>(&g_early[bh])[tid - 192] = make_uint4(0u, 0u, 0u, 0u);
            }
        }
        if (b < NB - 2) continue;

        if (is_f(cta)) {
            uint32_t ga[10][2][4];
            uint4 hv[5] = {};
            const uint32_t hfrag = sb + SM_X + min(g, 4) * HPITCH + ((warp >> 1) * 80 + 4 * j) * 4;
#pragma unroll
            for (int s = 0; s < 5; s++) lds128_if(hv[s], hfrag + s * 64, b == NB - 1);
            if (b == NB - 1) mbar_wait(sb + BAR_FW + warp * 8, 0);
            if (warp == 7) TSW(10);
            CK(12, lds32(sb + SM_W));
#pragma unroll
            for (int s = 0; s < 10; s++) {
#pragma unroll
                for (int mt = 0; mt < 2; mt++) ldsm4t(ga[s][mt], (f64b ^ (mt * 32)) + SM_W + (warp * 10 + s) * 1024);
            }
            const uint32_t gpart = sb + SM_RED + (warp >> 1) * 640 + j * 256 + ((g + 2 * j) & 7) * 16 + (warp & 1) * 8;
            fin_sync<7>();
#pragma unroll
            for (int s = 0; s < 5; s++) lds128_if(hv[s], hfrag + s * 64, g == b);
            CK(4, hv[0].x);
            float acc[2][2][4] = {};
#pragma unroll
            for (int s = 0; s < 10; s++) {
#pragma unroll
                for (int mt = 0; mt < 2; mt++)
                    mma16816(acc[mt][s & 1], ga[s][mt], (s & 1) ? hv[s >> 1].z : hv[s >> 1].x, (s & 1) ? hv[s >> 1].w : hv[s >> 1].y);
            }
#pragma unroll
            for (int mt = 0; mt < 2; mt++) {
                if (j < 3) sts64f(gpart + mt * 2560, acc[mt][0][0] + acc[mt][1][0], acc[mt][0][2] + acc[mt][1][2]);
                if (j < 2) sts64f(gpart + mt * 2560 + 128, acc[mt][0][1] + acc[mt][1][1], acc[mt][0][3] + acc[mt][1][3]);
            }
            CK(5, 0);
            asm volatile("bar.arrive 4, 320;" ::: "memory");
        } else if (is_g(cta)) {
            uint32_t wb[12][4];
            if (b == NB - 1) mbar_wait(sb + BAR_FW + warp * 8, 0);
            if (warp == 7) TSW(11);
            CK(13, lds32(sb + SM_W));
#pragma unroll
            for (int s = 0; s < 12; s++) ldsm4t(wb[s], f32b + SM_W + (warp * 12 + s) * 512);
            const uint32_t* asrc = &g_st.ax[0].w[(~b & 1) * 2 + near_side(sb)][(warp * 32 + lane) * 4];
            uint32_t ypart = sb + SM_RED2 + warp * 512 + j * 128 + ((g + 2 * j) & 7) * 16;
            pin(ypart);
            fin_sync<7>();
            uint4 va[3];
#pragma unroll 1
            for (int it = 0; it < SPIN_MAX; it++) {
                uint32_t lo = 0xffffffffu;
#pragma unroll
                for (int i = 0; i < 3; i++) va[i] = ld_relaxed_v4(asrc + i * 4096);
#pragma unroll
                for (int i = 0; i < 3; i++) lo = min(min(lo, min(va[i].x, va[i].y)), min(va[i].z, va[i].w));
                if (__all_sync(0xffffffffu, lo != 0)) break;
            }
            CK(8, va[0].x);
            if (va[0].x != 0x12345 && warp == 7) TSW(15);
            float acc[4][4] = {};
#pragma unroll
            for (int s = 0; s < 12; s++) {
                const uint4 v = va[s >> 2];
                mma16816(acc[s & 3], wb[s], (s & 2) ? v.z : v.x, (s & 2) ? v.w : v.y);
            }
            float y[4];
#pragma unroll
            for (int e = 0; e < 4; e++) y[e] = j < 2 ? acc[0][e] + acc[2][e] : acc[1][e] + acc[3][e];
            sts128f(ypart, y[0], y[1], y[2], y[3]);
            CK(9, 0);
            fin_arrive<6>();
        }
    }
}

typedef CUresult (*EncodeFn)(CUtensorMap*, CUtensorMapDataType, cuuint32_t, void*, const cuuint64_t*, const cuuint64_t*,
                             const cuuint32_t*, const cuuint32_t*, CUtensorMapInterleave, CUtensorMapSwizzle,
                             CUtensorMapL2promotion, CUtensorMapFloatOOBfill);

CUtensorMap make_map(EncodeFn enc, void* ptr, uint64_t cols, uint64_t rows, uint32_t bcols, uint32_t brows,
                     CUtensorMapSwizzle sw, CUtensorMapL2promotion promo) {
    CUtensorMap m;
    const cuuint64_t dims[2] = {cols, rows};
    const cuuint64_t strides[1] = {cols * 2};
    const cuuint32_t box[2] = {bcols, brows};
    const cuuint32_t es[2] = {1, 1};
    enc(&m, CU_TENSOR_MAP_DATA_TYPE_BFLOAT16, 2, ptr, dims, strides, box, es, CU_TENSOR_MAP_INTERLEAVE_NONE, sw, promo,
        CU_TENSOR_MAP_FLOAT_OOB_FILL_NONE);
    return m;
}

}

extern "C" void kernel_launch(void* const* d_in, const int* in_sizes, int n_in, void* d_out, int out_size) {
    (void)in_sizes; (void)n_in; (void)out_size;
    static EncodeFn enc = nullptr;
    static int sms = 0;
    if (!enc) {
        cudaDriverEntryPointQueryResult qr;
        cudaGetDriverEntryPoint("cuTensorMapEncodeTiled", (void**)&enc, cudaEnableDefault, &qr);
        int dev = 0;
        cudaGetDevice(&dev);
        cudaDeviceGetAttribute(&sms, cudaDevAttrMultiProcessorCount, dev);
        cudaFuncSetAttribute(fused_decode_kernel, cudaFuncAttributeMaxDynamicSharedMemorySize, SM_TOTAL);
    }
    if (sms < NCTAS) return;
    const CUtensorMapL2promotion WPROMO = CU_TENSOR_MAP_L2_PROMOTION_L2_128B;
#define GPROMO 2
#define DPROMO 2
    Params p;
    p.k = make_map(enc, d_in[1], 64, (uint64_t)NBH * SK * 3, 64, TILE_ROWS / NPART, CU_TENSOR_MAP_SWIZZLE_128B, CU_TENSOR_MAP_L2_PROMOTION_NONE);
    p.v = make_map(enc, d_in[2], 64, (uint64_t)NBH * SK * 3, 64, TILE_ROWS / NPART, CU_TENSOR_MAP_SWIZZLE_128B, CU_TENSOR_MAP_L2_PROMOTION_NONE);
    p.wq = make_map(enc, d_in[3], NH * DH, DM, 48, 160, CU_TENSOR_MAP_SWIZZLE_NONE, WPROMO);
    p.wo = make_map(enc, d_in[4], DM, NH * DH, 32, DH, CU_TENSOR_MAP_SWIZZLE_64B, WPROMO);
    p.wg = make_map(enc, d_in[7], FF, DM, 32, 160, CU_TENSOR_MAP_SWIZZLE_64B, (CUtensorMapL2promotion)GPROMO);
    p.wu = make_map(enc, d_in[8], FF, DM, 32, 160, CU_TENSOR_MAP_SWIZZLE_64B, (CUtensorMapL2promotion)GPROMO);
    {
        const cuuint64_t dims[4] = {DM, 2, 8, FF / 16}, strides[3] = {8 * DM * 2, DM * 2, 16 * DM * 2};
        const cuuint32_t box[4] = {16, 2, 8, 12}, es[4] = {1, 1, 1, 1};
        enc(&p.wd, CU_TENSOR_MAP_DATA_TYPE_BFLOAT16, 4, d_in[9], dims, strides, box, es, CU_TENSOR_MAP_INTERLEAVE_NONE,
            CU_TENSOR_MAP_SWIZZLE_32B, (CUtensorMapL2promotion)DPROMO, CU_TENSOR_MAP_FLOAT_OOB_FILL_NONE);
    }
    p.x = (const __nv_bfloat16*)d_in[0];
    p.wr = (const __nv_bfloat16*)d_in[6];
    p.out = (__nv_bfloat16*)d_out;
    fused_decode_kernel<<<NCTAS, NTHREADS, SM_TOTAL, cudaStreamPerThread>>>(p);
}
```

```cpp
#include <cuda_runtime.h>
#include <cuda_bf16.h>
#include <cuda.h>
#include <stdint.h>

namespace {

constexpr int NB = 4, NH = 32, SK = 8192, DH = 192, DM = 640, FF = 1536;
constexpr int NBH = NB * NH;
constexpr int TILE = 64;
constexpr int UPB = SK / TILE;
constexpr int NUNITS = NBH * UPB;
constexpr int TILE_BYTES = TILE * DH * 2;
constexpr int TILE_ROWS = TILE * 3;
constexpr int NCTAS = 132;
constexpr int NQ_CTAS = 128;
constexpr int NE_CTAS = 112;
#define ROLES 1
__host__ __device__ constexpr bool is_f(int cta) { return cta < 96 && !(cta & 2); }
__host__ __device__ constexpr bool is_g(int cta) { return cta < 80 && (cta & 2); }
__host__ __device__ constexpr int ffn_slice(int cta) { return (cta >> 2) * 2 + (cta & 1); }

#define NWORK 2
#define NPART 1
#define NSPARE 1
#define SPARE_NS 0
#define LAG 2
#define NPOOL 640
#define RED0 116
#define RING 12
#define OREP 3
#define K0_DELAY_NS 1000
#define WO_AT_NS 3800
#define FW_TICKET 400
#define FW_AT_NS 3840
#define FW_GAP 320
#define FW_GAP2 200
#define FW_STAG (FW_GAP / 2)
#define HREP2 2
#define LSTAT 1
#define NPROBE 24
#define SIDE_XOR 0
#define FW_MID 2300
constexpr int NAUX = 8;
constexpr int NTHREADS = (NAUX + NWORK + 2) * 32;
constexpr int SPIN_MAX = 1 << 22;

constexpr int SM_KV = 0;
constexpr int SM_A = SM_KV + NWORK * TILE_BYTES;
constexpr int SM_W = SM_A + 61440;
constexpr int SM_X = SM_W + 81920;
constexpr int XPITCH = 648;
constexpr int HPITCH = 1344;
constexpr int SM_RED = SM_X + 5 * HPITCH + 64;
constexpr int SM_RED2 = SM_RED + 8 * 48 * 4 * 4;
constexpr int SM_MISC = SM_RED2 + 4096;
constexpr int BAR_WQ = SM_MISC + 32, BAR_WO = SM_MISC + 40, SM_SIDE = SM_MISC + 48, BAR_FW = SM_MISC + 64;
constexpr int BAR_KV = BAR_FW + 64;
constexpr int SM_TOTAL = BAR_KV + 2 * NWORK * NPART * 8;
static_assert(LAG == 2 && SM_W % 1024 == 0 && NB * XPITCH * 2 <= 4 * HPITCH && SM_RED % 128 == 0, "smem layout");

struct Params {
    CUtensorMap k, v;
    CUtensorMap wq;
    CUtensorMap wo;
    CUtensorMap wg, wu;
    CUtensorMap wd;
    const __nv_bfloat16 *x, *wr;
    __nv_bfloat16* out;
};

struct Early {
    uint32_t q[96];
    uint32_t umax[UPB];
};
struct Twin { uint32_t w[4][1024]; };
constexpr int PROBE = 1024 - 32;
#define LSTRIDE 16
struct State {
    Twin ax[3];
    Twin hx;
    Twin ox[OREP];
    Twin lx;
    float4 oacc[NBH * 64];
    float2 attn[NB][DM];
    uint32_t fw_time[32];
    float2 lsum[NBH][LSTRIDE];
    uint32_t score[NPOOL][32];
};
__host__ __device__ constexpr int oidx(int row, int grp) {
    return (row >> 2) * 256 + ((row & 1) * 2 + (grp >> 5)) * 64 + (row & 2) * 16 + (grp & 31);
}
constexpr int STATE_V4 = ((sizeof(State) / 32 + NQ_CTAS - 1) / NQ_CTAS) * 2;
static_assert(sizeof(State) % 32 == 0, "State is cleared in whole sectors");
static_assert(sizeof(Early) == 56 * 16, "an Early entry is cleared by 56 threads");
struct Scratch {
    State st;
    unsigned work[64];
    unsigned cnt_z[32];
    Early early[NBH];
    alignas(4096) float4 ring[RING][UPB][64];
};
constexpr size_t PAGE = 2u << 20;
static_assert(sizeof(Scratch) <= PAGE, "scratch must fit one page");
__device__ __align__(128) unsigned char g_raw[2 * PAGE];
__device__ __forceinline__ Scratch* scratch() {
    return reinterpret_cast<Scratch*>((reinterpret_cast<uintptr_t>(g_raw) + PAGE - 1) & ~(uintptr_t)(PAGE - 1));
}
#define g_early scratch()->early
#define g_st scratch()->st
#define g_ring scratch()->ring
#define g_cnt_z scratch()->cnt_z
#define g_work scratch()->work
#define TS(i)
#define TSW(i)
#define TS2(i)
#define TSI(n, i)
#define PH(i)
#define CK(i, dep)
#define ARR()
#define PROG(u)

__device__ __forceinline__ uint32_t s2u(const void* p) { return (uint32_t)__cvta_generic_to_shared(p); }
__device__ __forceinline__ void mbar_init(uint32_t bar, int cnt) {
    asm volatile("mbarrier.init.shared::cta.b64 [%0], %1;" :: "r"(bar), "r"(cnt) : "memory");
}
__device__ __forceinline__ void mbar_expect_tx(uint32_t bar, uint32_t bytes) {
    asm volatile("mbarrier.arrive.expect_tx.shared::cta.b64 _, [%0], %1;" :: "r"(bar), "r"(bytes) : "memory");
}
__device__ __forceinline__ void mbar_wait(uint32_t bar, uint32_t parity) {
    asm volatile("{\n.reg .pred p;\n.reg .u32 n;\nmov.u32 n, 0;\nWAIT_LOOP:\n"
                 "mbarrier.try_wait.parity.shared::cta.b64 p, [%0], %1;\n"
                 "@p bra WAIT_DONE;\nadd.u32 n, n, 1;\nsetp.lt.u32 p, n, %2;\n@p bra WAIT_LOOP;\nWAIT_DONE:\n}"
                 :: "r"(bar), "r"(parity), "n"(SPIN_MAX) : "memory");
}
__device__ __forceinline__ void request_tile(uint32_t dst, const CUtensorMap* tm, int unit, uint32_t bar, uint64_t pol) {
#pragma unroll
    for (int i = 0; i < NPART; i++)
        asm volatile("{\n.reg .pred p;\nelect.sync _|p, 0xffffffff;\n"
                     "@p mbarrier.arrive.expect_tx.shared::cta.b64 _, [%2], %6;\n"
                     "@p cp.async.bulk.tensor.2d.shared::cluster.global.mbarrier::complete_tx::bytes.L2::cache_hint "
                     "[%0], [%1, {%3, %4}], [%2], %5;\n}"
                     :: "r"(dst + i * (TILE_BYTES / NPART)), "l"(tm), "r"(bar + i * 8), "r"(0), "r"(unit * TILE_ROWS + i * (TILE_ROWS / NPART)),
                        "l"(pol), "n"(TILE_BYTES / NPART) : "memory");
}
__device__ __forceinline__ void put_groups(void* dst, int mode, const float (&o)[6], float tag, float tag2) {
    asm volatile("{\n.reg .pred s, r, t;\n.reg .b128 u, v;\n.reg .b64 a, b;\n"
                 "setp.eq.s32 s|r, %1, 0;\nsetp.eq.s32 t, %1, 2;\n"
                 "@r red.relaxed.gpu.global.add.v4.f32 [%0], {%2,%3,%4,%8};\n"
                 "@t red.relaxed.gpu.global.add.v4.f32 [%0+4096], {%2,%3,%4,%8};\n"
                 "@r red.relaxed.gpu.global.add.v4.f32 [%0+128], {%5,%6,%7,%9};\n"
                 "@t red.relaxed.gpu.global.add.v4.f32 [%0+4224], {%5,%6,%7,%9};\n"
                 "mov.b64 a, {%2, %3};\nmov.b64 b, {%4, %8};\nmov.b128 u, {a, b};\n"
                 "mov.b64 a, {%5, %6};\nmov.b64 b, {%7, %9};\nmov.b128 v, {a, b};\n"
                 "@s st.relaxed.gpu.global.b128 [%0], u;\n@s st.relaxed.gpu.global.b128 [%0+128], v;\n}"
                 :: "l"(dst), "r"(mode), "f"(o[0]), "f"(o[1]), "f"(o[2]), "f"(o[3]), "f"(o[4]), "f"(o[5]), "f"(tag), "f"(tag2) : "memory");
}
__device__ __forceinline__ void tma_box(uint32_t dst, const CUtensorMap* tm, int col, int row, uint32_t bar) {
    asm volatile("cp.async.bulk.tensor.2d.shared::cluster.global.mbarrier::complete_tx::bytes [%0], [%1, {%3, %4}], [%2];"
                 :: "r"(dst), "l"(tm), "r"(bar), "r"(col), "r"(row) : "memory");
}
__device__ __forceinline__ uint32_t lds32(uint32_t addr) {
    uint32_t v;
    asm volatile("ld.shared.u32 %0, [%1];" : "=r"(v) : "r"(addr) : "memory");
    return v;
}
__device__ __forceinline__ void ldsm4(uint32_t (&r)[4], uint32_t addr) {
    asm volatile("ldmatrix.sync.aligned.m8n8.x4.shared.b16 {%0,%1,%2,%3}, [%4];"
                 : "=r"(r[0]), "=r"(r[1]), "=r"(r[2]), "=r"(r[3]) : "r"(addr) : "memory");
}
__device__ __forceinline__ void ldsm4t(uint32_t (&r)[4], uint32_t addr) {
    asm volatile("ldmatrix.sync.aligned.m8n8.x4.trans.shared.b16 {%0,%1,%2,%3}, [%4];"
                 : "=r"(r[0]), "=r"(r[1]), "=r"(r[2]), "=r"(r[3]) : "r"(addr) : "memory");
}
__device__ __forceinline__ void mma16816(float (&c)[4], const uint32_t (&a)[4], uint32_t b0, uint32_t b1) {
    asm volatile("mma.sync.aligned.m16n8k16.row.col.f32.bf16.bf16.f32 {%0,%1,%2,%3}, {%4,%5,%6,%7}, {%8,%9}, {%0,%1,%2,%3};"
                 : "+f"(c[0]), "+f"(c[1]), "+f"(c[2]), "+f"(c[3])
                 : "r"(a[0]), "r"(a[1]), "r"(a[2]), "r"(a[3]), "r"(b0), "r"(b1));
}
__device__ __forceinline__ uint4 ld_relaxed_v4(const void* p) {
    uint4 v;
    asm volatile("ld.relaxed.gpu.global.v4.u32 {%0,%1,%2,%3}, [%4];" : "=r"(v.x), "=r"(v.y), "=r"(v.z), "=r"(v.w) : "l"(p) : "memory");
    return v;
}
__device__ __forceinline__ float4 ld_relaxed_f4(const void* p) {
    float4 v;
    asm volatile("ld.relaxed.gpu.global.v4.f32 {%0,%1,%2,%3}, [%4];" : "=f"(v.x), "=f"(v.y), "=f"(v.z), "=f"(v.w) : "l"(p) : "memory");
    return v;
}
__device__ __forceinline__ float2 ld_relaxed_f2(const void* p) {
    float2 v;
    asm volatile("ld.relaxed.gpu.global.v2.f32 {%0,%1}, [%2];" : "=f"(v.x), "=f"(v.y) : "l"(p) : "memory");
    return v;
}
__device__ __forceinline__ float4 ld_relaxed_b128(const void* p) {
    float4 v;
    asm volatile("{\n.reg .b128 t;\n.reg .b64 a, b;\nld.relaxed.gpu.global.b128 t, [%4];\nmov.b128 {a, b}, t;\n"
                 "mov.b64 {%0, %1}, a;\nmov.b64 {%2, %3}, b;\n}" : "=f"(v.x), "=f"(v.y), "=f"(v.z), "=f"(v.w) : "l"(p) : "memory");
    return v;
}
__device__ __forceinline__ void st_relaxed_b128(void* p, float x, float y, float z, float w) {
    asm volatile("{\n.reg .b128 t;\n.reg .b64 a, b;\nmov.b64 a, {%1, %2};\nmov.b64 b, {%3, %4};\nmov.b128 t, {a, b};\n"
                 "st.relaxed.gpu.global.b128 [%0], t;\n}" :: "l"(p), "f"(x), "f"(y), "f"(z), "f"(w) : "memory");
}
__device__ __forceinline__ unsigned ld_acquire(const unsigned* p) {
    unsigned v;
    asm volatile("ld.acquire.gpu.global.u32 %0, [%1];" : "=r"(v) : "l"(p) : "memory");
    return v;
}
__device__ __forceinline__ void st_relaxed(void* p, uint32_t v) {
    asm volatile("st.relaxed.gpu.global.u32 [%0], %1;" :: "l"(p), "r"(v) : "memory");
}
__device__ __forceinline__ void red_f2(float* p, float a, float b) {
    asm volatile("red.relaxed.gpu.global.add.v2.f32 [%0], {%1,%2};" :: "l"(p), "f"(a), "f"(b) : "memory");
}
__device__ __forceinline__ void draw(int& ticket, unsigned* ctr, bool pred) {
    asm volatile("{\n.reg .pred p;\nsetp.ne.u32 p, %2, 0;\n@p atom.relaxed.gpu.global.inc.u32 %0, [%1], 0x7fffffff;\n}"
                 : "+r"(ticket) : "l"(ctr), "r"((uint32_t)pred) : "memory");
}
__device__ __forceinline__ void red_release(unsigned* p) {
    asm volatile("red.release.gpu.global.add.u32 [%0], 1;" :: "l"(p) : "memory");
}
__device__ __forceinline__ uint32_t ld_relaxed_u32(const void* p) {
    uint32_t v;
    asm volatile("ld.relaxed.gpu.global.u32 %0, [%1];" : "=r"(v) : "l"(p) : "memory");
    return v;
}
__device__ __forceinline__ float rcp_approx(float v) {
    float r;
    asm("rcp.approx.ftz.f32 %0, %1;" : "=f"(r) : "f"(v));
    return r;
}
__device__ __forceinline__ float sigmoid_approx(float v) {
    float e;
    asm("ex2.approx.ftz.f32 %0, %1;" : "=f"(e) : "f"(v * -1.4426950408889634f));
    return rcp_approx(1.0f + e);
}
__device__ __forceinline__ float sqrt_approx(float v) {
    float r;
    asm("sqrt.approx.ftz.f32 %0, %1;" : "=f"(r) : "f"(v));
    return r;
}
__device__ __forceinline__ void wait_count(const unsigned* p, unsigned target) {
#pragma unroll 1
    for (int it = 0; it < SPIN_MAX; it++) {
        if (ld_acquire(p) >= target) break;
        __nanosleep(400);
    }
}
__device__ __forceinline__ void wait_row(int bh, float n) {
#pragma unroll 1
    for (int it = 0; it < SPIN_MAX; it++) {
        const float c = ld_relaxed_f2(g_st.lsum[bh]).y;
        if (c >= n) break;
        if (c == 0.f) __nanosleep(600);
    }
}
__device__ __forceinline__ void wait_row_o(int bh, float n) {
    wait_row(bh, n);
    if (bh >= RED0) return;
#pragma unroll 1
    for (int it = 0; it < SPIN_MAX; it++) {
        if (__uint_as_float(ld_relaxed_u32(&g_st.oacc[oidx(bh, 0)].w)) == UPB) break;
        __nanosleep(300);
    }
}
__device__ __forceinline__ void spin_ns(int ns) {
    const long long t0 = clock64();
    while (clock64() - t0 < (long long)ns * 2) {}
}
__device__ __forceinline__ uint32_t pack_bf16(float lo, float hi) {
    uint32_t r;
    asm("cvt.rn.bf16x2.f32 %0, %1, %2;" : "=r"(r) : "f"(hi), "f"(lo));
    return r;
}
__device__ __forceinline__ float bf16r(float v) { return __uint_as_float(pack_bf16(0.f, v)); }
__device__ __forceinline__ uint32_t pack_neg(float lo, float hi) {
    const uint32_t w = pack_bf16(-lo, -hi);
    return w ? w : 0x80008000u;
}
__device__ __forceinline__ float lo_f(uint32_t v) { return __uint_as_float(v << 16); }
__device__ __forceinline__ float hi_f(uint32_t v) { return __uint_as_float(v & 0xffff0000u); }
__device__ __forceinline__ float warp_sum(float v) {
#pragma unroll
    for (int o = 16; o; o >>= 1) v += __shfl_xor_sync(0xffffffffu, v, o);
    return v;
}
__device__ __forceinline__ void layernorm20(float (&v)[20]) {
    float s = 0.f;
#pragma unroll
    for (int i = 0; i < 20; i++) s += v[i];
    const float mean = warp_sum(s) * (1.0f / DM);
    float q = 0.f;
#pragma unroll
    for (int i = 0; i < 20; i++) { const float d = v[i] - mean; q += d * d; }
    const float var = bf16r(warp_sum(q) * (1.0f / DM));
    const float m = bf16r(mean);
    const float rden = 1.0f / bf16r(sqrtf(bf16r(var + 1e-5f)));
#pragma unroll
    for (int i = 0; i < 20; i++) v[i] = bf16r(bf16r(v[i] - m) * rden);
}

__device__ __forceinline__ void moments(float m1, float m2, float& nmean, float& rden) {
    m1 *= 1.0f / DM;
    const float var = bf16r(fmaxf(fmaf(-m1, m1, m2 * (1.0f / DM)), 0.f));
    nmean = bf16r(m1);
    rden = rcp_approx(bf16r(sqrt_approx(bf16r(var + 1e-5f))));
}
__device__ __forceinline__ float sel4(int j, float a, float b, float c, float d) {
    float lo, hi, r;
    asm("{\n.reg .pred p;\nsetp.ne.s32 p, %3, 0;\nselp.f32 %0, %2, %1, p;\n}" : "=f"(lo) : "f"(a), "f"(b), "r"(j & 1));
    asm("{\n.reg .pred p;\nsetp.ne.s32 p, %3, 0;\nselp.f32 %0, %2, %1, p;\n}" : "=f"(hi) : "f"(c), "f"(d), "r"(j & 1));
    asm("{\n.reg .pred p;\nsetp.ne.s32 p, %3, 0;\nselp.f32 %0, %2, %1, p;\n}" : "=f"(r) : "f"(lo), "f"(hi), "r"(j & 2));
    return r;
}
template <typename T> __device__ __forceinline__ void pin(T*& p) { asm volatile("" : "+l"(p)); }
__device__ __forceinline__ void pin(uint32_t& v) { asm volatile("" : "+r"(v)); }
__device__ __forceinline__ void pin(float& v) { asm volatile("" : "+f"(v)); }
__device__ __forceinline__ uint32_t after(uint32_t n, float v) {
    asm volatile("{\n.reg .pred p;\nsetp.eq.u32 p, %1, 0x7fc1a5a5;\n@p add.u32 %0, %0, 32;\n}" : "+r"(n) : "r"(__float_as_uint(v)));
    return n;
}
__device__ __forceinline__ float2 lds64f(uint32_t addr) {
    float2 v;
    asm volatile("ld.shared.v2.f32 {%0,%1}, [%2];" : "=f"(v.x), "=f"(v.y) : "r"(addr) : "memory");
    return v;
}
__device__ __forceinline__ void sts32f(uint32_t addr, float v) { asm volatile("st.shared.f32 [%0], %1;" :: "r"(addr), "f"(v) : "memory"); }
template <int ID> __device__ __forceinline__ void fin_arrive() { asm volatile("bar.arrive %0, 288;" :: "n"(ID) : "memory"); }
template <int ID> __device__ __forceinline__ void fin_sync() { asm volatile("bar.sync %0, 288;" :: "n"(ID) : "memory"); }
template <int ID> __device__ __forceinline__ void fin_sync(uint32_t n) { asm volatile("bar.sync %0, %1;" :: "n"(ID), "r"(n) : "memory"); }
__device__ __forceinline__ float2 sum8(uint32_t addr) {
    float2 t[8];
#pragma unroll
    for (int w = 0; w < 8; w++) t[w] = lds64f(addr + w * 128);
    return make_float2(((t[0].x + t[1].x) + (t[2].x + t[3].x)) + ((t[4].x + t[5].x) + (t[6].x + t[7].x)),
                       ((t[0].y + t[1].y) + (t[2].y + t[3].y)) + ((t[4].y + t[5].y) + (t[6].y + t[7].y)));
}
__device__ __forceinline__ float4 sum4x4(uint32_t addr, int pitch) {
    float4 t[4];
#pragma unroll
    for (int w = 0; w < 4; w++)
        asm volatile("ld.shared.v4.f32 {%0,%1,%2,%3}, [%4];" : "=f"(t[w].x), "=f"(t[w].y), "=f"(t[w].z), "=f"(t[w].w) : "r"(addr + w * pitch) : "memory");
    return make_float4((t[0].x + t[1].x) + (t[2].x + t[3].x), (t[0].y + t[1].y) + (t[2].y + t[3].y),
                       (t[0].z + t[1].z) + (t[2].z + t[3].z), (t[0].w + t[1].w) + (t[2].w + t[3].w));
}
__device__ __forceinline__ void sts64f(uint32_t addr, float x, float y) {
    asm volatile("st.shared.v2.f32 [%0], {%1,%2};" :: "r"(addr), "f"(x), "f"(y) : "memory");
}
__device__ __forceinline__ void lds128_if(uint4& v, uint32_t addr, bool pred) {
    asm volatile("{\n.reg .pred p;\nsetp.ne.u32 p, %5, 0;\n@p ld.shared.v4.u32 {%0,%1,%2,%3}, [%4];\n}"
                 : "+r"(v.x), "+r"(v.y), "+r"(v.z), "+r"(v.w) : "r"(addr), "r"((uint32_t)pred) : "memory");
}
__device__ __forceinline__ void sts128f(uint32_t addr, float x, float y, float z, float w) {
    asm volatile("st.shared.v4.f32 [%0], {%1,%2,%3,%4};" :: "r"(addr), "f"(x), "f"(y), "f"(z), "f"(w) : "memory");
}
template <int NJ>
__device__ __forceinline__ void load_o(uint32_t (&ob)[3 * NJ][2], int bh, int J0, int j) {
    float4 v[NJ][4];
    float2 l;
#pragma unroll 1
    for (int it = 0; it < SPIN_MAX; it++) {
#pragma unroll
        for (int J = 0; J < NJ; J++) {
#pragma unroll
            for (int e = 0; e < 4; e++) v[J][e] = ld_relaxed_f4(&g_st.oacc[oidx(bh, j)] + oidx(0, (J0 + J) * 16 + e * 4));
        }
        l = ld_relaxed_f2(g_st.lsum[bh]);
        bool ok = l.y == UPB;
#pragma unroll
        for (int J = 0; J < NJ; J++) {
#pragma unroll
            for (int e = 0; e < 4; e++) ok &= v[J][e].w == UPB;
        }
        if (__all_sync(0xffffffffu, ok)) break;
    }
    const float rl = __fdividef(1.0f, l.x);
#pragma unroll
    for (int J = 0; J < NJ; J++) {
        ob[3 * J][0] = pack_bf16(v[J][0].x * rl, v[J][1].x * rl);     ob[3 * J][1] = pack_bf16(v[J][2].x * rl, v[J][3].x * rl);
        ob[3 * J + 1][0] = pack_bf16(v[J][0].y * rl, v[J][1].y * rl); ob[3 * J + 1][1] = pack_bf16(v[J][2].y * rl, v[J][3].y * rl);
        ob[3 * J + 2][0] = pack_bf16(v[J][0].z * rl, v[J][1].z * rl); ob[3 * J + 2][1] = pack_bf16(v[J][2].z * rl, v[J][3].z * rl);
    }
}
__device__ __forceinline__ int near_side(uint32_t sb) {
    uint32_t v;
    asm volatile("ld.volatile.shared.u32 %0, [%1];" : "=r"(v) : "r"(sb + SM_SIDE) : "memory");
    return v;
}
__device__ __forceinline__ void poll_row(uint4& a, uint4& b, uint2& c, const void* pa, const void* pb, const void* pc, uint32_t sa, uint32_t sc,
                                         bool arrive, bool nap) {
    asm volatile("{\n.reg .pred p, q, r, s;\n.reg .u32 m, n, it;\n"
                 "setp.ne.u32 r, %15, 0;\nsetp.ne.u32 s, %16, 0;\nmov.u32 it, 0;\n"
                 "POLL:\n"
                 "ld.relaxed.gpu.global.v4.u32 {%0,%1,%2,%3}, [%10];\n"
                 "ld.relaxed.gpu.global.v4.u32 {%4,%5,%6,%7}, [%11];\n"
                 "ld.relaxed.gpu.global.v2.u32 {%8,%9}, [%12];\n"
                 "add.u32 it, it, 1;\nsetp.ge.u32 q, it, %17;\n"
                 "st.shared.v4.u32 [%13], {%0,%1,%2,%3};\n"
                 "st.shared.v4.u32 [%13+512], {%4,%5,%6,%7};\n"
                 "st.shared.v2.u32 [%14], {%8,%9};\n"
                 "min.u32 m, %0, %1;\nmin.u32 m, m, %2;\nmin.u32 n, %3, %4;\nmin.u32 n, n, %5;\nmin.u32 m, m, %6;\nmin.u32 m, m, %7;\n"
                 "min.u32 n, n, m;\nmin.u32 m, %8, %9;\nmin.u32 m, m, n;\n"
                 "setp.ne.or.u32 p, m, 0, q;\n"
                 "vote.sync.all.pred p, p, 0xffffffff;\n"
                 "and.pred q, p, r;\n"
                 "@q bar.arrive 7, 288;\n"
                 "@p bra.uni DONE;\n"
                 "@s nanosleep.u32 500;\n"
                 "bra.uni POLL;\n"
                 "DONE:\n}"
                 : "=&r"(a.x), "=&r"(a.y), "=&r"(a.z), "=&r"(a.w), "=&r"(b.x), "=&r"(b.y), "=&r"(b.z), "=&r"(b.w), "=&r"(c.x), "=&r"(c.y)
                 : "l"(pa), "l"(pb), "l"(pc), "r"(sa), "r"(sc), "r"((uint32_t)arrive), "r"((uint32_t)nap), "n"(SPIN_MAX) : "memory");
}
__device__ __forceinline__ void aux_sync() { asm volatile("bar.sync 1, 256;" ::: "memory"); }

__global__ void __launch_bounds__(NTHREADS, 1)
fused_decode_kernel(const __grid_constant__ Params p) {
    extern __shared__ __align__(1024) unsigned char smem[];
    const uint32_t sb = s2u(smem);
    const int tid = threadIdx.x, warp = __shfl_sync(0xffffffffu, tid >> 5, 0), lane = tid & 31;
    const int cta = blockIdx.x;
    constexpr int grid = NCTAS;
    const int g = lane >> 2, j = lane & 3;

    TS(0);
    if (tid == 128) {
        mbar_init(sb + BAR_WQ, 1);
        asm volatile("fence.mbarrier_init.release.cluster;" ::: "memory");
        asm volatile("fence.proxy.async.shared::cta;" ::: "memory");
        if (cta < NQ_CTAS) {
            mbar_expect_tx(sb + BAR_WQ, 61440);
#pragma unroll 1
            for (int i = 0; i < 4; i++) tma_box(sb + SM_W + i * 15360, &p.wq, cta * 48, i * 160, sb + BAR_WQ);
        }
    } else if (tid == 160) {
        mbar_init(sb + BAR_WO, 1);
        sts32f(sb + SM_SIDE, 0.f);
        asm volatile("fence.mbarrier_init.release.cluster;" ::: "memory");
        asm volatile("fence.proxy.async.shared::cta;" ::: "memory");
    } else if (tid >= 192 && tid < 200 + 2 * NWORK * NPART) {
        mbar_init(sb + BAR_FW + (tid - 192) * 8, 1);
        asm volatile("fence.mbarrier_init.release.cluster;" ::: "memory");
        asm volatile("fence.proxy.async.shared::cta;" ::: "memory");
    }
    __syncthreads();
    if (warp >= NAUX + NWORK) {
        const int fw = warp - (NAUX + NWORK), fi = ffn_slice(cta);
        if (fw == 0) {
            if (cta < NQ_CTAS) {
#pragma unroll
                for (int i = lane; i < STATE_V4; i += 32)
                    if (cta * STATE_V4 + i < (int)(sizeof(State) / 16)) reinterpret_cast<uint4*>(&g_st)[cta * STATE_V4 + i] = make_uint4(0u, 0u, 0u, 0u);
                __syncwarp();
                if (lane == 0) red_release(g_cnt_z);
            }
            if (lane == 0) { TS2(2); wait_count(g_cnt_z, NQ_CTAS); TS2(29); }
            __syncwarp();
            asm volatile("bar.arrive 2, %0;" :: "n"((NWORK + 2) * 32) : "memory");
            fin_arrive<3>();
        } else {
            asm volatile("bar.sync 2, %0;" :: "n"((NWORK + 2) * 32) : "memory");
            if (lane == 0) {
                uint32_t* ctr = &g_st.hx.w[0][PROBE];
                uint32_t best[2] = {~0u, ~0u};
#pragma unroll 1
                for (int i = 0; i < NPROBE; i++) {
#pragma unroll
                    for (int c = 0; c < 2; c++) {
                        uint32_t t0 = clock(), t1 = t0, v;
                        asm volatile("atom.relaxed.gpu.global.inc.u32 %0, [%1], 0x7fffffff;" : "=r"(v) : "l"(ctr + c * 1024) : "memory");
                        asm volatile("{\n.reg .pred p;\nsetp.ne.u32 p, %1, 0xffffffff;\n@p mov.u32 %0, %%clock;\n}" : "+r"(t1) : "r"(v) : "memory");
                        best[c] = min(best[c], t1 - t0);
                    }
                    __nanosleep(1000);
                }
                sts32f(sb + SM_SIDE, __uint_as_float((best[1] < best[0]) ^ SIDE_XOR));
            }
            __syncwarp();
        }
        int job = cta;
        auto sum_rows = [&](int row_end) {
#pragma unroll 1
            for (; job < 8 * min(row_end, RED0); job += NCTAS) {
                const int row = job >> 3, grp = (job & 7) * 8 + (lane & 7);
                if (lane == 0) wait_row(row, UPB);
                __syncwarp();
                const float4* src = &g_ring[row % RING][lane >> 3][grp];
                float sx = 0.f, sy = 0.f, sz = 0.f;
#pragma unroll 1
                for (int i = 0; i < 2; i++, src += 64 * 64) {
                    float4 v[16];
#pragma unroll 1
                    for (int it = 0; it < SPIN_MAX; it++) {
                        bool ok = true;
#pragma unroll
                        for (int k = 0; k < 16; k++) v[k] = ld_relaxed_b128(src + k * 4 * 64);
#pragma unroll
                        for (int k = 0; k < 16; k++) ok &= v[k].w == (float)(row + 1);
                        if (__all_sync(0xffffffffu, ok)) break;
                    }
#pragma unroll
                    for (int k = 0; k < 16; k++) { sx += v[k].x; sy += v[k].y; sz += v[k].z; }
                }
#pragma unroll
                for (int o = 8; o < 32; o <<= 1) {
                    sx += __shfl_xor_sync(0xffffffffu, sx, o); sy += __shfl_xor_sync(0xffffffffu, sy, o); sz += __shfl_xor_sync(0xffffffffu, sz, o);
                }
                if (lane < 8) st_relaxed_b128(&g_st.oacc[oidx(row, grp)], sx, sy, sz, UPB);
            }
        };
        const int ho0 = lane / 20 * 256 + lane % 20 * 4, ho1 = (lane + 32) / 20 * 256 + (lane + 32) % 20 * 4, ho2 = 3 * 256 + 16 + 2 * lane;
        uint32_t wr[10] = {};
        float wsum = 0.f;
        if (is_g(cta) && fw == 0) {
#pragma unroll
            for (int i = 0; i < 10; i++) {
                const int w = 4 * lane + 128 * (i >> 2) + (i & 3) - (i >= 8 ? 2 * lane : 0);
                wr[i] = *reinterpret_cast<const uint32_t*>(p.wr + (w >> 4) * 32 + (w & 3) * 8 + ((w >> 1) & 6));
                wsum += lo_f(wr[i]) + hi_f(wr[i]);
            }
            wsum = warp_sum(wsum);
        }
        const int fb = lane >> 3, fg = lane & 7;
        if (fw == 0) {
#pragma unroll
            for (int i = lane; i < DM / 2; i += 32) sts32f(sb + SM_X + 4 * HPITCH + i * 4, __uint_as_float(0x3f803f80u));
        }
        float nmean = 0.f, rden = 0.f, sig = 0.f;
#pragma unroll 1
        for (int b = 0; b < NB; b++) {
            const bool ffn = b >= NB - 2;
            if (fw == 0) {
                sum_rows((b + 1) * NH);
                if (ffn) asm volatile("bar.arrive 8, 64;" ::: "memory");
            } else if (ffn) {
                asm volatile("bar.sync 8, 64;" ::: "memory");
                if (lane == 0 && b == NB - 1) {
                    uint32_t t0 = 0, now;
#pragma unroll 1
                    for (int it = 0; it < SPIN_MAX; it++) {
                        t0 = ld_relaxed_u32(g_st.fw_time);
                        if (t0) break;
                        __nanosleep(400);
                    }
                    asm volatile("fence.proxy.async.shared::cta;" ::: "memory");
#pragma unroll 1
                    for (int it = 0; it < SPIN_MAX; it++) {
                        asm volatile("mov.u32 %0, %%globaltimer_lo;" : "=r"(now));
                        if ((int)(now - t0) >= FW_AT_NS) break;
                    }
                    TS2(9);
                    uint32_t t = clock() + (is_f(cta) ? (fi & 1) * FW_STAG : FW_MID + (fi & 3) * (FW_GAP2 / 4));
#pragma unroll 1
                    for (int i = 0; i < 8; i++) {
                        const uint32_t bar = sb + BAR_FW + i * 8;
                        while ((int)(clock() - t) < 0) {}
                        if (is_f(cta)) {
                            mbar_expect_tx(bar, 10240);
                            tma_box(sb + SM_W + i * 10240, (i & 1) ? &p.wu : &p.wg, fi * 32, (i >> 1) * 160, bar);
                            t += FW_GAP;
                        } else if (is_g(cta)) {
                            mbar_expect_tx(bar, 6144);
                            asm volatile("cp.async.bulk.tensor.4d.shared::cluster.global.mbarrier::complete_tx::bytes [%0], [%1, {%3, %4, %4, %5}], [%2];"
                                         :: "r"(sb + SM_W + i * 6144), "l"(&p.wd), "r"(bar), "r"(fi * 16), "r"(0), "r"(i * 12) : "memory");
                            t += FW_GAP2;
                        }
                    }
                }
                __syncwarp();
                if (is_f(cta)) {
                    const uint32_t* src = &g_st.hx.w[near_side(sb)][min(fb, b) * 256 + 96];
                    float4 m;
#pragma unroll 1
                    for (int it = 0; it < SPIN_MAX; it++) {
                        m = ld_relaxed_f4(src);
                        if (__all_sync(0xffffffffu, m.y + m.w == 2 * (NCTAS - NE_CTAS))) break;
                        if (b < NB - 1) __nanosleep(500);
                    }
                    moments(m.x, m.z, m.x, m.z);
                    sts64f(sb + SM_RED + 5120 + fb * 8, m.x, m.z);
                }
            }
            if (fw == 0 && cta >= NE_CTAS) {
                const int lc = cta - NE_CTAS, col = lc * 32 + 2 * (lane & 15);
                const uint32_t xv = *reinterpret_cast<const uint32_t*>(p.x + b * DM + col);
                uint32_t* dst = &(ffn ? g_st.hx.w : g_st.lx.w + 2)[lane >> 4][(b & 1) * 128 + lc / 5 * 256 + lc % 5 * 16 + (col & 6) * 2 + ((col >> 3) & 3)];
                uint32_t part = sb + SM_RED + (lane & 15) * 8;
                if (lane == 0) wait_row(b * NH + 28, 1);
                __syncwarp();
                float4 early;
#pragma unroll 1
                for (int it = 0; it < SPIN_MAX; it++) {
                    early = ld_relaxed_f4(&g_st.attn[b][col]);
                    if (__all_sync(0xffffffffu, early.y == NE_CTAS / 4 && early.w == NE_CTAS / 4)) break;
                }
                if (early.x != 1.2345f && lane == 0) TS2(6);
                CK(1, __float_as_uint(early.x));
                float x0 = lo_f(xv), x1 = hi_f(xv);
                pin(dst); pin(part); pin(x0); pin(x1);
                fin_sync<4>();
                CK(2, lds32(sb + SM_RED));
                const float2 late = sum8(part);
                const uint32_t hv = pack_neg(x0 + bf16r(early.x + late.x), x1 + bf16r(early.z + late.y));
                st_relaxed(dst, hv);
                if (HREP2 && ffn) st_relaxed(dst + 2048, hv);
                CK(3, 0);
                float m = lane < 16 ? lo_f(hv) + hi_f(hv) : fmaf(lo_f(hv), lo_f(hv), hi_f(hv) * hi_f(hv));
#pragma unroll
                for (int o = 1; o < 16; o <<= 1) m += __shfl_xor_sync(0xffffffffu, m, o);
                if ((lane & 14) == 0) red_f2(reinterpret_cast<float*>(&g_st.hx.w[lane & 1][b * 256 + 96 + (lane >> 4) * 2]), m, 1.f);
                fin_arrive<5>();
            }
            if (fw == 0 && (is_g(cta) || is_f(cta))) {
                const uint32_t* src = &(ffn ? g_st.hx.w : g_st.lx.w + 2)[near_side(sb) ^ (HREP2 && ffn && (HREP2 == 1 ? (fi & 1) : is_g(cta)) ? 3 : 0)][(b & 1) * 128];
                const uint32_t hrow = sb + SM_X + b * HPITCH;
                if (lane == 0) wait_row(b * NH + NH - 1, UPB);
                __syncwarp();
                uint4 h0, h1;
                uint2 h2;
                poll_row(h0, h1, h2, src + ho0, src + ho1, src + ho2, hrow + lane * 16, hrow + 1024 + lane * 8, ffn, b < NB - 1);
                CK(4, h0.x);
                if (!LSTAT || is_g(cta)) {
                const uint32_t hw[10] = {h0.x, h0.y, h0.z, h0.w, h1.x, h1.y, h1.z, h1.w, h2.x, h2.y};
                float s1[2] = {}, s2[2] = {};
#pragma unroll
                for (int i = 0; i < 10; i++) {
                    const float v0 = lo_f(hw[i]), v1 = hi_f(hw[i]);
                    s1[i & 1] += v0 + v1;
                    s2[i & 1] = fmaf(v0, v0, fmaf(v1, v1, s2[i & 1]));
                }
                float m1 = s1[0] + s1[1], m2 = s2[0] + s2[1];
#pragma unroll
                for (int o = 16; o; o >>= 1) { m1 += __shfl_xor_sync(0xffffffffu, m1, o); m2 += __shfl_xor_sync(0xffffffffu, m2, o); }
                moments(m1, m2, m1, m2);
                {
                    float rr = 0.f;
#pragma unroll
                    for (int i = 0; i < 10; i++) rr = fmaf(lo_f(hw[i]), lo_f(wr[i]), fmaf(hi_f(hw[i]), hi_f(wr[i]), rr));
                    const float sg = bf16r(sigmoid_approx(bf16r((m1 * wsum - warp_sum(rr)) * m2)));
                    if (fb == b) { nmean = m1; rden = m2; sig = sg; }
                    __syncwarp();
                    if (ffn) {
                        const int gi = fi, yj = 2 * (fb & 1) + (fb >> 1);
                        uint32_t ypart = sb + SM_RED2 + yj * 128 + ((fg + 2 * yj) & 7) * 16;
                        __nv_bfloat16* out = p.out + fb * DM + gi * 16 + fg;
                        const float2 hw2 = lds64f(sb + SM_X + fb * HPITCH + ((gi >> 1) * 16 + (fg & 6) * 2 + (gi & 1) * 2) * 4);
                        const uint32_t w0 = __float_as_uint(hw2.x), w1 = __float_as_uint(hw2.y);
                        float nh0 = (fg & 1) ? hi_f(w0) : lo_f(w0), nh1 = (fg & 1) ? hi_f(w1) : lo_f(w1);
                        float ln0 = bf16r(bf16r(nmean - nh0) * rden), ln1 = bf16r(bf16r(nmean - nh1) * rden);
                        pin(ypart); pin(out);
                        fin_sync<6>(after(after(after(288, sig), ln0), ln1));
                        CK(10, lds32(ypart));
                        const float4 ya = sum4x4(ypart, 512), yb = sum4x4(ypart + 2048, 512);
                        const float4 y = make_float4(ya.x + yb.x, ya.y + yb.y, ya.z + yb.z, ya.w + yb.w);
                        const float y0 = -(((fb & 1) ? y.y : y.x) + __shfl_xor_sync(0xffffffffu, (fb & 1) ? y.x : y.y, 8));
                        const float y1 = -(((fb & 1) ? y.w : y.z) + __shfl_xor_sync(0xffffffffu, (fb & 1) ? y.z : y.w, 8));
                        const uint32_t ov = pack_bf16(bf16r(ln0 + bf16r(bf16r(y0) * sig)) - nh0, bf16r(ln1 + bf16r(bf16r(y1) * sig)) - nh1);
                        if (b == NB - 1) {
                            asm volatile("st.global.u16 [%0], %1;" :: "l"(out), "h"((unsigned short)(ov & 0xffffu)) : "memory");
                            asm volatile("st.global.u16 [%0], %1;" :: "l"(out + 8), "h"((unsigned short)(ov >> 16)) : "memory");
                        }
                        CK(11, 0);
                        if (lane == 0) TS2(13);
                    }
                }
                }
            }
            if (is_f(cta) && ffn) {
                const int ks = (2 * fi + fw) % 12;
                uint32_t* dst = &g_st.ax[ks >> 2].w[(~b & 1) * 2][((fi / 6) * 32 + ((ks & 1) * 4 + fb) * 4 + (fg & 3)) * 4 + (ks & 2) + (fg >> 2)];
                uint32_t part = sb + SM_RED + fw * 2560 + fb * 128 + ((fg + (fb & 2)) & 7) * 16;
                uint32_t psum = sb + SM_RED + fw * 2560 + 4 * 128 + ((fg + 4) & 7) * 16;
                pin(dst); pin(part); pin(psum);
                asm volatile("bar.sync 4, 320;" ::: "memory");
                CK(6, lds32(part));
                const float4 d = sum4x4(part, 640), cs = sum4x4(psum, 640);
                const float2 mo = lds64f(sb + SM_RED + 5120 + fb * 8);
                nmean = mo.x; rden = mo.y;
                const float g0 = bf16r(fmaf(nmean, cs.x, -d.x) * rden), g1 = bf16r(fmaf(nmean, cs.y, -d.y) * rden);
                const float u0 = bf16r(fmaf(nmean, cs.z, -d.z) * rden), u1 = bf16r(fmaf(nmean, cs.w, -d.w) * rden);
                const uint32_t av = pack_neg(bf16r(g0 * sigmoid_approx(g0)) * u0, bf16r(g1 * sigmoid_approx(g1)) * u1);
                st_relaxed(dst, av);
                st_relaxed(dst + 1024, av);
                CK(7, 0);
            }
        }
        if (cta == 0 && tid == (NAUX + NWORK) * 32) { g_work[0] = 0; g_work[32] = 0; g_cnt_z[0] = 0; }
        return;
    }
    if (warp >= NAUX) {
        const int wk = warp - NAUX;
        const uint32_t bar = sb + BAR_KV + wk * (NPART * 8);
        const uint32_t buf = sb + SM_KV + wk * TILE_BYTES;
        uint64_t pol;
        asm volatile("createpolicy.fractional.L2::evict_first.b64 %0, 1.0;" : "=l"(pol));
        const int nstatic = NWORK * grid;
        constexpr int POOL0 = NUNITS - NPOOL;
        int uk = wk * grid + cta;
        if (K0_DELAY_NS) spin_ns(K0_DELAY_NS);
        __syncwarp();
        request_tile(buf, &p.k, uk, bar, pol);
        if (lane == 0) {
            if (wk == 0) {
                const uint32_t wbar = sb + BAR_WO;
                spin_ns(WO_AT_NS - K0_DELAY_NS);
                mbar_expect_tx(wbar, cta < NE_CTAS ? 61440 : 49152);
#pragma unroll 1
                for (int i = 0; i < (cta < NE_CTAS ? 5 : 4); i++) {
                    if (cta < NE_CTAS) tma_box(sb + SM_A + i * 12288, &p.wo, (cta & 3) * 160 + i * 32, (cta >> 2) * DH, wbar);
                    else tma_box(sb + SM_A + i * 12288, &p.wo, (cta - NE_CTAS) * 32, (28 + i) * DH, wbar);
                }
            }
        }
        __syncwarp();
        uint32_t koff[3], voff[3];
        {
            const int r = lane & 7, hf = (lane >> 3) & 1;
            const int kkey = hf ? 8 + (r ^ 1) : r;
            const int vh = lane >> 4;
            const int vkey = ((r & 1) ? 8 : 0) + (vh ? (r ^ 1) : r);
#pragma unroll
            for (int b = 0; b < 3; b++) {
                const int rk = 3 * kkey + b, rv = 3 * vkey + b;
                koff[b] = buf + rk * 128 + (((lane >> 4) ^ (rk & 7)) << 4);
                voff[b] = buf + rv * 128 + ((hf ^ (rv & 7)) << 4);
            }
        }
        uint32_t phase = 0, kbar = bar;
        uint4 qf[6];
        auto load_q = [&](int u) {
            const uint32_t* q = &g_early[u / UPB].q[j * 4];
#pragma unroll
            for (int i = 0; i < 6; i++) qf[i] = ld_relaxed_v4(q + i * 16);
        };
        load_q(uk);
        int uq[LAG];
        uint32_t sq[LAG];
#pragma unroll
        for (int i = 0; i < LAG; i++) { uq[i] = -1; sq[i] = 0; }
        uint4 mv = make_uint4(0u, 0u, 0u, 0u);
        float freed = UPB;
        while (true) {
            const int uv = uq[0];
            uint32_t sv = sq[0];
#pragma unroll
            for (int i = 0; i + 1 < LAG; i++) { uq[i] = uq[i + 1]; sq[i] = sq[i + 1]; }
            uq[LAG - 1] = uk;
            if (uk < NUNITS) {
                PH(7);
#pragma unroll 1
                for (int it = 0; it < SPIN_MAX; it++) {
                    uint32_t lo = 0xffffffffu;
#pragma unroll
                    for (int i = 0; i < 6; i++) lo = min(min(lo, min(qf[i].x, qf[i].y)), min(qf[i].z, qf[i].w));
                    if (__all_sync(0xffffffffu, lo != 0)) break;
                    __nanosleep(250);
                    load_q(uk);
                }
#pragma unroll
                for (int t = 0; t < NPART; t++) mbar_wait(kbar + t * 8, phase);
                phase ^= 1;
                PH(0); ARR();
                TSI(0, 16); TSI(1, 18);
                float acc[2][4][4] = {};
#pragma unroll
                for (int ks = 0; ks < 12; ks++) {
                    const uint4 qq = qf[ks >> 1];
                    const uint32_t b0 = (ks & 1) ? qq.z : qq.x, b1 = (ks & 1) ? qq.w : qq.y;
#pragma unroll
                    for (int mt = 0; mt < 4; mt++) {
                        uint32_t a[4];
                        ldsm4(a, (koff[ks >> 2] ^ ((ks & 3) << 5)) + mt * 6144);
                        mma16816(acc[ks & 1][mt], a, b0, b1);
                    }
                }
                PH(1);
                TSI(0, 17); TSI(1, 19);
                if (uv < NUNITS && kbar == bar) request_tile(buf, uv >= 0 ? &p.v : &p.k, uv >= 0 ? uv : uk + (wk < NSPARE ? 2 : 1) * nstatic, bar, pol);
                const float sa = sel4(j, acc[0][0][0], acc[0][1][0], acc[0][2][0], acc[0][3][0]) + sel4(j, acc[1][0][0], acc[1][1][0], acc[1][2][0], acc[1][3][0]);
                const float sc = sel4(j, acc[0][0][2], acc[0][1][2], acc[0][2][2], acc[0][3][2]) + sel4(j, acc[1][0][2], acc[1][1][2], acc[1][2][2], acc[1][3][2]);
                const uint32_t raw = pack_bf16(sa, sc);
                const float scale = -0.07216878364870322f;
                const uint32_t sk = pack_bf16(lo_f(raw) * scale, hi_f(raw) * scale);
                sq[LAG - 1] = sk;
                if (uk >= POOL0) st_relaxed(&g_st.score[uk - POOL0][lane], sk ? sk : 0x80008000u);
                int a = (int)(sk << 16), b = (int)(sk & 0xffff0000u);
                a ^= (a >> 31) & 0x7fff0000; b ^= (b >> 31) & 0x7fff0000;
                const int mx = __reduce_max_sync(0xffffffffu, max(a, b));
                if (lane == 0) st_relaxed(&g_early[uk / UPB].umax[uk % UPB], (uint32_t)mx | 1u);
            }
            if (uv < 0) {
                if (wk < NSPARE) {
                    const int d = uk < nstatic ? SM_W - SM_KV : SM_KV - SM_W;
#pragma unroll
                    for (int b = 0; b < 3; b++) koff[b] += d;
                    kbar = uk < nstatic ? bar + NWORK * NPART * 8 : bar;
                    phase = uk >= nstatic;
                }
                uk += nstatic;
                load_q(uk);
                continue;
            }
            if (uv >= NUNITS) break;
            const int bh = uv / UPB;
#pragma unroll 1
            for (int it = 0; it < SPIN_MAX; it++) {
                if (__all_sync(0xffffffffu, (mv.x & mv.y & mv.z & mv.w & 1u) && (uv < POOL0 || sv != 0) && freed == UPB)) break;
                mv = ld_relaxed_v4(&g_early[bh].umax[lane * 4]);
                if (bh >= RING && bh < RED0) freed = __uint_as_float(ld_relaxed_u32(&g_st.oacc[oidx(bh - RING, (lane & 7) * 8)].w));
                if (uv >= POOL0) sv = ld_relaxed_u32(&g_st.score[uv - POOL0][lane]);
            }
            PH(2);
            int un = NUNITS, vn = 0;
            draw(un, g_work, uk < NUNITS && lane == 0);
            uint32_t tdraw;
            asm volatile("mov.u32 %0, %%globaltimer_lo;" : "=r"(tdraw));
            draw(vn, g_work + 32, uq[0] >= POOL0 && lane == 0);
            int mx = __reduce_max_sync(0xffffffffu, max(max((int)mv.x, (int)mv.y), max((int)mv.z, (int)mv.w))) & 0xffff0000;
            mx ^= (mx >> 31) & 0x7fff0000;
            const float m = __int_as_float(mx);
            const float l2e = 1.4426950408889634f;
            const uint32_t pp = pack_bf16(exp2f((lo_f(sv) - m) * l2e), exp2f((hi_f(sv) - m) * l2e));
            uint32_t pb[8];
#pragma unroll
            for (int t = 0; t < 4; t++) {
                pb[2 * t] = __shfl_sync(0xffffffffu, pp, 8 * j + t);
                pb[2 * t + 1] = __shfl_sync(0xffffffffu, pp, 8 * j + 4 + t);
            }
            float lacc[4] = {};
            const uint32_t ones[4] = {0x3f803f80u, 0x3f803f80u, 0x3f803f80u, 0x3f803f80u};
#pragma unroll
            for (int t = 0; t < 4; t++) mma16816(lacc, ones, pb[2 * t], pb[2 * t + 1]);
            if (uv < nstatic) {
                asm volatile("bar.sync 2, %0;" :: "n"((NWORK + 2) * 32) : "memory");
                TSW(3);
            }
            const int grp = 16 * j + 4 * (g & 1) + (g >> 1);
            uint32_t mode = (bh >= RED0) + (bh >= NBH - 4);
            float tag = mode ? 1.f : (float)(bh + 1), tag2 = tag;
            void* dst = mode == 0 ? (void*)&g_ring[bh % RING][uv % UPB][grp] :
                        mode == 1 ? (void*)&g_st.oacc[oidx(bh, grp)] : (void*)&g_st.ox[uv % OREP].w[0][oidx(bh & 3, grp) * 4];
            if (mode == 2 && lane < 2) red_f2(reinterpret_cast<float*>(&g_st.lx.w[lane][(bh & 3) * 256]), lacc[0], 1.f);
            un = __shfl_sync(0xffffffffu, un, 0) + (LAG + 1) * nstatic;
            vn = __shfl_sync(0xffffffffu, vn, 0);
            if (uq[0] >= POOL0) uq[0] = POOL0 + vn;
            if (vn == FW_TICKET && lane == 0) st_relaxed(g_st.fw_time, tdraw | 1u);
            pin(dst); pin(mode); pin(tag); pin(tag2); pin(voff[0]); pin(voff[1]); pin(voff[2]);
            PH(3);
            float acc[12][4] = {};
#pragma unroll
            for (int t = 0; t < 4; t++) {
                if (t % (4 / NPART) == 0) mbar_wait(bar + t / (4 / NPART) * 8, phase);
                if (t == 4 - 4 / NPART) { PH(4); ARR(); CK(12, lds32(buf)); }
#pragma unroll
                for (int mt = 0; mt < 12; mt++) {
                    uint32_t a[4];
                    ldsm4t(a, (voff[mt >> 2] ^ ((mt & 3) << 5)) + t * 6144);
                    mma16816(acc[mt], a, pb[2 * t], pb[2 * t + 1]);
                }
            }
            phase ^= 1;
            PH(5);
            if (lane == 0) PROG(un);
            if (un < NUNITS || uq[0] < NUNITS) request_tile(buf, un < NUNITS ? &p.k : &p.v, un < NUNITS ? un : uq[0], bar, pol);
            float o[6];
#pragma unroll
            for (int e = 0; e < 6; e++) {
                const int q = e % 3, c = (e / 3) * 2;
                o[e] = sel4(j, acc[q][c], acc[3 + q][c], acc[6 + q][c], acc[9 + q][c]);
            }
            put_groups(dst, mode, o, tag, tag2);
            CK(13, 0);
            if (un < NUNITS) load_q(un);
            if (lane == 0) red_f2(&g_st.lsum[bh][0].x, lacc[0], 1.f);
            PH(6);
            if (uq[0] >= NUNITS && un >= NUNITS) break;
            uk = un;
            if (uq[0] < NUNITS) {
                const int nb = uq[0] / UPB;
                mv = ld_relaxed_v4(&g_early[nb].umax[lane * 4]);
                freed = nb >= RING && nb < RED0 ? __uint_as_float(ld_relaxed_u32(&g_st.oacc[oidx(nb - RING, (lane & 7) * 8)].w)) : UPB;
                if (uq[0] >= POOL0) sq[0] = ld_relaxed_u32(&g_st.score[uq[0] - POOL0][lane]);
            }
        }
        TSW(4 + wk);
        return;
    }

    __nv_bfloat16* xs = reinterpret_cast<__nv_bfloat16*>(smem + SM_X);
    float* red = reinterpret_cast<float*>(smem + SM_RED);
    const int frow = (lane & 7) + ((lane >> 4) << 3), fcol = (lane >> 3) & 1;
    const uint32_t f32b = sb + (frow * 2 + (fcol ^ ((frow >> 2) & 1))) * 16;
    const uint32_t f64b = sb + (frow * 4 + (fcol ^ ((frow >> 1) & 3))) * 16;
    if (cta < NQ_CTAS) {
        uint2 xr[5];
        if (warp < NB) {
#pragma unroll
            for (int i = 0; i < 5; i++) xr[i] = *reinterpret_cast<const uint2*>(p.x + warp * DM + i * 128 + lane * 4);
        }
        TS(26);
        if (warp < NB) {
            float v[20];
#pragma unroll
            for (int i = 0; i < 5; i++) {
                v[4 * i] = lo_f(xr[i].x); v[4 * i + 1] = hi_f(xr[i].x); v[4 * i + 2] = lo_f(xr[i].y); v[4 * i + 3] = hi_f(xr[i].y);
            }
            layernorm20(v);
#pragma unroll
            for (int i = 0; i < 5; i++)
                *reinterpret_cast<uint2*>(xs + warp * XPITCH + i * 128 + lane * 4) =
                    make_uint2(pack_bf16(v[4 * i], v[4 * i + 1]), pack_bf16(v[4 * i + 2], v[4 * i + 3]));
        }
        TS(27);
        aux_sync();
        mbar_wait(sb + BAR_WQ, 0);
        TS(1);
        const uint32_t xfrag = sb + SM_X + ((g & 3) * XPITCH + 2 * j) * 2;
        float acc[3][4] = {};
#pragma unroll
        for (int s = 0; s < 5; s++) {
            const int ks = warp * 5 + s;
            const uint32_t b0 = lds32(xfrag + ks * 32), b1 = lds32(xfrag + ks * 32 + 16);
            const int row = ks * 16 + frow;
#pragma unroll
            for (int mt = 0; mt < 3; mt++) {
                uint32_t a[4];
                ldsm4t(a, sb + SM_W + (row * 6 + 2 * mt + fcol) * 16);
                mma16816(acc[mt], a, b0, b1);
            }
        }
        if (j < 2) {
#pragma unroll
            for (int mt = 0; mt < 3; mt++) {
                *reinterpret_cast<float2*>(red + (warp * 48 + mt * 16 + g) * 4 + 2 * j) = make_float2(acc[mt][0], acc[mt][1]);
                *reinterpret_cast<float2*>(red + (warp * 48 + mt * 16 + 8 + g) * 4 + 2 * j) = make_float2(acc[mt][2], acc[mt][3]);
            }
        }
        aux_sync();
        if (tid < 96) {
            const int b = tid & 3, cp = tid >> 2;
            float s0 = 0.f, s1 = 0.f;
#pragma unroll
            for (int w = 0; w < 8; w++) { s0 += red[(w * 48 + 2 * cp) * 4 + b]; s1 += red[(w * 48 + 2 * cp + 1) * 4 + b]; }
            const int h = cta >> 2, d = (cta & 3) * 48 + 2 * cp;
            const int ch = d >> 3, jj = (d & 7) >> 1;
            st_relaxed(&g_early[b * NH + h].q[(ch >> 2) * 16 + jj * 4 + (ch & 3)], pack_neg(s0, s1));
        }
        TS(28);
    }
    if (warp >= 4 && warp < 4 + NSPARE) {
        uint64_t pol;
        asm volatile("createpolicy.fractional.L2::evict_first.b64 %0, 1.0;" : "=l"(pol));
        spin_ns(cta < NQ_CTAS ? SPARE_NS : WO_AT_NS + SPARE_NS);
        asm volatile("fence.proxy.async.shared::cta;" ::: "memory");
        __syncwarp();
        request_tile(sb + SM_W + (warp - 4) * TILE_BYTES, &p.k, (NWORK + warp - 4) * grid + cta, sb + BAR_KV + (NWORK + warp - 4) * (NPART * 8), pol);
    }
    fin_sync<3>();
    mbar_wait(sb + BAR_WO, 0);
    TS(7);
    uint32_t part = sb + SM_RED + (warp * 32 + 8 * j + g) * 4;

#pragma unroll 1
    for (int b = 0; b < NB; b++) {
        if (cta >= NE_CTAS) {
            uint32_t a[6][2][4];
#pragma unroll
            for (int s = 0; s < 6; s++) {
#pragma unroll
                for (int mt = 0; mt < 2; mt++) ldsm4t(a[s][mt], (f64b ^ (mt * 32)) + SM_A + (warp * 6 + s) * 1024);
            }
            const int bh = b * NH + 28 + (warp >> 1);
            const int side = near_side(sb) ^ 1;
            const void* osrc[OREP];
#pragma unroll
            for (int c = 0; c < OREP; c++)
                osrc[c] = b == NB - 1 ? (const void*)&g_st.ox[c].w[side][oidx(bh & 3, (warp & 1) * 32 + lane) * 4] : &g_st.oacc[oidx(bh, (warp & 1) * 32 + lane)];
            const void* lsrc = b == NB - 1 ? (const void*)&g_st.lx.w[side][(bh & 3) * 256] : g_st.lsum[bh];
            if (lane == 0) wait_row_o(bh, 1);
            __syncwarp();
            float2 lv;
#pragma unroll 1
            for (int it = 0; it < SPIN_MAX; it++) {
                lv = ld_relaxed_f2(lsrc);
                if (lv.y == UPB) break;
            }
            __syncwarp();
            float rl = rcp_approx(lv.x) * (b == NB - 1 ? 1.f : 1.f / OREP), full = b == NB - 1 ? UPB : UPB * OREP;
            float4 ov;
            pin(part); pin(rl); pin(full);
#pragma unroll 1
            for (int it = 0; it < SPIN_MAX; it++) {
                float4 oc[OREP];
#pragma unroll
                for (int c = 0; c < OREP; c++) oc[c] = ld_relaxed_f4(osrc[c]);
                ov = oc[0];
#pragma unroll
                for (int c = 1; c < OREP; c++) { ov.x += oc[c].x; ov.y += oc[c].y; ov.z += oc[c].z; ov.w += oc[c].w; }
                if (__all_sync(0xffffffffu, ov.w == full)) break;
            }
            CK(0, __float_as_uint(ov.x));
            if (ov.x != 1.2345f && warp == 7) TSW(14);
            const float px = __shfl_xor_sync(0xffffffffu, ov.x, 4), py = __shfl_xor_sync(0xffffffffu, ov.y, 4),
                        pz = __shfl_xor_sync(0xffffffffu, ov.z, 4);
            const uint32_t w[3] = {pack_bf16(ov.x * rl, px * rl), pack_bf16(ov.y * rl, py * rl), pack_bf16(ov.z * rl, pz * rl)};
            float acc[2][2][4] = {};
#pragma unroll
            for (int s = 0; s < 6; s++) {
                const uint32_t b0 = __shfl_sync(0xffffffffu, w[s % 3], (s / 3) * 16 + j);
                const uint32_t b1 = __shfl_sync(0xffffffffu, w[s % 3], (s / 3) * 16 + 8 + j);
#pragma unroll
                for (int mt = 0; mt < 2; mt++) mma16816(acc[mt][s & 1], a[s][mt], b0, b1);
            }
            sts32f(part, sel4(j, acc[0][0][0] + acc[0][1][0], acc[0][0][2] + acc[0][1][2], acc[1][0][0] + acc[1][1][0], acc[1][0][2] + acc[1][1][2]));
            CK(1, 0);
            fin_arrive<4>();
            fin_sync<5>();
            if (cta < NE_CTAS + 4 && tid < 56) reinterpret_cast<uint4*>(&g_early[b * NH + 28 + cta - NE_CTAS])[tid] = make_uint4(0u, 0u, 0u, 0u);
        } else {
            const int bh = b * NH + (cta >> 2);
            if (tid == 0) wait_row_o(bh, UPB);
            aux_sync();
            if (warp < 5) {
                uint32_t ob[12][2];
                load_o<4>(ob, bh, 0, j);
                float acc[2][2][4] = {};
#pragma unroll
                for (int ks = 0; ks < 12; ks++) {
#pragma unroll
                    for (int mt = 0; mt < 2; mt++) {
                        uint32_t a[4];
                        ldsm4t(a, (f64b ^ (mt * 32)) + SM_A + warp * 12288 + ks * 1024);
                        mma16816(acc[mt][ks & 1], a, ob[ks][0], ob[ks][1]);
                    }
                }
                red_f2(&g_st.attn[b][(cta & 3) * 160 + warp * 32 + 8 * j + g].x,
                       sel4(j, acc[0][0][0] + acc[0][1][0], acc[0][0][2] + acc[0][1][2], acc[1][0][0] + acc[1][1][0], acc[1][0][2] + acc[1][1][2]), 1.f);
                TS(8);
            } else if (warp > 5 && (cta & 3) == 0 && tid - 192 < 56) {
                reinterpret_cast<uint4*>(&g_early[bh])[tid - 192] = make_uint4(0u, 0u, 0u, 0u);
            }
        }
        if (b < NB - 2) continue;

        if (is_f(cta)) {
            uint32_t ga[10][2][4];
            uint4 hv[5] = {};
            const uint32_t hfrag = sb + SM_X + min(g, 4) * HPITCH + ((warp >> 1) * 80 + 4 * j) * 4;
#pragma unroll
            for (int s = 0; s < 5; s++) lds128_if(hv[s], hfrag + s * 64, b == NB - 1);
            if (b == NB - 1) mbar_wait(sb + BAR_FW + warp * 8, 0);
            if (warp == 7) TSW(10);
            CK(12, lds32(sb + SM_W));
#pragma unroll
            for (int s = 0; s < 10; s++) {
#pragma unroll
                for (int mt = 0; mt < 2; mt++) ldsm4t(ga[s][mt], (f64b ^ (mt * 32)) + SM_W + (warp * 10 + s) * 1024);
            }
            const uint32_t gpart = sb + SM_RED + (warp >> 1) * 640 + j * 256 + ((g + 2 * j) & 7) * 16 + (warp & 1) * 8;
            fin_sync<7>();
#pragma unroll
            for (int s = 0; s < 5; s++) lds128_if(hv[s], hfrag + s * 64, g == b);
            CK(4, hv[0].x);
            float acc[2][2][4] = {};
#pragma unroll
            for (int s = 0; s < 10; s++) {
#pragma unroll
                for (int mt = 0; mt < 2; mt++)
                    mma16816(acc[mt][s & 1], ga[s][mt], (s & 1) ? hv[s >> 1].z : hv[s >> 1].x, (s & 1) ? hv[s >> 1].w : hv[s >> 1].y);
            }
#pragma unroll
            for (int mt = 0; mt < 2; mt++) {
                if (j < 3) sts64f(gpart + mt * 2560, acc[mt][0][0] + acc[mt][1][0], acc[mt][0][2] + acc[mt][1][2]);
                if (j < 2) sts64f(gpart + mt * 2560 + 128, acc[mt][0][1] + acc[mt][1][1], acc[mt][0][3] + acc[mt][1][3]);
            }
            CK(5, 0);
            asm volatile("bar.arrive 4, 320;" ::: "memory");
        } else if (is_g(cta)) {
            uint32_t wb[12][4];
            if (b == NB - 1) mbar_wait(sb + BAR_FW + warp * 8, 0);
            if (warp == 7) TSW(11);
            CK(13, lds32(sb + SM_W));
#pragma unroll
            for (int s = 0; s < 12; s++) ldsm4t(wb[s], f32b + SM_W + (warp * 12 + s) * 512);
            const uint32_t* asrc = &g_st.ax[0].w[(~b & 1) * 2 + near_side(sb)][(warp * 32 + lane) * 4];
            uint32_t ypart = sb + SM_RED2 + warp * 512 + j * 128 + ((g + 2 * j) & 7) * 16;
            pin(ypart);
            fin_sync<7>();
            uint4 va[3];
#pragma unroll 1
            for (int it = 0; it < SPIN_MAX; it++) {
                uint32_t lo = 0xffffffffu;
#pragma unroll
                for (int i = 0; i < 3; i++) va[i] = ld_relaxed_v4(asrc + i * 4096);
#pragma unroll
                for (int i = 0; i < 3; i++) lo = min(min(lo, min(va[i].x, va[i].y)), min(va[i].z, va[i].w));
                if (__all_sync(0xffffffffu, lo != 0)) break;
            }
            CK(8, va[0].x);
            if (va[0].x != 0x12345 && warp == 7) TSW(15);
            float acc[4][4] = {};
#pragma unroll
            for (int s = 0; s < 12; s++) {
                const uint4 v = va[s >> 2];
                mma16816(acc[s & 3], wb[s], (s & 2) ? v.z : v.x, (s & 2) ? v.w : v.y);
            }
            float y[4];
#pragma unroll
            for (int e = 0; e < 4; e++) y[e] = j < 2 ? acc[0][e] + acc[2][e] : acc[1][e] + acc[3][e];
            sts128f(ypart, y[0], y[1], y[2], y[3]);
            CK(9, 0);
            fin_arrive<6>();
        }
    }
}

typedef CUresult (*EncodeFn)(CUtensorMap*, CUtensorMapDataType, cuuint32_t, void*, const cuuint64_t*, const cuuint64_t*,
                             const cuuint32_t*, const cuuint32_t*, CUtensorMapInterleave, CUtensorMapSwizzle,
                             CUtensorMapL2promotion, CUtensorMapFloatOOBfill);

CUtensorMap make_map(EncodeFn enc, void* ptr, uint64_t cols, uint64_t rows, uint32_t bcols, uint32_t brows,
                     CUtensorMapSwizzle sw, CUtensorMapL2promotion promo) {
    CUtensorMap m;
    const cuuint64_t dims[2] = {cols, rows};
    const cuuint64_t strides[1] = {cols * 2};
    const cuuint32_t box[2] = {bcols, brows};
    const cuuint32_t es[2] = {1, 1};
    enc(&m, CU_TENSOR_MAP_DATA_TYPE_BFLOAT16, 2, ptr, dims, strides, box, es, CU_TENSOR_MAP_INTERLEAVE_NONE, sw, promo,
        CU_TENSOR_MAP_FLOAT_OOB_FILL_NONE);
    return m;
}

}

extern "C" void kernel_launch(void* const* d_in, const int* in_sizes, int n_in, void* d_out, int out_size) {
    (void)in_sizes; (void)n_in; (void)out_size;
    static EncodeFn enc = nullptr;
    static int sms = 0;
    if (!enc) {
        cudaDriverEntryPointQueryResult qr;
        cudaGetDriverEntryPoint("cuTensorMapEncodeTiled", (void**)&enc, cudaEnableDefault, &qr);
        int dev = 0;
        cudaGetDevice(&dev);
        cudaDeviceGetAttribute(&sms, cudaDevAttrMultiProcessorCount, dev);
        cudaFuncSetAttribute(fused_decode_kernel, cudaFuncAttributeMaxDynamicSharedMemorySize, SM_TOTAL);
    }
    if (sms < NCTAS) return;
    const CUtensorMapL2promotion WPROMO = CU_TENSOR_MAP_L2_PROMOTION_L2_128B;
#define GPROMO 2
#define DPROMO 2
    Params p;
    p.k = make_map(enc, d_in[1], 64, (uint64_t)NBH * SK * 3, 64, TILE_ROWS / NPART, CU_TENSOR_MAP_SWIZZLE_128B, CU_TENSOR_MAP_L2_PROMOTION_NONE);
    p.v = make_map(enc, d_in[2], 64, (uint64_t)NBH * SK * 3, 64, TILE_ROWS / NPART, CU_TENSOR_MAP_SWIZZLE_128B, CU_TENSOR_MAP_L2_PROMOTION_NONE);
    p.wq = make_map(enc, d_in[3], NH * DH, DM, 48, 160, CU_TENSOR_MAP_SWIZZLE_NONE, WPROMO);
    p.wo = make_map(enc, d_in[4], DM, NH * DH, 32, DH, CU_TENSOR_MAP_SWIZZLE_64B, WPROMO);
    p.wg = make_map(enc, d_in[7], FF, DM, 32, 160, CU_TENSOR_MAP_SWIZZLE_64B, (CUtensorMapL2promotion)GPROMO);
    p.wu = make_map(enc, d_in[8], FF, DM, 32, 160, CU_TENSOR_MAP_SWIZZLE_64B, (CUtensorMapL2promotion)GPROMO);
    {
        const cuuint64_t dims[4] = {DM, 2, 8, FF / 16}, strides[3] = {8 * DM * 2, DM * 2, 16 * DM * 2};
        const cuuint32_t box[4] = {16, 2, 8, 12}, es[4] = {1, 1, 1, 1};
        enc(&p.wd, CU_TENSOR_MAP_DATA_TYPE_BFLOAT16, 4, d_in[9], dims, strides, box, es, CU_TENSOR_MAP_INTERLEAVE_NONE,
            CU_TENSOR_MAP_SWIZZLE_32B, (CUtensorMapL2promotion)DPROMO, CU_TENSOR_MAP_FLOAT_OOB_FILL_NONE);
    }
    p.x = (const __nv_bfloat16*)d_in[0];
    p.wr = (const __nv_bfloat16*)d_in[6];
    p.out = (__nv_bfloat16*)d_out;
    fused_decode_kernel<<<NCTAS, NTHREADS, SM_TOTAL, cudaStreamPerThread>>>(p);
}
```

```cpp
#include <cuda_runtime.h>
#include <cuda_bf16.h>
#include <cuda.h>
#include <stdint.h>

namespace {

constexpr int NB = 4, NH = 32, SK = 8192, DH = 192, DM = 640, FF = 1536;
constexpr int NBH = NB * NH;
constexpr int TILE = 64;
constexpr int UPB = SK / TILE;
constexpr int NUNITS = NBH * UPB;
constexpr int TILE_BYTES = TILE * DH * 2;
constexpr int TILE_ROWS = TILE * 3;
constexpr int NCTAS = 132;
constexpr int NQ_CTAS = 128;
constexpr int NE_CTAS = 112;
#define ROLES 1
__host__ __device__ constexpr bool is_f(int cta) { return cta < 96 && !(cta & 2); }
__host__ __device__ constexpr bool is_g(int cta) { return cta < 80 && (cta & 2); }
__host__ __device__ constexpr int ffn_slice(int cta) { return (cta >> 2) * 2 + (cta & 1); }

#define NWORK 2
#define NPART 1
#define NSPARE 1
#define SPARE_NS 0
#define LAG 2
#define NPOOL 640
#define RED0 116
#define RING 12
#define OREP 3
#define K0_DELAY_NS 1000
#define WO_AT_NS 3800
#define FW_TICKET 400
#define FW_AT_NS 3840
#define FW_GAP 320
#define FW_GAP2 200
#define FW_STAG (FW_GAP / 2)
#define HREP2 2
#define LSTAT 1
#define WQ_FENCE 0
#define NPROBE 24
#define SIDE_XOR 0
#define FW_MID 2300
constexpr int NAUX = 8;
constexpr int NTHREADS = (NAUX + NWORK + 2) * 32;
constexpr int SPIN_MAX = 1 << 22;

constexpr int SM_KV = 0;
constexpr int SM_A = SM_KV + NWORK * TILE_BYTES;
constexpr int SM_W = SM_A + 61440;
constexpr int SM_X = SM_W + 81920;
constexpr int XPITCH = 648;
constexpr int HPITCH = 1344;
constexpr int SM_RED = SM_X + 5 * HPITCH + 64;
constexpr int SM_RED2 = SM_RED + 8 * 48 * 4 * 4;
constexpr int SM_MISC = SM_RED2 + 4096;
constexpr int BAR_WQ = SM_MISC + 32, BAR_WO = SM_MISC + 40, SM_SIDE = SM_MISC + 48, BAR_FW = SM_MISC + 64;
constexpr int BAR_KV = BAR_FW + 64;
constexpr int SM_TOTAL = BAR_KV + 2 * NWORK * NPART * 8;
static_assert(LAG == 2 && SM_W % 1024 == 0 && NB * XPITCH * 2 <= 4 * HPITCH && SM_RED % 128 == 0, "smem layout");

struct Params {
    CUtensorMap k, v;
    CUtensorMap wq;
    CUtensorMap wo;
    CUtensorMap wg, wu;
    CUtensorMap wd;
    const __nv_bfloat16 *x, *wr;
    __nv_bfloat16* out;
};

struct Early {
    uint32_t q[96];
    uint32_t umax[UPB];
};
struct Twin { uint32_t w[4][1024]; };
constexpr int PROBE = 1024 - 32;
#define LSTRIDE 16
struct State {
    Twin ax[3];
    Twin hx;
    Twin ox[OREP];
    Twin lx;
    float4 oacc[NBH * 64];
    float2 attn[NB][DM];
    uint32_t fw_time[32];
    float2 lsum[NBH][LSTRIDE];
    uint32_t score[NPOOL][32];
};
__host__ __device__ constexpr int oidx(int row, int grp) {
    return (row >> 2) * 256 + ((row & 1) * 2 + (grp >> 5)) * 64 + (row & 2) * 16 + (grp & 31);
}
constexpr int STATE_V4 = ((sizeof(State) / 32 + NQ_CTAS - 1) / NQ_CTAS) * 2;
static_assert(sizeof(State) % 32 == 0, "State is cleared in whole sectors");
static_assert(sizeof(Early) == 56 * 16, "an Early entry is cleared by 56 threads");
struct Scratch {
    State st;
    unsigned work[64];
    unsigned cnt_z[32];
    Early early[NBH];
    alignas(4096) float4 ring[RING][UPB][64];
};
constexpr size_t PAGE = 2u << 20;
static_assert(sizeof(Scratch) <= PAGE, "scratch must fit one page");
__device__ __align__(128) unsigned char g_raw[2 * PAGE];
__device__ __forceinline__ Scratch* scratch() {
    return reinterpret_cast<Scratch*>((reinterpret_cast<uintptr_t>(g_raw) + PAGE - 1) & ~(uintptr_t)(PAGE - 1));
}
#define g_early scratch()->early
#define g_st scratch()->st
#define g_ring scratch()->ring
#define g_cnt_z scratch()->cnt_z
#define g_work scratch()->work
#define TS(i)
#define TSW(i)
#define TS2(i)
#define TSI(n, i)
#define PH(i)
#define CK(i, dep)
#define ARR()
#define PROG(u)

__device__ __forceinline__ uint32_t s2u(const void* p) { return (uint32_t)__cvta_generic_to_shared(p); }
__device__ __forceinline__ void mbar_init(uint32_t bar, int cnt) {
    asm volatile("mbarrier.init.shared::cta.b64 [%0], %1;" :: "r"(bar), "r"(cnt) : "memory");
}
__device__ __forceinline__ void mbar_expect_tx(uint32_t bar, uint32_t bytes) {
    asm volatile("mbarrier.arrive.expect_tx.shared::cta.b64 _, [%0], %1;" :: "r"(bar), "r"(bytes) : "memory");
}
__device__ __forceinline__ void mbar_wait(uint32_t bar, uint32_t parity) {
    asm volatile("{\n.reg .pred p;\n.reg .u32 n;\nmov.u32 n, 0;\nWAIT_LOOP:\n"
                 "mbarrier.try_wait.parity.shared::cta.b64 p, [%0], %1;\n"
                 "@p bra WAIT_DONE;\nadd.u32 n, n, 1;\nsetp.lt.u32 p, n, %2;\n@p bra WAIT_LOOP;\nWAIT_DONE:\n}"
                 :: "r"(bar), "r"(parity), "n"(SPIN_MAX) : "memory");
}
__device__ __forceinline__ void request_tile(uint32_t dst, const CUtensorMap* tm, int unit, uint32_t bar, uint64_t pol) {
#pragma unroll
    for (int i = 0; i < NPART; i++)
        asm volatile("{\n.reg .pred p;\nelect.sync _|p, 0xffffffff;\n"
                     "@p mbarrier.arrive.expect_tx.shared::cta.b64 _, [%2], %6;\n"
                     "@p cp.async.bulk.tensor.2d.shared::cluster.global.mbarrier::complete_tx::bytes.L2::cache_hint "
                     "[%0], [%1, {%3, %4}], [%2], %5;\n}"
                     :: "r"(dst + i * (TILE_BYTES / NPART)), "l"(tm), "r"(bar + i * 8), "r"(0), "r"(unit * TILE_ROWS + i * (TILE_ROWS / NPART)),
                        "l"(pol), "n"(TILE_BYTES / NPART) : "memory");
}
__device__ __forceinline__ void put_groups(void* dst, int mode, const float (&o)[6], float tag, float tag2) {
    asm volatile("{\n.reg .pred s, r, t;\n.reg .b128 u, v;\n.reg .b64 a, b;\n"
                 "setp.eq.s32 s|r, %1, 0;\nsetp.eq.s32 t, %1, 2;\n"
                 "@r red.relaxed.gpu.global.add.v4.f32 [%0], {%2,%3,%4,%8};\n"
                 "@t red.relaxed.gpu.global.add.v4.f32 [%0+4096], {%2,%3,%4,%8};\n"
                 "@r red.relaxed.gpu.global.add.v4.f32 [%0+128], {%5,%6,%7,%9};\n"
                 "@t red.relaxed.gpu.global.add.v4.f32 [%0+4224], {%5,%6,%7,%9};\n"
                 "mov.b64 a, {%2, %3};\nmov.b64 b, {%4, %8};\nmov.b128 u, {a, b};\n"
                 "mov.b64 a, {%5, %6};\nmov.b64 b, {%7, %9};\nmov.b128 v, {a, b};\n"
                 "@s st.relaxed.gpu.global.b128 [%0], u;\n@s st.relaxed.gpu.global.b128 [%0+128], v;\n}"
                 :: "l"(dst), "r"(mode), "f"(o[0]), "f"(o[1]), "f"(o[2]), "f"(o[3]), "f"(o[4]), "f"(o[5]), "f"(tag), "f"(tag2) : "memory");
}
__device__ __forceinline__ void tma_box(uint32_t dst, const CUtensorMap* tm, int col, int row, uint32_t bar) {
    asm volatile("cp.async.bulk.tensor.2d.shared::cluster.global.mbarrier::complete_tx::bytes [%0], [%1, {%3, %4}], [%2];"
                 :: "r"(dst), "l"(tm), "r"(bar), "r"(col), "r"(row) : "memory");
}
__device__ __forceinline__ uint32_t lds32(uint32_t addr) {
    uint32_t v;
    asm volatile("ld.shared.u32 %0, [%1];" : "=r"(v) : "r"(addr) : "memory");
    return v;
}
__device__ __forceinline__ void ldsm4(uint32_t (&r)[4], uint32_t addr) {
    asm volatile("ldmatrix.sync.aligned.m8n8.x4.shared.b16 {%0,%1,%2,%3}, [%4];"
                 : "=r"(r[0]), "=r"(r[1]), "=r"(r[2]), "=r"(r[3]) : "r"(addr) : "memory");
}
__device__ __forceinline__ void ldsm4t(uint32_t (&r)[4], uint32_t addr) {
    asm volatile("ldmatrix.sync.aligned.m8n8.x4.trans.shared.b16 {%0,%1,%2,%3}, [%4];"
                 : "=r"(r[0]), "=r"(r[1]), "=r"(r[2]), "=r"(r[3]) : "r"(addr) : "memory");
}
__device__ __forceinline__ void mma16816(float (&c)[4], const uint32_t (&a)[4], uint32_t b0, uint32_t b1) {
    asm volatile("mma.sync.aligned.m16n8k16.row.col.f32.bf16.bf16.f32 {%0,%1,%2,%3}, {%4,%5,%6,%7}, {%8,%9}, {%0,%1,%2,%3};"
                 : "+f"(c[0]), "+f"(c[1]), "+f"(c[2]), "+f"(c[3])
                 : "r"(a[0]), "r"(a[1]), "r"(a[2]), "r"(a[3]), "r"(b0), "r"(b1));
}
__device__ __forceinline__ uint4 ld_relaxed_v4(const void* p) {
    uint4 v;
    asm volatile("ld.relaxed.gpu.global.v4.u32 {%0,%1,%2,%3}, [%4];" : "=r"(v.x), "=r"(v.y), "=r"(v.z), "=r"(v.w) : "l"(p) : "memory");
    return v;
}
__device__ __forceinline__ float4 ld_relaxed_f4(const void* p) {
    float4 v;
    asm volatile("ld.relaxed.gpu.global.v4.f32 {%0,%1,%2,%3}, [%4];" : "=f"(v.x), "=f"(v.y), "=f"(v.z), "=f"(v.w) : "l"(p) : "memory");
    return v;
}
__device__ __forceinline__ float2 ld_relaxed_f2(const void* p) {
    float2 v;
    asm volatile("ld.relaxed.gpu.global.v2.f32 {%0,%1}, [%2];" : "=f"(v.x), "=f"(v.y) : "l"(p) : "memory");
    return v;
}
__device__ __forceinline__ float4 ld_relaxed_b128(const void* p) {
    float4 v;
    asm volatile("{\n.reg .b128 t;\n.reg .b64 a, b;\nld.relaxed.gpu.global.b128 t, [%4];\nmov.b128 {a, b}, t;\n"
                 "mov.b64 {%0, %1}, a;\nmov.b64 {%2, %3}, b;\n}" : "=f"(v.x), "=f"(v.y), "=f"(v.z), "=f"(v.w) : "l"(p) : "memory");
    return v;
}
__device__ __forceinline__ void st_relaxed_b128(void* p, float x, float y, float z, float w) {
    asm volatile("{\n.reg .b128 t;\n.reg .b64 a, b;\nmov.b64 a, {%1, %2};\nmov.b64 b, {%3, %4};\nmov.b128 t, {a, b};\n"
                 "st.relaxed.gpu.global.b128 [%0], t;\n}" :: "l"(p), "f"(x), "f"(y), "f"(z), "f"(w) : "memory");
}
__device__ __forceinline__ unsigned ld_acquire(const unsigned* p) {
    unsigned v;
    asm volatile("ld.acquire.gpu.global.u32 %0, [%1];" : "=r"(v) : "l"(p) : "memory");
    return v;
}
__device__ __forceinline__ void st_relaxed(void* p, uint32_t v) {
    asm volatile("st.relaxed.gpu.global.u32 [%0], %1;" :: "l"(p), "r"(v) : "memory");
}
__device__ __forceinline__ void red_f2(float* p, float a, float b) {
    asm volatile("red.relaxed.gpu.global.add.v2.f32 [%0], {%1,%2};" :: "l"(p), "f"(a), "f"(b) : "memory");
}
__device__ __forceinline__ void draw(int& ticket, unsigned* ctr, bool pred) {
    asm volatile("{\n.reg .pred p;\nsetp.ne.u32 p, %2, 0;\n@p atom.relaxed.gpu.global.inc.u32 %0, [%1], 0x7fffffff;\n}"
                 : "+r"(ticket) : "l"(ctr), "r"((uint32_t)pred) : "memory");
}
__device__ __forceinline__ void red_release(unsigned* p) {
    asm volatile("red.release.gpu.global.add.u32 [%0], 1;" :: "l"(p) : "memory");
}
__device__ __forceinline__ uint32_t ld_relaxed_u32(const void* p) {
    uint32_t v;
    asm volatile("ld.relaxed.gpu.global.u32 %0, [%1];" : "=r"(v) : "l"(p) : "memory");
    return v;
}
__device__ __forceinline__ float rcp_approx(float v) {
    float r;
    asm("rcp.approx.ftz.f32 %0, %1;" : "=f"(r) : "f"(v));
    return r;
}
__device__ __forceinline__ float sigmoid_approx(float v) {
    float e;
    asm("ex2.approx.ftz.f32 %0, %1;" : "=f"(e) : "f"(v * -1.4426950408889634f));
    return rcp_approx(1.0f + e);
}
__device__ __forceinline__ float sqrt_approx(float v) {
    float r;
    asm("sqrt.approx.ftz.f32 %0, %1;" : "=f"(r) : "f"(v));
    return r;
}
__device__ __forceinline__ void wait_count(const unsigned* p, unsigned target) {
#pragma unroll 1
    for (int it = 0; it < SPIN_MAX; it++) {
        if (ld_acquire(p) >= target) break;
        __nanosleep(400);
    }
}
__device__ __forceinline__ void wait_row(int bh, float n) {
#pragma unroll 1
    for (int it = 0; it < SPIN_MAX; it++) {
        const float c = ld_relaxed_f2(g_st.lsum[bh]).y;
        if (c >= n) break;
        if (c == 0.f) __nanosleep(600);
    }
}
__device__ __forceinline__ void wait_row_o(int bh, float n) {
    wait_row(bh, n);
    if (bh >= RED0) return;
#pragma unroll 1
    for (int it = 0; it < SPIN_MAX; it++) {
        if (__uint_as_float(ld_relaxed_u32(&g_st.oacc[oidx(bh, 0)].w)) == UPB) break;
        __nanosleep(300);
    }
}
__device__ __forceinline__ void spin_ns(int ns) {
    const long long t0 = clock64();
    while (clock64() - t0 < (long long)ns * 2) {}
}
__device__ __forceinline__ uint32_t pack_bf16(float lo, float hi) {
    uint32_t r;
    asm("cvt.rn.bf16x2.f32 %0, %1, %2;" : "=r"(r) : "f"(hi), "f"(lo));
    return r;
}
__device__ __forceinline__ float bf16r(float v) { return __uint_as_float(pack_bf16(0.f, v)); }
__device__ __forceinline__ uint32_t pack_neg(float lo, float hi) {
    const uint32_t w = pack_bf16(-lo, -hi);
    return w ? w : 0x80008000u;
}
__device__ __forceinline__ float lo_f(uint32_t v) { return __uint_as_float(v << 16); }
__device__ __forceinline__ float hi_f(uint32_t v) { return __uint_as_float(v & 0xffff0000u); }
__device__ __forceinline__ float warp_sum(float v) {
#pragma unroll
    for (int o = 16; o; o >>= 1) v += __shfl_xor_sync(0xffffffffu, v, o);
    return v;
}
__device__ __forceinline__ void layernorm20(float (&v)[20]) {
    float s = 0.f;
#pragma unroll
    for (int i = 0; i < 20; i++) s += v[i];
    const float mean = warp_sum(s) * (1.0f / DM);
    float q = 0.f;
#pragma unroll
    for (int i = 0; i < 20; i++) { const float d = v[i] - mean; q += d * d; }
    const float var = bf16r(warp_sum(q) * (1.0f / DM));
    const float m = bf16r(mean);
    const float rden = 1.0f / bf16r(sqrtf(bf16r(var + 1e-5f)));
#pragma unroll
    for (int i = 0; i < 20; i++) v[i] = bf16r(bf16r(v[i] - m) * rden);
}

__device__ __forceinline__ void moments(float m1, float m2, float& nmean, float& rden) {
    m1 *= 1.0f / DM;
    const float var = bf16r(fmaxf(fmaf(-m1, m1, m2 * (1.0f / DM)), 0.f));
    nmean = bf16r(m1);
    rden = rcp_approx(bf16r(sqrt_approx(bf16r(var + 1e-5f))));
}
__device__ __forceinline__ float sel4(int j, float a, float b, float c, float d) {
    float lo, hi, r;
    asm("{\n.reg .pred p;\nsetp.ne.s32 p, %3, 0;\nselp.f32 %0, %2, %1, p;\n}" : "=f"(lo) : "f"(a), "f"(b), "r"(j & 1));
    asm("{\n.reg .pred p;\nsetp.ne.s32 p, %3, 0;\nselp.f32 %0, %2, %1, p;\n}" : "=f"(hi) : "f"(c), "f"(d), "r"(j & 1));
    asm("{\n.reg .pred p;\nsetp.ne.s32 p, %3, 0;\nselp.f32 %0, %2, %1, p;\n}" : "=f"(r) : "f"(lo), "f"(hi), "r"(j & 2));
    return r;
}
template <typename T> __device__ __forceinline__ void pin(T*& p) { asm volatile("" : "+l"(p)); }
__device__ __forceinline__ void pin(uint32_t& v) { asm volatile("" : "+r"(v)); }
__device__ __forceinline__ void pin(float& v) { asm volatile("" : "+f"(v)); }
__device__ __forceinline__ uint32_t after(uint32_t n, float v) {
    asm volatile("{\n.reg .pred p;\nsetp.eq.u32 p, %1, 0x7fc1a5a5;\n@p add.u32 %0, %0, 32;\n}" : "+r"(n) : "r"(__float_as_uint(v)));
    return n;
}
__device__ __forceinline__ float2 lds64f(uint32_t addr) {
    float2 v;
    asm volatile("ld.shared.v2.f32 {%0,%1}, [%2];" : "=f"(v.x), "=f"(v.y) : "r"(addr) : "memory");
    return v;
}
__device__ __forceinline__ void sts32f(uint32_t addr, float v) { asm volatile("st.shared.f32 [%0], %1;" :: "r"(addr), "f"(v) : "memory"); }
template <int ID> __device__ __forceinline__ void fin_arrive() { asm volatile("bar.arrive %0, 288;" :: "n"(ID) : "memory"); }
template <int ID> __device__ __forceinline__ void fin_sync() { asm volatile("bar.sync %0, 288;" :: "n"(ID) : "memory"); }
template <int ID> __device__ __forceinline__ void fin_sync(uint32_t n) { asm volatile("bar.sync %0, %1;" :: "n"(ID), "r"(n) : "memory"); }
__device__ __forceinline__ float2 sum8(uint32_t addr) {
    float2 t[8];
#pragma unroll
    for (int w = 0; w < 8; w++) t[w] = lds64f(addr + w * 128);
    return make_float2(((t[0].x + t[1].x) + (t[2].x + t[3].x)) + ((t[4].x + t[5].x) + (t[6].x + t[7].x)),
                       ((t[0].y + t[1].y) + (t[2].y + t[3].y)) + ((t[4].y + t[5].y) + (t[6].y + t[7].y)));
}
__device__ __forceinline__ float4 sum4x4(uint32_t addr, int pitch) {
    float4 t[4];
#pragma unroll
    for (int w = 0; w < 4; w++)
        asm volatile("ld.shared.v4.f32 {%0,%1,%2,%3}, [%4];" : "=f"(t[w].x), "=f"(t[w].y), "=f"(t[w].z), "=f"(t[w].w) : "r"(addr + w * pitch) : "memory");
    return make_float4((t[0].x + t[1].x) + (t[2].x + t[3].x), (t[0].y + t[1].y) + (t[2].y + t[3].y),
                       (t[0].z + t[1].z) + (t[2].z + t[3].z), (t[0].w + t[1].w) + (t[2].w + t[3].w));
}
__device__ __forceinline__ void sts64f(uint32_t addr, float x, float y) {
    asm volatile("st.shared.v2.f32 [%0], {%1,%2};" :: "r"(addr), "f"(x), "f"(y) : "memory");
}
__device__ __forceinline__ void lds128_if(uint4& v, uint32_t addr, bool pred) {
    asm volatile("{\n.reg .pred p;\nsetp.ne.u32 p, %5, 0;\n@p ld.shared.v4.u32 {%0,%1,%2,%3}, [%4];\n}"
                 : "+r"(v.x), "+r"(v.y), "+r"(v.z), "+r"(v.w) : "r"(addr), "r"((uint32_t)pred) : "memory");
}
__device__ __forceinline__ void sts128f(uint32_t addr, float x, float y, float z, float w) {
    asm volatile("st.shared.v4.f32 [%0], {%1,%2,%3,%4};" :: "r"(addr), "f"(x), "f"(y), "f"(z), "f"(w) : "memory");
}
template <int NJ>
__device__ __forceinline__ void load_o(uint32_t (&ob)[3 * NJ][2], int bh, int J0, int j) {
    float4 v[NJ][4];
    float2 l;
#pragma unroll 1
    for (int it = 0; it < SPIN_MAX; it++) {
#pragma unroll
        for (int J = 0; J < NJ; J++) {
#pragma unroll
            for (int e = 0; e < 4; e++) v[J][e] = ld_relaxed_f4(&g_st.oacc[oidx(bh, j)] + oidx(0, (J0 + J) * 16 + e * 4));
        }
        l = ld_relaxed_f2(g_st.lsum[bh]);
        bool ok = l.y == UPB;
#pragma unroll
        for (int J = 0; J < NJ; J++) {
#pragma unroll
            for (int e = 0; e < 4; e++) ok &= v[J][e].w == UPB;
        }
        if (__all_sync(0xffffffffu, ok)) break;
    }
    const float rl = __fdividef(1.0f, l.x);
#pragma unroll
    for (int J = 0; J < NJ; J++) {
        ob[3 * J][0] = pack_bf16(v[J][0].x * rl, v[J][1].x * rl);     ob[3 * J][1] = pack_bf16(v[J][2].x * rl, v[J][3].x * rl);
        ob[3 * J + 1][0] = pack_bf16(v[J][0].y * rl, v[J][1].y * rl); ob[3 * J + 1][1] = pack_bf16(v[J][2].y * rl, v[J][3].y * rl);
        ob[3 * J + 2][0] = pack_bf16(v[J][0].z * rl, v[J][1].z * rl); ob[3 * J + 2][1] = pack_bf16(v[J][2].z * rl, v[J][3].z * rl);
    }
}
__device__ __forceinline__ int near_side(uint32_t sb) {
    uint32_t v;
    asm volatile("ld.volatile.shared.u32 %0, [%1];" : "=r"(v) : "r"(sb + SM_SIDE) : "memory");
    return v;
}
__device__ __forceinline__ void poll_row(uint4& a, uint4& b, uint2& c, const void* pa, const void* pb, const void* pc, uint32_t sa, uint32_t sc,
                                         bool arrive, bool nap) {
    asm volatile("{\n.reg .pred p, q, r, s;\n.reg .u32 m, n, it;\n"
                 "setp.ne.u32 r, %15, 0;\nsetp.ne.u32 s, %16, 0;\nmov.u32 it, 0;\n"
                 "POLL:\n"
                 "ld.relaxed.gpu.global.v4.u32 {%0,%1,%2,%3}, [%10];\n"
                 "ld.relaxed.gpu.global.v4.u32 {%4,%5,%6,%7}, [%11];\n"
                 "ld.relaxed.gpu.global.v2.u32 {%8,%9}, [%12];\n"
                 "add.u32 it, it, 1;\nsetp.ge.u32 q, it, %17;\n"
                 "st.shared.v4.u32 [%13], {%0,%1,%2,%3};\n"
                 "st.shared.v4.u32 [%13+512], {%4,%5,%6,%7};\n"
                 "st.shared.v2.u32 [%14], {%8,%9};\n"
                 "min.u32 m, %0, %1;\nmin.u32 m, m, %2;\nmin.u32 n, %3, %4;\nmin.u32 n, n, %5;\nmin.u32 m, m, %6;\nmin.u32 m, m, %7;\n"
                 "min.u32 n, n, m;\nmin.u32 m, %8, %9;\nmin.u32 m, m, n;\n"
                 "setp.ne.or.u32 p, m, 0, q;\n"
                 "vote.sync.all.pred p, p, 0xffffffff;\n"
                 "and.pred q, p, r;\n"
                 "@q bar.arrive 7, 288;\n"
                 "@p bra.uni DONE;\n"
                 "@s nanosleep.u32 500;\n"
                 "bra.uni POLL;\n"
                 "DONE:\n}"
                 : "=&r"(a.x), "=&r"(a.y), "=&r"(a.z), "=&r"(a.w), "=&r"(b.x), "=&r"(b.y), "=&r"(b.z), "=&r"(b.w), "=&r"(c.x), "=&r"(c.y)
                 : "l"(pa), "l"(pb), "l"(pc), "r"(sa), "r"(sc), "r"((uint32_t)arrive), "r"((uint32_t)nap), "n"(SPIN_MAX) : "memory");
}
__device__ __forceinline__ void aux_sync() { asm volatile("bar.sync 1, 256;" ::: "memory"); }

__global__ void __launch_bounds__(NTHREADS, 1)
fused_decode_kernel(const __grid_constant__ Params p) {
    extern __shared__ __align__(1024) unsigned char smem[];
    const uint32_t sb = s2u(smem);
    const int tid = threadIdx.x, cta = blockIdx.x;
    if (tid < 32 && cta < NQ_CTAS) {
        asm volatile("{\n.reg .pred p;\nelect.sync _|p, 0xffffffff;\n"
                     "@p mbarrier.init.shared::cta.b64 [%2], 1;\n"
                     "@p fence.mbarrier_init.release.cluster;\n"
                     "@p mbarrier.arrive.expect_tx.shared::cta.b64 _, [%2], 61440;\n"
                     "@p cp.async.bulk.tensor.2d.shared::cluster.global.mbarrier::complete_tx::bytes [%0], [%1, {%3, %4}], [%2];\n"
                     "@p cp.async.bulk.tensor.2d.shared::cluster.global.mbarrier::complete_tx::bytes [%0+15360], [%1, {%3, %5}], [%2];\n"
                     "@p cp.async.bulk.tensor.2d.shared::cluster.global.mbarrier::complete_tx::bytes [%0+30720], [%1, {%3, %6}], [%2];\n"
                     "@p cp.async.bulk.tensor.2d.shared::cluster.global.mbarrier::complete_tx::bytes [%0+46080], [%1, {%3, %7}], [%2];\n}"
                     :: "r"(sb + SM_W), "l"(&p.wq), "r"(sb + BAR_WQ), "r"(cta * 48), "r"(0), "r"(160), "r"(320), "r"(480) : "memory");
    }
    const int warp = __shfl_sync(0xffffffffu, tid >> 5, 0), lane = tid & 31;
    constexpr int grid = NCTAS;
    const int g = lane >> 2, j = lane & 3;
    TS(0);
    if (tid == 160) {
        mbar_init(sb + BAR_WO, 1);
#pragma unroll
        for (int i = 0; i < 8 + 2 * NWORK * NPART; i++) mbar_init(sb + BAR_FW + i * 8, 1);
        sts32f(sb + SM_SIDE, 0.f);
        asm volatile("fence.mbarrier_init.release.cluster;" ::: "memory");
        asm volatile("fence.proxy.async.shared::cta;" ::: "memory");
    }
    __syncthreads();
    if (warp >= NAUX + NWORK) {
        const int fw = warp - (NAUX + NWORK), fi = ffn_slice(cta);
        if (fw == 0) {
            if (cta < NQ_CTAS) {
#pragma unroll
                for (int i = lane; i < STATE_V4; i += 32)
                    if (cta * STATE_V4 + i < (int)(sizeof(State) / 16)) reinterpret_cast<uint4*>(&g_st)[cta * STATE_V4 + i] = make_uint4(0u, 0u, 0u, 0u);
                __syncwarp();
                if (lane == 0) red_release(g_cnt_z);
            }
            if (lane == 0) { TS2(2); wait_count(g_cnt_z, NQ_CTAS); TS2(29); }
            __syncwarp();
            asm volatile("bar.arrive 2, %0;" :: "n"((NWORK + 2) * 32) : "memory");
            fin_arrive<3>();
        } else {
            asm volatile("bar.sync 2, %0;" :: "n"((NWORK + 2) * 32) : "memory");
            if (lane == 0) {
                uint32_t* ctr = &g_st.hx.w[0][PROBE];
                uint32_t best[2] = {~0u, ~0u};
#pragma unroll 1
                for (int i = 0; i < NPROBE; i++) {
#pragma unroll
                    for (int c = 0; c < 2; c++) {
                        uint32_t t0 = clock(), t1 = t0, v;
                        asm volatile("atom.relaxed.gpu.global.inc.u32 %0, [%1], 0x7fffffff;" : "=r"(v) : "l"(ctr + c * 1024) : "memory");
                        asm volatile("{\n.reg .pred p;\nsetp.ne.u32 p, %1, 0xffffffff;\n@p mov.u32 %0, %%clock;\n}" : "+r"(t1) : "r"(v) : "memory");
                        best[c] = min(best[c], t1 - t0);
                    }
                    __nanosleep(1000);
                }
                sts32f(sb + SM_SIDE, __uint_as_float((best[1] < best[0]) ^ SIDE_XOR));
            }
            __syncwarp();
        }
        int job = cta;
        auto sum_rows = [&](int row_end) {
#pragma unroll 1
            for (; job < 8 * min(row_end, RED0); job += NCTAS) {
                const int row = job >> 3, grp = (job & 7) * 8 + (lane & 7);
                if (lane == 0) wait_row(row, UPB);
                __syncwarp();
                const float4* src = &g_ring[row % RING][lane >> 3][grp];
                float sx = 0.f, sy = 0.f, sz = 0.f;
#pragma unroll 1
                for (int i = 0; i < 2; i++, src += 64 * 64) {
                    float4 v[16];
#pragma unroll 1
                    for (int it = 0; it < SPIN_MAX; it++) {
                        bool ok = true;
#pragma unroll
                        for (int k = 0; k < 16; k++) v[k] = ld_relaxed_b128(src + k * 4 * 64);
#pragma unroll
                        for (int k = 0; k < 16; k++) ok &= v[k].w == (float)(row + 1);
                        if (__all_sync(0xffffffffu, ok)) break;
                    }
#pragma unroll
                    for (int k = 0; k < 16; k++) { sx += v[k].x; sy += v[k].y; sz += v[k].z; }
                }
#pragma unroll
                for (int o = 8; o < 32; o <<= 1) {
                    sx += __shfl_xor_sync(0xffffffffu, sx, o); sy += __shfl_xor_sync(0xffffffffu, sy, o); sz += __shfl_xor_sync(0xffffffffu, sz, o);
                }
                if (lane < 8) st_relaxed_b128(&g_st.oacc[oidx(row, grp)], sx, sy, sz, UPB);
            }
        };
        const int ho0 = lane / 20 * 256 + lane % 20 * 4, ho1 = (lane + 32) / 20 * 256 + (lane + 32) % 20 * 4, ho2 = 3 * 256 + 16 + 2 * lane;
        uint32_t wr[10] = {};
        float wsum = 0.f;
        if (is_g(cta) && fw == 0) {
#pragma unroll
            for (int i = 0; i < 10; i++) {
                const int w = 4 * lane + 128 * (i >> 2) + (i & 3) - (i >= 8 ? 2 * lane : 0);
                wr[i] = *reinterpret_cast<const uint32_t*>(p.wr + (w >> 4) * 32 + (w & 3) * 8 + ((w >> 1) & 6));
                wsum += lo_f(wr[i]) + hi_f(wr[i]);
            }
            wsum = warp_sum(wsum);
        }
        const int fb = lane >> 3, fg = lane & 7;
        if (fw == 0) {
#pragma unroll
            for (int i = lane; i < DM / 2; i += 32) sts32f(sb + SM_X + 4 * HPITCH + i * 4, __uint_as_float(0x3f803f80u));
        }
        float nmean = 0.f, rden = 0.f, sig = 0.f;
#pragma unroll 1
        for (int b = 0; b < NB; b++) {
            const bool ffn = b >= NB - 2;
            if (fw == 0) {
                sum_rows((b + 1) * NH);
                if (ffn) asm volatile("bar.arrive 8, 64;" ::: "memory");
            } else if (ffn) {
                asm volatile("bar.sync 8, 64;" ::: "memory");
                if (lane == 0 && b == NB - 1) {
                    uint32_t t0 = 0, now;
#pragma unroll 1
                    for (int it = 0; it < SPIN_MAX; it++) {
                        t0 = ld_relaxed_u32(g_st.fw_time);
                        if (t0) break;
                        __nanosleep(400);
                    }
                    asm volatile("fence.proxy.async.shared::cta;" ::: "memory");
#pragma unroll 1
                    for (int it = 0; it < SPIN_MAX; it++) {
                        asm volatile("mov.u32 %0, %%globaltimer_lo;" : "=r"(now));
                        if ((int)(now - t0) >= FW_AT_NS) break;
                    }
                    TS2(9);
                    uint32_t t = clock() + (is_f(cta) ? (fi & 1) * FW_STAG : FW_MID + (fi & 3) * (FW_GAP2 / 4));
#pragma unroll 1
                    for (int i = 0; i < 8; i++) {
                        const uint32_t bar = sb + BAR_FW + i * 8;
                        while ((int)(clock() - t) < 0) {}
                        if (is_f(cta)) {
                            mbar_expect_tx(bar, 10240);
                            tma_box(sb + SM_W + i * 10240, (i & 1) ? &p.wu : &p.wg, fi * 32, (i >> 1) * 160, bar);
                            t += FW_GAP;
                        } else if (is_g(cta)) {
                            mbar_expect_tx(bar, 6144);
                            asm volatile("cp.async.bulk.tensor.4d.shared::cluster.global.mbarrier::complete_tx::bytes [%0], [%1, {%3, %4, %4, %5}], [%2];"
                                         :: "r"(sb + SM_W + i * 6144), "l"(&p.wd), "r"(bar), "r"(fi * 16), "r"(0), "r"(i * 12) : "memory");
                            t += FW_GAP2;
                        }
                    }
                }
                __syncwarp();
                if (is_f(cta)) {
                    const uint32_t* src = &g_st.hx.w[near_side(sb)][min(fb, b) * 256 + 96];
                    float4 m;
#pragma unroll 1
                    for (int it = 0; it < SPIN_MAX; it++) {
                        m = ld_relaxed_f4(src);
                        if (__all_sync(0xffffffffu, m.y + m.w == 2 * (NCTAS - NE_CTAS))) break;
                        if (b < NB - 1) __nanosleep(500);
                    }
                    moments(m.x, m.z, m.x, m.z);
                    sts64f(sb + SM_RED + 5120 + fb * 8, m.x, m.z);
                }
            }
            if (fw == 0 && cta >= NE_CTAS) {
                const int lc = cta - NE_CTAS, col = lc * 32 + 2 * (lane & 15);
                const uint32_t xv = *reinterpret_cast<const uint32_t*>(p.x + b * DM + col);
                uint32_t* dst = &(ffn ? g_st.hx.w : g_st.lx.w + 2)[lane >> 4][(b & 1) * 128 + lc / 5 * 256 + lc % 5 * 16 + (col & 6) * 2 + ((col >> 3) & 3)];
                uint32_t part = sb + SM_RED + (lane & 15) * 8;
                if (lane == 0) wait_row(b * NH + 28, 1);
                __syncwarp();
                float4 early;
#pragma unroll 1
                for (int it = 0; it < SPIN_MAX; it++) {
                    early = ld_relaxed_f4(&g_st.attn[b][col]);
                    if (__all_sync(0xffffffffu, early.y == NE_CTAS / 4 && early.w == NE_CTAS / 4)) break;
                }
                if (early.x != 1.2345f && lane == 0) TS2(6);
                CK(1, __float_as_uint(early.x));
                float x0 = lo_f(xv), x1 = hi_f(xv);
                pin(dst); pin(part); pin(x0); pin(x1);
                fin_sync<4>();
                CK(2, lds32(sb + SM_RED));
                const float2 late = sum8(part);
                const uint32_t hv = pack_neg(x0 + bf16r(early.x + late.x), x1 + bf16r(early.z + late.y));
                st_relaxed(dst, hv);
                if (HREP2 && ffn) st_relaxed(dst + 2048, hv);
                CK(3, 0);
                float m = lane < 16 ? lo_f(hv) + hi_f(hv) : fmaf(lo_f(hv), lo_f(hv), hi_f(hv) * hi_f(hv));
#pragma unroll
                for (int o = 1; o < 16; o <<= 1) m += __shfl_xor_sync(0xffffffffu, m, o);
                if ((lane & 14) == 0) red_f2(reinterpret_cast<float*>(&g_st.hx.w[lane & 1][b * 256 + 96 + (lane >> 4) * 2]), m, 1.f);
                fin_arrive<5>();
            }
            if (fw == 0 && (is_g(cta) || is_f(cta))) {
                const uint32_t* src = &(ffn ? g_st.hx.w : g_st.lx.w + 2)[near_side(sb) ^ (HREP2 && ffn && (HREP2 == 1 ? (fi & 1) : is_g(cta)) ? 3 : 0)][(b & 1) * 128];
                const uint32_t hrow = sb + SM_X + b * HPITCH;
                if (lane == 0) wait_row(b * NH + NH - 1, UPB);
                __syncwarp();
                uint4 h0, h1;
                uint2 h2;
                poll_row(h0, h1, h2, src + ho0, src + ho1, src + ho2, hrow + lane * 16, hrow + 1024 + lane * 8, ffn, b < NB - 1);
                CK(4, h0.x);
                if (!LSTAT || is_g(cta)) {
                const uint32_t hw[10] = {h0.x, h0.y, h0.z, h0.w, h1.x, h1.y, h1.z, h1.w, h2.x, h2.y};
                float s1[2] = {}, s2[2] = {};
#pragma unroll
                for (int i = 0; i < 10; i++) {
                    const float v0 = lo_f(hw[i]), v1 = hi_f(hw[i]);
                    s1[i & 1] += v0 + v1;
                    s2[i & 1] = fmaf(v0, v0, fmaf(v1, v1, s2[i & 1]));
                }
                float m1 = s1[0] + s1[1], m2 = s2[0] + s2[1];
#pragma unroll
                for (int o = 16; o; o >>= 1) { m1 += __shfl_xor_sync(0xffffffffu, m1, o); m2 += __shfl_xor_sync(0xffffffffu, m2, o); }
                moments(m1, m2, m1, m2);
                {
                    float rr = 0.f;
#pragma unroll
                    for (int i = 0; i < 10; i++) rr = fmaf(lo_f(hw[i]), lo_f(wr[i]), fmaf(hi_f(hw[i]), hi_f(wr[i]), rr));
                    const float sg = bf16r(sigmoid_approx(bf16r((m1 * wsum - warp_sum(rr)) * m2)));
                    if (fb == b) { nmean = m1; rden = m2; sig = sg; }
                    __syncwarp();
                    if (ffn) {
                        const int gi = fi, yj = 2 * (fb & 1) + (fb >> 1);
                        uint32_t ypart = sb + SM_RED2 + yj * 128 + ((fg + 2 * yj) & 7) * 16;
                        __nv_bfloat16* out = p.out + fb * DM + gi * 16 + fg;
                        const float2 hw2 = lds64f(sb + SM_X + fb * HPITCH + ((gi >> 1) * 16 + (fg & 6) * 2 + (gi & 1) * 2) * 4);
                        const uint32_t w0 = __float_as_uint(hw2.x), w1 = __float_as_uint(hw2.y);
                        float nh0 = (fg & 1) ? hi_f(w0) : lo_f(w0), nh1 = (fg & 1) ? hi_f(w1) : lo_f(w1);
                        float ln0 = bf16r(bf16r(nmean - nh0) * rden), ln1 = bf16r(bf16r(nmean - nh1) * rden);
                        pin(ypart); pin(out);
                        fin_sync<6>(after(after(after(288, sig), ln0), ln1));
                        CK(10, lds32(ypart));
                        const float4 ya = sum4x4(ypart, 512), yb = sum4x4(ypart + 2048, 512);
                        const float4 y = make_float4(ya.x + yb.x, ya.y + yb.y, ya.z + yb.z, ya.w + yb.w);
                        const float y0 = -(((fb & 1) ? y.y : y.x) + __shfl_xor_sync(0xffffffffu, (fb & 1) ? y.x : y.y, 8));
                        const float y1 = -(((fb & 1) ? y.w : y.z) + __shfl_xor_sync(0xffffffffu, (fb & 1) ? y.z : y.w, 8));
                        const uint32_t ov = pack_bf16(bf16r(ln0 + bf16r(bf16r(y0) * sig)) - nh0, bf16r(ln1 + bf16r(bf16r(y1) * sig)) - nh1);
                        if (b == NB - 1) {
                            asm volatile("st.global.u16 [%0], %1;" :: "l"(out), "h"((unsigned short)(ov & 0xffffu)) : "memory");
                            asm volatile("st.global.u16 [%0], %1;" :: "l"(out + 8), "h"((unsigned short)(ov >> 16)) : "memory");
                        }
                        CK(11, 0);
                        if (lane == 0) TS2(13);
                    }
                }
                }
            }
            if (is_f(cta) && ffn) {
                const int ks = (2 * fi + fw) % 12;
                uint32_t* dst = &g_st.ax[ks >> 2].w[(~b & 1) * 2][((fi / 6) * 32 + ((ks & 1) * 4 + fb) * 4 + (fg & 3)) * 4 + (ks & 2) + (fg >> 2)];
                uint32_t part = sb + SM_RED + fw * 2560 + fb * 128 + ((fg + (fb & 2)) & 7) * 16;
                uint32_t psum = sb + SM_RED + fw * 2560 + 4 * 128 + ((fg + 4) & 7) * 16;
                pin(dst); pin(part); pin(psum);
                asm volatile("bar.sync 4, 320;" ::: "memory");
                CK(6, lds32(part));
                const float4 d = sum4x4(part, 640), cs = sum4x4(psum, 640);
                const float2 mo = lds64f(sb + SM_RED + 5120 + fb * 8);
                nmean = mo.x; rden = mo.y;
                const float g0 = bf16r(fmaf(nmean, cs.x, -d.x) * rden), g1 = bf16r(fmaf(nmean, cs.y, -d.y) * rden);
                const float u0 = bf16r(fmaf(nmean, cs.z, -d.z) * rden), u1 = bf16r(fmaf(nmean, cs.w, -d.w) * rden);
                const uint32_t av = pack_neg(bf16r(g0 * sigmoid_approx(g0)) * u0, bf16r(g1 * sigmoid_approx(g1)) * u1);
                st_relaxed(dst, av);
                st_relaxed(dst + 1024, av);
                CK(7, 0);
            }
        }
        if (cta == 0 && tid == (NAUX + NWORK) * 32) { g_work[0] = 0; g_work[32] = 0; g_cnt_z[0] = 0; }
        return;
    }
    if (warp >= NAUX) {
        const int wk = warp - NAUX;
        const uint32_t bar = sb + BAR_KV + wk * (NPART * 8);
        const uint32_t buf = sb + SM_KV + wk * TILE_BYTES;
        uint64_t pol;
        asm volatile("createpolicy.fractional.L2::evict_first.b64 %0, 1.0;" : "=l"(pol));
        const int nstatic = NWORK * grid;
        constexpr int POOL0 = NUNITS - NPOOL;
        int uk = wk * grid + cta;
        if (K0_DELAY_NS) spin_ns(K0_DELAY_NS);
        __syncwarp();
        request_tile(buf, &p.k, uk, bar, pol);
        if (lane == 0) {
            if (wk == 0) {
                const uint32_t wbar = sb + BAR_WO;
                spin_ns(WO_AT_NS - K0_DELAY_NS);
                mbar_expect_tx(wbar, cta < NE_CTAS ? 61440 : 49152);
#pragma unroll 1
                for (int i = 0; i < (cta < NE_CTAS ? 5 : 4); i++) {
                    if (cta < NE_CTAS) tma_box(sb + SM_A + i * 12288, &p.wo, (cta & 3) * 160 + i * 32, (cta >> 2) * DH, wbar);
                    else tma_box(sb + SM_A + i * 12288, &p.wo, (cta - NE_CTAS) * 32, (28 + i) * DH, wbar);
                }
            }
        }
        __syncwarp();
        uint32_t koff[3], voff[3];
        {
            const int r = lane & 7, hf = (lane >> 3) & 1;
            const int kkey = hf ? 8 + (r ^ 1) : r;
            const int vh = lane >> 4;
            const int vkey = ((r & 1) ? 8 : 0) + (vh ? (r ^ 1) : r);
#pragma unroll
            for (int b = 0; b < 3; b++) {
                const int rk = 3 * kkey + b, rv = 3 * vkey + b;
                koff[b] = buf + rk * 128 + (((lane >> 4) ^ (rk & 7)) << 4);
                voff[b] = buf + rv * 128 + ((hf ^ (rv & 7)) << 4);
            }
        }
        uint32_t phase = 0, kbar = bar;
        uint4 qf[6];
        auto load_q = [&](int u) {
            const uint32_t* q = &g_early[u / UPB].q[j * 4];
#pragma unroll
            for (int i = 0; i < 6; i++) qf[i] = ld_relaxed_v4(q + i * 16);
        };
        load_q(uk);
        int uq[LAG];
        uint32_t sq[LAG];
#pragma unroll
        for (int i = 0; i < LAG; i++) { uq[i] = -1; sq[i] = 0; }
        uint4 mv = make_uint4(0u, 0u, 0u, 0u);
        float freed = UPB;
        while (true) {
            const int uv = uq[0];
            uint32_t sv = sq[0];
#pragma unroll
            for (int i = 0; i + 1 < LAG; i++) { uq[i] = uq[i + 1]; sq[i] = sq[i + 1]; }
            uq[LAG - 1] = uk;
            if (uk < NUNITS) {
                PH(7);
#pragma unroll 1
                for (int it = 0; it < SPIN_MAX; it++) {
                    uint32_t lo = 0xffffffffu;
#pragma unroll
                    for (int i = 0; i < 6; i++) lo = min(min(lo, min(qf[i].x, qf[i].y)), min(qf[i].z, qf[i].w));
                    if (__all_sync(0xffffffffu, lo != 0)) break;
                    __nanosleep(250);
                    load_q(uk);
                }
#pragma unroll
                for (int t = 0; t < NPART; t++) mbar_wait(kbar + t * 8, phase);
                phase ^= 1;
                PH(0); ARR();
                TSI(0, 16); TSI(1, 18);
                float acc[2][4][4] = {};
#pragma unroll
                for (int ks = 0; ks < 12; ks++) {
                    const uint4 qq = qf[ks >> 1];
                    const uint32_t b0 = (ks & 1) ? qq.z : qq.x, b1 = (ks & 1) ? qq.w : qq.y;
#pragma unroll
                    for (int mt = 0; mt < 4; mt++) {
                        uint32_t a[4];
                        ldsm4(a, (koff[ks >> 2] ^ ((ks & 3) << 5)) + mt * 6144);
                        mma16816(acc[ks & 1][mt], a, b0, b1);
                    }
                }
                PH(1);
                TSI(0, 17); TSI(1, 19);
                if (uv < NUNITS && kbar == bar) request_tile(buf, uv >= 0 ? &p.v : &p.k, uv >= 0 ? uv : uk + (wk < NSPARE ? 2 : 1) * nstatic, bar, pol);
                const float sa = sel4(j, acc[0][0][0], acc[0][1][0], acc[0][2][0], acc[0][3][0]) + sel4(j, acc[1][0][0], acc[1][1][0], acc[1][2][0], acc[1][3][0]);
                const float sc = sel4(j, acc[0][0][2], acc[0][1][2], acc[0][2][2], acc[0][3][2]) + sel4(j, acc[1][0][2], acc[1][1][2], acc[1][2][2], acc[1][3][2]);
                const uint32_t raw = pack_bf16(sa, sc);
                const float scale = -0.07216878364870322f;
                const uint32_t sk = pack_bf16(lo_f(raw) * scale, hi_f(raw) * scale);
                sq[LAG - 1] = sk;
                if (uk >= POOL0) st_relaxed(&g_st.score[uk - POOL0][lane], sk ? sk : 0x80008000u);
                int a = (int)(sk << 16), b = (int)(sk & 0xffff0000u);
                a ^= (a >> 31) & 0x7fff0000; b ^= (b >> 31) & 0x7fff0000;
                const int mx = __reduce_max_sync(0xffffffffu, max(a, b));
                if (lane == 0) st_relaxed(&g_early[uk / UPB].umax[uk % UPB], (uint32_t)mx | 1u);
            }
            if (uv < 0) {
                if (wk < NSPARE) {
                    const int d = uk < nstatic ? SM_W - SM_KV : SM_KV - SM_W;
#pragma unroll
                    for (int b = 0; b < 3; b++) koff[b] += d;
                    kbar = uk < nstatic ? bar + NWORK * NPART * 8 : bar;
                    phase = uk >= nstatic;
                }
                uk += nstatic;
                load_q(uk);
                continue;
            }
            if (uv >= NUNITS) break;
            const int bh = uv / UPB;
#pragma unroll 1
            for (int it = 0; it < SPIN_MAX; it++) {
                if (__all_sync(0xffffffffu, (mv.x & mv.y & mv.z & mv.w & 1u) && (uv < POOL0 || sv != 0) && freed == UPB)) break;
                mv = ld_relaxed_v4(&g_early[bh].umax[lane * 4]);
                if (bh >= RING && bh < RED0) freed = __uint_as_float(ld_relaxed_u32(&g_st.oacc[oidx(bh - RING, (lane & 7) * 8)].w));
                if (uv >= POOL0) sv = ld_relaxed_u32(&g_st.score[uv - POOL0][lane]);
            }
            PH(2);
            int un = NUNITS, vn = 0;
            draw(un, g_work, uk < NUNITS && lane == 0);
            uint32_t tdraw;
            asm volatile("mov.u32 %0, %%globaltimer_lo;" : "=r"(tdraw));
            draw(vn, g_work + 32, uq[0] >= POOL0 && lane == 0);
            int mx = __reduce_max_sync(0xffffffffu, max(max((int)mv.x, (int)mv.y), max((int)mv.z, (int)mv.w))) & 0xffff0000;
            mx ^= (mx >> 31) & 0x7fff0000;
            const float m = __int_as_float(mx);
            const float l2e = 1.4426950408889634f;
            const uint32_t pp = pack_bf16(exp2f((lo_f(sv) - m) * l2e), exp2f((hi_f(sv) - m) * l2e));
            uint32_t pb[8];
#pragma unroll
            for (int t = 0; t < 4; t++) {
                pb[2 * t] = __shfl_sync(0xffffffffu, pp, 8 * j + t);
                pb[2 * t + 1] = __shfl_sync(0xffffffffu, pp, 8 * j + 4 + t);
            }
            float lacc[4] = {};
            const uint32_t ones[4] = {0x3f803f80u, 0x3f803f80u, 0x3f803f80u, 0x3f803f80u};
#pragma unroll
            for (int t = 0; t < 4; t++) mma16816(lacc, ones, pb[2 * t], pb[2 * t + 1]);
            if (uv < nstatic) {
                asm volatile("bar.sync 2, %0;" :: "n"((NWORK + 2) * 32) : "memory");
                TSW(3);
            }
            const int grp = 16 * j + 4 * (g & 1) + (g >> 1);
            uint32_t mode = (bh >= RED0) + (bh >= NBH - 4);
            float tag = mode ? 1.f : (float)(bh + 1), tag2 = tag;
            void* dst = mode == 0 ? (void*)&g_ring[bh % RING][uv % UPB][grp] :
                        mode == 1 ? (void*)&g_st.oacc[oidx(bh, grp)] : (void*)&g_st.ox[uv % OREP].w[0][oidx(bh & 3, grp) * 4];
            if (mode == 2 && lane < 2) red_f2(reinterpret_cast<float*>(&g_st.lx.w[lane][(bh & 3) * 256]), lacc[0], 1.f);
            un = __shfl_sync(0xffffffffu, un, 0) + (LAG + 1) * nstatic;
            vn = __shfl_sync(0xffffffffu, vn, 0);
            if (uq[0] >= POOL0) uq[0] = POOL0 + vn;
            if (vn == FW_TICKET && lane == 0) st_relaxed(g_st.fw_time, tdraw | 1u);
            pin(dst); pin(mode); pin(tag); pin(tag2); pin(voff[0]); pin(voff[1]); pin(voff[2]);
            PH(3);
            float acc[12][4] = {};
#pragma unroll
            for (int t = 0; t < 4; t++) {
                if (t % (4 / NPART) == 0) mbar_wait(bar + t / (4 / NPART) * 8, phase);
                if (t == 4 - 4 / NPART) { PH(4); ARR(); CK(12, lds32(buf)); }
#pragma unroll
                for (int mt = 0; mt < 12; mt++) {
                    uint32_t a[4];
                    ldsm4t(a, (voff[mt >> 2] ^ ((mt & 3) << 5)) + t * 6144);
                    mma16816(acc[mt], a, pb[2 * t], pb[2 * t + 1]);
                }
            }
            phase ^= 1;
            PH(5);
            if (lane == 0) PROG(un);
            if (un < NUNITS || uq[0] < NUNITS) request_tile(buf, un < NUNITS ? &p.k : &p.v, un < NUNITS ? un : uq[0], bar, pol);
            float o[6];
#pragma unroll
            for (int e = 0; e < 6; e++) {
                const int q = e % 3, c = (e / 3) * 2;
                o[e] = sel4(j, acc[q][c], acc[3 + q][c], acc[6 + q][c], acc[9 + q][c]);
            }
            put_groups(dst, mode, o, tag, tag2);
            CK(13, 0);
            if (un < NUNITS) load_q(un);
            if (lane == 0) red_f2(&g_st.lsum[bh][0].x, lacc[0], 1.f);
            PH(6);
            if (uq[0] >= NUNITS && un >= NUNITS) break;
            uk = un;
            if (uq[0] < NUNITS) {
                const int nb = uq[0] / UPB;
                mv = ld_relaxed_v4(&g_early[nb].umax[lane * 4]);
                freed = nb >= RING && nb < RED0 ? __uint_as_float(ld_relaxed_u32(&g_st.oacc[oidx(nb - RING, (lane & 7) * 8)].w)) : UPB;
                if (uq[0] >= POOL0) sq[0] = ld_relaxed_u32(&g_st.score[uq[0] - POOL0][lane]);
            }
        }
        TSW(4 + wk);
        return;
    }

    __nv_bfloat16* xs = reinterpret_cast<__nv_bfloat16*>(smem + SM_X);
    float* red = reinterpret_cast<float*>(smem + SM_RED);
    const int frow = (lane & 7) + ((lane >> 4) << 3), fcol = (lane >> 3) & 1;
    const uint32_t f32b = sb + (frow * 2 + (fcol ^ ((frow >> 2) & 1))) * 16;
    const uint32_t f64b = sb + (frow * 4 + (fcol ^ ((frow >> 1) & 3))) * 16;
    if (cta < NQ_CTAS) {
        uint2 xr[5];
        if (warp < NB) {
#pragma unroll
            for (int i = 0; i < 5; i++) xr[i] = *reinterpret_cast<const uint2*>(p.x + warp * DM + i * 128 + lane * 4);
        }
        TS(26);
        if (warp < NB) {
            float v[20];
#pragma unroll
            for (int i = 0; i < 5; i++) {
                v[4 * i] = lo_f(xr[i].x); v[4 * i + 1] = hi_f(xr[i].x); v[4 * i + 2] = lo_f(xr[i].y); v[4 * i + 3] = hi_f(xr[i].y);
            }
            layernorm20(v);
#pragma unroll
            for (int i = 0; i < 5; i++)
                *reinterpret_cast<uint2*>(xs + warp * XPITCH + i * 128 + lane * 4) =
                    make_uint2(pack_bf16(v[4 * i], v[4 * i + 1]), pack_bf16(v[4 * i + 2], v[4 * i + 3]));
        }
        TS(27);
        aux_sync();
        mbar_wait(sb + BAR_WQ, 0);
        TS(1);
        const uint32_t xfrag = sb + SM_X + ((g & 3) * XPITCH + 2 * j) * 2;
        float acc[3][4] = {};
#pragma unroll
        for (int s = 0; s < 5; s++) {
            const int ks = warp * 5 + s;
            const uint32_t b0 = lds32(xfrag + ks * 32), b1 = lds32(xfrag + ks * 32 + 16);
            const int row = ks * 16 + frow;
#pragma unroll
            for (int mt = 0; mt < 3; mt++) {
                uint32_t a[4];
                ldsm4t(a, sb + SM_W + (row * 6 + 2 * mt + fcol) * 16);
                mma16816(acc[mt], a, b0, b1);
            }
        }
        if (j < 2) {
#pragma unroll
            for (int mt = 0; mt < 3; mt++) {
                *reinterpret_cast<float2*>(red + (warp * 48 + mt * 16 + g) * 4 + 2 * j) = make_float2(acc[mt][0], acc[mt][1]);
                *reinterpret_cast<float2*>(red + (warp * 48 + mt * 16 + 8 + g) * 4 + 2 * j) = make_float2(acc[mt][2], acc[mt][3]);
            }
        }
        aux_sync();
        if (tid < 96) {
            const int b = tid & 3, cp = tid >> 2;
            float s0 = 0.f, s1 = 0.f;
#pragma unroll
            for (int w = 0; w < 8; w++) { s0 += red[(w * 48 + 2 * cp) * 4 + b]; s1 += red[(w * 48 + 2 * cp + 1) * 4 + b]; }
            const int h = cta >> 2, d = (cta & 3) * 48 + 2 * cp;
            const int ch = d >> 3, jj = (d & 7) >> 1;
            st_relaxed(&g_early[b * NH + h].q[(ch >> 2) * 16 + jj * 4 + (ch & 3)], pack_neg(s0, s1));
        }
        TS(28);
    }
    if (warp >= 4 && warp < 4 + NSPARE) {
        uint64_t pol;
        asm volatile("createpolicy.fractional.L2::evict_first.b64 %0, 1.0;" : "=l"(pol));
        spin_ns(cta < NQ_CTAS ? SPARE_NS : WO_AT_NS + SPARE_NS);
        asm volatile("fence.proxy.async.shared::cta;" ::: "memory");
        __syncwarp();
        request_tile(sb + SM_W + (warp - 4) * TILE_BYTES, &p.k, (NWORK + warp - 4) * grid + cta, sb + BAR_KV + (NWORK + warp - 4) * (NPART * 8), pol);
    }
    fin_sync<3>();
    mbar_wait(sb + BAR_WO, 0);
    TS(7);
    uint32_t part = sb + SM_RED + (warp * 32 + 8 * j + g) * 4;

#pragma unroll 1
    for (int b = 0; b < NB; b++) {
        if (cta >= NE_CTAS) {
            uint32_t a[6][2][4];
#pragma unroll
            for (int s = 0; s < 6; s++) {
#pragma unroll
                for (int mt = 0; mt < 2; mt++) ldsm4t(a[s][mt], (f64b ^ (mt * 32)) + SM_A + (warp * 6 + s) * 1024);
            }
            const int bh = b * NH + 28 + (warp >> 1);
            const int side = near_side(sb) ^ 1;
            const void* osrc[OREP];
#pragma unroll
            for (int c = 0; c < OREP; c++)
                osrc[c] = b == NB - 1 ? (const void*)&g_st.ox[c].w[side][oidx(bh & 3, (warp & 1) * 32 + lane) * 4] : &g_st.oacc[oidx(bh, (warp & 1) * 32 + lane)];
            const void* lsrc = b == NB - 1 ? (const void*)&g_st.lx.w[side][(bh & 3) * 256] : g_st.lsum[bh];
            if (lane == 0) wait_row_o(bh, 1);
            __syncwarp();
            float2 lv;
#pragma unroll 1
            for (int it = 0; it < SPIN_MAX; it++) {
                lv = ld_relaxed_f2(lsrc);
                if (lv.y == UPB) break;
            }
            __syncwarp();
            float rl = rcp_approx(lv.x) * (b == NB - 1 ? 1.f : 1.f / OREP), full = b == NB - 1 ? UPB : UPB * OREP;
            float4 ov;
            pin(part); pin(rl); pin(full);
#pragma unroll 1
            for (int it = 0; it < SPIN_MAX; it++) {
                float4 oc[OREP];
#pragma unroll
                for (int c = 0; c < OREP; c++) oc[c] = ld_relaxed_f4(osrc[c]);
                ov = oc[0];
#pragma unroll
                for (int c = 1; c < OREP; c++) { ov.x += oc[c].x; ov.y += oc[c].y; ov.z += oc[c].z; ov.w += oc[c].w; }
                if (__all_sync(0xffffffffu, ov.w == full)) break;
            }
            CK(0, __float_as_uint(ov.x));
            if (ov.x != 1.2345f && warp == 7) TSW(14);
            const float px = __shfl_xor_sync(0xffffffffu, ov.x, 4), py = __shfl_xor_sync(0xffffffffu, ov.y, 4),
                        pz = __shfl_xor_sync(0xffffffffu, ov.z, 4);
            const uint32_t w[3] = {pack_bf16(ov.x * rl, px * rl), pack_bf16(ov.y * rl, py * rl), pack_bf16(ov.z * rl, pz * rl)};
            float acc[2][2][4] = {};
#pragma unroll
            for (int s = 0; s < 6; s++) {
                const uint32_t b0 = __shfl_sync(0xffffffffu, w[s % 3], (s / 3) * 16 + j);
                const uint32_t b1 = __shfl_sync(0xffffffffu, w[s % 3], (s / 3) * 16 + 8 + j);
#pragma unroll
                for (int mt = 0; mt < 2; mt++) mma16816(acc[mt][s & 1], a[s][mt], b0, b1);
            }
            sts32f(part, sel4(j, acc[0][0][0] + acc[0][1][0], acc[0][0][2] + acc[0][1][2], acc[1][0][0] + acc[1][1][0], acc[1][0][2] + acc[1][1][2]));
            CK(1, 0);
            fin_arrive<4>();
            fin_sync<5>();
            if (cta < NE_CTAS + 4 && tid < 56) reinterpret_cast<uint4*>(&g_early[b * NH + 28 + cta - NE_CTAS])[tid] = make_uint4(0u, 0u, 0u, 0u);
        } else {
            const int bh = b * NH + (cta >> 2);
            if (tid == 0) wait_row_o(bh, UPB);
            aux_sync();
            if (warp < 5) {
                uint32_t ob[12][2];
                load_o<4>(ob, bh, 0, j);
                float acc[2][2][4] = {};
#pragma unroll
                for (int ks = 0; ks < 12; ks++) {
#pragma unroll
                    for (int mt = 0; mt < 2; mt++) {
                        uint32_t a[4];
                        ldsm4t(a, (f64b ^ (mt * 32)) + SM_A + warp * 12288 + ks * 1024);
                        mma16816(acc[mt][ks & 1], a, ob[ks][0], ob[ks][1]);
                    }
                }
                red_f2(&g_st.attn[b][(cta & 3) * 160 + warp * 32 + 8 * j + g].x,
                       sel4(j, acc[0][0][0] + acc[0][1][0], acc[0][0][2] + acc[0][1][2], acc[1][0][0] + acc[1][1][0], acc[1][0][2] + acc[1][1][2]), 1.f);
                TS(8);
            } else if (warp > 5 && (cta & 3) == 0 && tid - 192 < 56) {
                reinterpret_cast<uint4*>(&g_early[bh])[tid - 192] = make_uint4(0u, 0u, 0u, 0u);
            }
        }
        if (b < NB - 2) continue;

        if (is_f(cta)) {
            uint32_t ga[10][2][4];
            uint4 hv[5] = {};
            const uint32_t hfrag = sb + SM_X + min(g, 4) * HPITCH + ((warp >> 1) * 80 + 4 * j) * 4;
#pragma unroll
            for (int s = 0; s < 5; s++) lds128_if(hv[s], hfrag + s * 64, b == NB - 1);
            if (b == NB - 1) mbar_wait(sb + BAR_FW + warp * 8, 0);
            if (warp == 7) TSW(10);
            CK(12, lds32(sb + SM_W));
#pragma unroll
            for (int s = 0; s < 10; s++) {
#pragma unroll
                for (int mt = 0; mt < 2; mt++) ldsm4t(ga[s][mt], (f64b ^ (mt * 32)) + SM_W + (warp * 10 + s) * 1024);
            }
            const uint32_t gpart = sb + SM_RED + (warp >> 1) * 640 + j * 256 + ((g + 2 * j) & 7) * 16 + (warp & 1) * 8;
            fin_sync<7>();
#pragma unroll
            for (int s = 0; s < 5; s++) lds128_if(hv[s], hfrag + s * 64, g == b);
            CK(4, hv[0].x);
            float acc[2][2][4] = {};
#pragma unroll
            for (int s = 0; s < 10; s++) {
#pragma unroll
                for (int mt = 0; mt < 2; mt++)
                    mma16816(acc[mt][s & 1], ga[s][mt], (s & 1) ? hv[s >> 1].z : hv[s >> 1].x, (s & 1) ? hv[s >> 1].w : hv[s >> 1].y);
            }
#pragma unroll
            for (int mt = 0; mt < 2; mt++) {
                if (j < 3) sts64f(gpart + mt * 2560, acc[mt][0][0] + acc[mt][1][0], acc[mt][0][2] + acc[mt][1][2]);
                if (j < 2) sts64f(gpart + mt * 2560 + 128, acc[mt][0][1] + acc[mt][1][1], acc[mt][0][3] + acc[mt][1][3]);
            }
            CK(5, 0);
            asm volatile("bar.arrive 4, 320;" ::: "memory");
        } else if (is_g(cta)) {
            uint32_t wb[12][4];
            if (b == NB - 1) mbar_wait(sb + BAR_FW + warp * 8, 0);
            if (warp == 7) TSW(11);
            CK(13, lds32(sb + SM_W));
#pragma unroll
            for (int s = 0; s < 12; s++) ldsm4t(wb[s], f32b + SM_W + (warp * 12 + s) * 512);
            const uint32_t* asrc = &g_st.ax[0].w[(~b & 1) * 2 + near_side(sb)][(warp * 32 + lane) * 4];
            uint32_t ypart = sb + SM_RED2 + warp * 512 + j * 128 + ((g + 2 * j) & 7) * 16;
            pin(ypart);
            fin_sync<7>();
            uint4 va[3];
#pragma unroll 1
            for (int it = 0; it < SPIN_MAX; it++) {
                uint32_t lo = 0xffffffffu;
#pragma unroll
                for (int i = 0; i < 3; i++) va[i] = ld_relaxed_v4(asrc + i * 4096);
#pragma unroll
                for (int i = 0; i < 3; i++) lo = min(min(lo, min(va[i].x, va[i].y)), min(va[i].z, va[i].w));
                if (__all_sync(0xffffffffu, lo != 0)) break;
            }
            CK(8, va[0].x);
            if (va[0].x != 0x12345 && warp == 7) TSW(15);
            float acc[4][4] = {};
#pragma unroll
            for (int s = 0; s < 12; s++) {
                const uint4 v = va[s >> 2];
                mma16816(acc[s & 3], wb[s], (s & 2) ? v.z : v.x, (s & 2) ? v.w : v.y);
            }
            float y[4];
#pragma unroll
            for (int e = 0; e < 4; e++) y[e] = j < 2 ? acc[0][e] + acc[2][e] : acc[1][e] + acc[3][e];
            sts128f(ypart, y[0], y[1], y[2], y[3]);
            CK(9, 0);
            fin_arrive<6>();
        }
    }
}

typedef CUresult (*EncodeFn)(CUtensorMap*, CUtensorMapDataType, cuuint32_t, void*, const cuuint64_t*, const cuuint64_t*,
                             const cuuint32_t*, const cuuint32_t*, CUtensorMapInterleave, CUtensorMapSwizzle,
                             CUtensorMapL2promotion, CUtensorMapFloatOOBfill);

CUtensorMap make_map(EncodeFn enc, void* ptr, uint64_t cols, uint64_t rows, uint32_t bcols, uint32_t brows,
                     CUtensorMapSwizzle sw, CUtensorMapL2promotion promo) {
    CUtensorMap m;
    const cuuint64_t dims[2] = {cols, rows};
    const cuuint64_t strides[1] = {cols * 2};
    const cuuint32_t box[2] = {bcols, brows};
    const cuuint32_t es[2] = {1, 1};
    enc(&m, CU_TENSOR_MAP_DATA_TYPE_BFLOAT16, 2, ptr, dims, strides, box, es, CU_TENSOR_MAP_INTERLEAVE_NONE, sw, promo,
        CU_TENSOR_MAP_FLOAT_OOB_FILL_NONE);
    return m;
}

}

extern "C" void kernel_launch(void* const* d_in, const int* in_sizes, int n_in, void* d_out, int out_size) {
    (void)in_sizes; (void)n_in; (void)out_size;
    static EncodeFn enc = nullptr;
    static int sms = 0;
    if (!enc) {
        cudaDriverEntryPointQueryResult qr;
        cudaGetDriverEntryPoint("cuTensorMapEncodeTiled", (void**)&enc, cudaEnableDefault, &qr);
        int dev = 0;
        cudaGetDevice(&dev);
        cudaDeviceGetAttribute(&sms, cudaDevAttrMultiProcessorCount, dev);
        cudaFuncSetAttribute(fused_decode_kernel, cudaFuncAttributeMaxDynamicSharedMemorySize, SM_TOTAL);
    }
    if (sms < NCTAS) return;
    const CUtensorMapL2promotion WPROMO = CU_TENSOR_MAP_L2_PROMOTION_L2_128B;
#define GPROMO 2
#define DPROMO 2
    Params p;
    p.k = make_map(enc, d_in[1], 64, (uint64_t)NBH * SK * 3, 64, TILE_ROWS / NPART, CU_TENSOR_MAP_SWIZZLE_128B, CU_TENSOR_MAP_L2_PROMOTION_NONE);
    p.v = make_map(enc, d_in[2], 64, (uint64_t)NBH * SK * 3, 64, TILE_ROWS / NPART, CU_TENSOR_MAP_SWIZZLE_128B, CU_TENSOR_MAP_L2_PROMOTION_NONE);
    p.wq = make_map(enc, d_in[3], NH * DH, DM, 48, 160, CU_TENSOR_MAP_SWIZZLE_NONE, WPROMO);
    p.wo = make_map(enc, d_in[4], DM, NH * DH, 32, DH, CU_TENSOR_MAP_SWIZZLE_64B, WPROMO);
    p.wg = make_map(enc, d_in[7], FF, DM, 32, 160, CU_TENSOR_MAP_SWIZZLE_64B, (CUtensorMapL2promotion)GPROMO);
    p.wu = make_map(enc, d_in[8], FF, DM, 32, 160, CU_TENSOR_MAP_SWIZZLE_64B, (CUtensorMapL2promotion)GPROMO);
    {
        const cuuint64_t dims[4] = {DM, 2, 8, FF / 16}, strides[3] = {8 * DM * 2, DM * 2, 16 * DM * 2};
        const cuuint32_t box[4] = {16, 2, 8, 12}, es[4] = {1, 1, 1, 1};
        enc(&p.wd, CU_TENSOR_MAP_DATA_TYPE_BFLOAT16, 4, d_in[9], dims, strides, box, es, CU_TENSOR_MAP_INTERLEAVE_NONE,
            CU_TENSOR_MAP_SWIZZLE_32B, (CUtensorMapL2promotion)DPROMO, CU_TENSOR_MAP_FLOAT_OOB_FILL_NONE);
    }
    p.x = (const __nv_bfloat16*)d_in[0];
    p.wr = (const __nv_bfloat16*)d_in[6];
    p.out = (__nv_bfloat16*)d_out;
    fused_decode_kernel<<<NCTAS, NTHREADS, SM_TOTAL, cudaStreamPerThread>>>(p);
}
```

```cpp
#include <cuda_runtime.h>
#include <cuda_bf16.h>
#include <cuda.h>
#include <stdint.h>

namespace {

constexpr int NB = 4, NH = 32, SK = 8192, DH = 192, DM = 640, FF = 1536;
constexpr int NBH = NB * NH;
constexpr int TILE = 64;
constexpr int UPB = SK / TILE;
constexpr int NUNITS = NBH * UPB;
constexpr int TILE_BYTES = TILE * DH * 2;
constexpr int TILE_ROWS = TILE * 3;
constexpr int NCTAS = 132;
constexpr int NQ_CTAS = 128;
constexpr int NE_CTAS = 112;
#define ROLES 1
__host__ __device__ constexpr bool is_f(int cta) { return cta < 96 && !(cta & 2); }
__host__ __device__ constexpr bool is_g(int cta) { return cta < 80 && (cta & 2); }
__host__ __device__ constexpr int ffn_slice(int cta) { return (cta >> 2) * 2 + (cta & 1); }

#define NWORK 2
#define NPART 1
#define NSPARE 1
#define SPARE_NS 0
#define LAG 2
#define NPOOL 640
#define RED0 116
#define RING 12
#define OREP 3
#define K0_DELAY_NS 1200
#define WO_AT_NS 3800
#define FW_TICKET 520
#define FW_AT_NS 2900
#define FW_GAP 320
#define FW_GAP2 200
#define FW_STAG (FW_GAP / 2)
#define HREP2 2
#define LSTAT 1
#define WQ_FENCE 0
#define TRIM 7
#define HGATE 700
#define NPROBE 24
#define SIDE_XOR 0
#define FW_MID 2300
constexpr int NAUX = 8;
constexpr int NTHREADS = (NAUX + NWORK + 2) * 32;
constexpr int SPIN_MAX = 1 << 22;

constexpr int SM_KV = 0;
constexpr int SM_A = SM_KV + NWORK * TILE_BYTES;
constexpr int SM_W = SM_A + 61440;
constexpr int SM_X = SM_W + 81920;
constexpr int XPITCH = 648;
constexpr int HPITCH = 1344;
constexpr int SM_RED = SM_X + 5 * HPITCH + 64;
constexpr int SM_RED2 = SM_RED + 8 * 48 * 4 * 4;
constexpr int SM_MISC = SM_RED2 + 4096;
constexpr int BAR_WQ = SM_MISC + 32, BAR_WO = SM_MISC + 40, SM_SIDE = SM_MISC + 48, BAR_FW = SM_MISC + 64;
constexpr int BAR_KV = BAR_FW + 64;
constexpr int SM_TOTAL = BAR_KV + 2 * NWORK * NPART * 8;
static_assert(LAG == 2 && SM_W % 1024 == 0 && NB * XPITCH * 2 <= 4 * HPITCH && SM_RED % 128 == 0, "smem layout");

struct Params {
    CUtensorMap k, v;
    CUtensorMap wq;
    CUtensorMap wo;
    CUtensorMap wg, wu;
    CUtensorMap wd;
    const __nv_bfloat16 *x, *wr;
    __nv_bfloat16* out;
};

struct Early {
    uint32_t q[96];
    uint32_t umax[UPB];
};
struct Twin { uint32_t w[4][1024]; };
constexpr int PROBE = 1024 - 32;
#define LSTRIDE 16
struct State {
    Twin ax[3];
    Twin hx;
    Twin ox[OREP];
    Twin lx;
    float4 oacc[NBH * 64];
    float2 attn[NB][DM];
    uint32_t fw_time[32];
    float2 lsum[NBH][LSTRIDE];
    uint32_t score[NPOOL][32];
};
__host__ __device__ constexpr int oidx(int row, int grp) {
    return (row >> 2) * 256 + ((row & 1) * 2 + (grp >> 5)) * 64 + (row & 2) * 16 + (grp & 31);
}
constexpr int STATE_V4 = ((sizeof(State) / 32 + NQ_CTAS - 1) / NQ_CTAS) * 2;
static_assert(sizeof(State) % 32 == 0, "State is cleared in whole sectors");
static_assert(sizeof(Early) == 56 * 16, "an Early entry is cleared by 56 threads");
struct Scratch {
    State st;
    unsigned work[64];
    unsigned cnt_z[32];
    Early early[NBH];
    alignas(4096) float4 ring[RING][UPB][64];
};
constexpr size_t PAGE = 2u << 20;
static_assert(sizeof(Scratch) <= PAGE, "scratch must fit one page");
__device__ __align__(128) unsigned char g_raw[2 * PAGE];
__device__ __forceinline__ Scratch* scratch() {
    return reinterpret_cast<Scratch*>((reinterpret_cast<uintptr_t>(g_raw) + PAGE - 1) & ~(uintptr_t)(PAGE - 1));
}
#define g_early scratch()->early
#define g_st scratch()->st
#define g_ring scratch()->ring
#define g_cnt_z scratch()->cnt_z
#define g_work scratch()->work
#define TS(i)
#define TSW(i)
#define TS2(i)
#define TSI(n, i)
#define PH(i)
#define CK(i, dep)
#define ARR()
#define PROG(u)

__device__ __forceinline__ uint32_t s2u(const void* p) { return (uint32_t)__cvta_generic_to_shared(p); }
__device__ __forceinline__ void mbar_init(uint32_t bar, int cnt) {
    asm volatile("mbarrier.init.shared::cta.b64 [%0], %1;" :: "r"(bar), "r"(cnt) : "memory");
}
__device__ __forceinline__ void mbar_expect_tx(uint32_t bar, uint32_t bytes) {
    asm volatile("mbarrier.arrive.expect_tx.shared::cta.b64 _, [%0], %1;" :: "r"(bar), "r"(bytes) : "memory");
}
__device__ __forceinline__ void mbar_wait(uint32_t bar, uint32_t parity) {
    asm volatile("{\n.reg .pred p;\n.reg .u32 n;\nmov.u32 n, 0;\nWAIT_LOOP:\n"
                 "mbarrier.try_wait.parity.shared::cta.b64 p, [%0], %1;\n"
                 "@p bra WAIT_DONE;\nadd.u32 n, n, 1;\nsetp.lt.u32 p, n, %2;\n@p bra WAIT_LOOP;\nWAIT_DONE:\n}"
                 :: "r"(bar), "r"(parity), "n"(SPIN_MAX) : "memory");
}
__device__ __forceinline__ void request_tile(uint32_t dst, const CUtensorMap* tm, int unit, uint32_t bar, uint64_t pol) {
#pragma unroll
    for (int i = 0; i < NPART; i++)
        asm volatile("{\n.reg .pred p;\nelect.sync _|p, 0xffffffff;\n"
                     "@p mbarrier.arrive.expect_tx.shared::cta.b64 _, [%2], %6;\n"
                     "@p cp.async.bulk.tensor.2d.shared::cluster.global.mbarrier::complete_tx::bytes.L2::cache_hint "
                     "[%0], [%1, {%3, %4}], [%2], %5;\n}"
                     :: "r"(dst + i * (TILE_BYTES / NPART)), "l"(tm), "r"(bar + i * 8), "r"(0), "r"(unit * TILE_ROWS + i * (TILE_ROWS / NPART)),
                        "l"(pol), "n"(TILE_BYTES / NPART) : "memory");
}
__device__ __forceinline__ void put_groups(void* dst, int mode, const float (&o)[6], float tag, float tag2) {
    asm volatile("{\n.reg .pred s, r, t;\n.reg .b128 u, v;\n.reg .b64 a, b;\n"
                 "setp.eq.s32 s|r, %1, 0;\nsetp.eq.s32 t, %1, 2;\n"
                 "@r red.relaxed.gpu.global.add.v4.f32 [%0], {%2,%3,%4,%8};\n"
                 "@t red.relaxed.gpu.global.add.v4.f32 [%0+4096], {%2,%3,%4,%8};\n"
                 "@r red.relaxed.gpu.global.add.v4.f32 [%0+128], {%5,%6,%7,%9};\n"
                 "@t red.relaxed.gpu.global.add.v4.f32 [%0+4224], {%5,%6,%7,%9};\n"
                 "mov.b64 a, {%2, %3};\nmov.b64 b, {%4, %8};\nmov.b128 u, {a, b};\n"
                 "mov.b64 a, {%5, %6};\nmov.b64 b, {%7, %9};\nmov.b128 v, {a, b};\n"
                 "@s st.relaxed.gpu.global.b128 [%0], u;\n@s st.relaxed.gpu.global.b128 [%0+128], v;\n}"
                 :: "l"(dst), "r"(mode), "f"(o[0]), "f"(o[1]), "f"(o[2]), "f"(o[3]), "f"(o[4]), "f"(o[5]), "f"(tag), "f"(tag2) : "memory");
}
__device__ __forceinline__ void request_box(uint32_t dst, const CUtensorMap* tm, int col, int row, uint32_t bar, uint32_t bytes) {
    asm volatile("{\n.reg .pred p, q;\nelect.sync _|p, 0xffffffff;\nsetp.ne.and.u32 q, %5, 0, p;\n"
                 "@q mbarrier.arrive.expect_tx.shared::cta.b64 _, [%2], %5;\n"
                 "@p cp.async.bulk.tensor.2d.shared::cluster.global.mbarrier::complete_tx::bytes [%0], [%1, {%3, %4}], [%2];\n}"
                 :: "r"(dst), "l"(tm), "r"(bar), "r"(col), "r"(row), "r"(bytes) : "memory");
}
__device__ __forceinline__ uint32_t lds32(uint32_t addr) {
    uint32_t v;
    asm volatile("ld.shared.u32 %0, [%1];" : "=r"(v) : "r"(addr) : "memory");
    return v;
}
__device__ __forceinline__ void ldsm4(uint32_t (&r)[4], uint32_t addr) {
    asm volatile("ldmatrix.sync.aligned.m8n8.x4.shared.b16 {%0,%1,%2,%3}, [%4];"
                 : "=r"(r[0]), "=r"(r[1]), "=r"(r[2]), "=r"(r[3]) : "r"(addr) : "memory");
}
__device__ __forceinline__ void ldsm4t(uint32_t (&r)[4], uint32_t addr) {
    asm volatile("ldmatrix.sync.aligned.m8n8.x4.trans.shared.b16 {%0,%1,%2,%3}, [%4];"
                 : "=r"(r[0]), "=r"(r[1]), "=r"(r[2]), "=r"(r[3]) : "r"(addr) : "memory");
}
__device__ __forceinline__ void mma16816(float (&c)[4], const uint32_t (&a)[4], uint32_t b0, uint32_t b1) {
    asm volatile("mma.sync.aligned.m16n8k16.row.col.f32.bf16.bf16.f32 {%0,%1,%2,%3}, {%4,%5,%6,%7}, {%8,%9}, {%0,%1,%2,%3};"
                 : "+f"(c[0]), "+f"(c[1]), "+f"(c[2]), "+f"(c[3])
                 : "r"(a[0]), "r"(a[1]), "r"(a[2]), "r"(a[3]), "r"(b0), "r"(b1));
}
__device__ __forceinline__ uint4 ld_relaxed_v4(const void* p) {
    uint4 v;
    asm volatile("ld.relaxed.gpu.global.v4.u32 {%0,%1,%2,%3}, [%4];" : "=r"(v.x), "=r"(v.y), "=r"(v.z), "=r"(v.w) : "l"(p) : "memory");
    return v;
}
__device__ __forceinline__ float4 ld_relaxed_f4(const void* p) {
    float4 v;
    asm volatile("ld.relaxed.gpu.global.v4.f32 {%0,%1,%2,%3}, [%4];" : "=f"(v.x), "=f"(v.y), "=f"(v.z), "=f"(v.w) : "l"(p) : "memory");
    return v;
}
__device__ __forceinline__ float2 ld_relaxed_f2(const void* p) {
    float2 v;
    asm volatile("ld.relaxed.gpu.global.v2.f32 {%0,%1}, [%2];" : "=f"(v.x), "=f"(v.y) : "l"(p) : "memory");
    return v;
}
__device__ __forceinline__ float4 ld_relaxed_b128(const void* p) {
    float4 v;
    asm volatile("{\n.reg .b128 t;\n.reg .b64 a, b;\nld.relaxed.gpu.global.b128 t, [%4];\nmov.b128 {a, b}, t;\n"
                 "mov.b64 {%0, %1}, a;\nmov.b64 {%2, %3}, b;\n}" : "=f"(v.x), "=f"(v.y), "=f"(v.z), "=f"(v.w) : "l"(p) : "memory");
    return v;
}
__device__ __forceinline__ void st_relaxed_b128(void* p, float x, float y, float z, float w) {
    asm volatile("{\n.reg .b128 t;\n.reg .b64 a, b;\nmov.b64 a, {%1, %2};\nmov.b64 b, {%3, %4};\nmov.b128 t, {a, b};\n"
                 "st.relaxed.gpu.global.b128 [%0], t;\n}" :: "l"(p), "f"(x), "f"(y), "f"(z), "f"(w) : "memory");
}
__device__ __forceinline__ unsigned ld_acquire(const unsigned* p) {
    unsigned v;
    asm volatile("ld.acquire.gpu.global.u32 %0, [%1];" : "=r"(v) : "l"(p) : "memory");
    return v;
}
__device__ __forceinline__ void st_relaxed(void* p, uint32_t v) {
    asm volatile("st.relaxed.gpu.global.u32 [%0], %1;" :: "l"(p), "r"(v) : "memory");
}
__device__ __forceinline__ void red_f2(float* p, float a, float b) {
    asm volatile("red.relaxed.gpu.global.add.v2.f32 [%0], {%1,%2};" :: "l"(p), "f"(a), "f"(b) : "memory");
}
__device__ __forceinline__ void draw(int& ticket, unsigned* ctr, bool pred) {
    asm volatile("{\n.reg .pred p;\nsetp.ne.u32 p, %2, 0;\n@p atom.relaxed.gpu.global.inc.u32 %0, [%1], 0x7fffffff;\n}"
                 : "+r"(ticket) : "l"(ctr), "r"((uint32_t)pred) : "memory");
}
__device__ __forceinline__ void red_release(unsigned* p) {
    asm volatile("red.release.gpu.global.add.u32 [%0], 1;" :: "l"(p) : "memory");
}
__device__ __forceinline__ uint32_t ld_relaxed_u32(const void* p) {
    uint32_t v;
    asm volatile("ld.relaxed.gpu.global.u32 %0, [%1];" : "=r"(v) : "l"(p) : "memory");
    return v;
}
__device__ __forceinline__ float rcp_approx(float v) {
    float r;
    asm("rcp.approx.ftz.f32 %0, %1;" : "=f"(r) : "f"(v));
    return r;
}
__device__ __forceinline__ float ex2_approx(float v) {
    float e;
    asm("ex2.approx.ftz.f32 %0, %1;" : "=f"(e) : "f"(v));
    return e;
}
__device__ __forceinline__ float sigmoid_approx(float v) { return rcp_approx(1.0f + ex2_approx(v * -1.4426950408889634f)); }
__device__ __forceinline__ float sqrt_approx(float v) {
    float r;
    asm("sqrt.approx.ftz.f32 %0, %1;" : "=f"(r) : "f"(v));
    return r;
}
__device__ __forceinline__ bool all(bool v) { return __all_sync(0xffffffffu, v); }
__device__ __forceinline__ void wait_count(const unsigned* p, unsigned target) {
#pragma unroll 1
    for (int it = 0; it < SPIN_MAX; it++) {
        if (all(ld_acquire(p) >= target)) break;
        __nanosleep(400);
    }
}
__device__ __forceinline__ float wait_sum(const void* p, float n, int nap = 0) {
    float2 v;
#pragma unroll 1
    for (int it = 0; it < SPIN_MAX; it++) {
        v = ld_relaxed_f2(p);
        if (all(v.y >= n)) break;
        if (all(v.y == 0.f)) __nanosleep(600);
        else if (nap) __nanosleep(nap);
    }
    return v.x;
}
__device__ __forceinline__ void wait_row(int bh, float n) { wait_sum(g_st.lsum[bh], n); }
__device__ __forceinline__ void wait_row_o(int bh, float n) {
    wait_row(bh, n);
    if (bh >= RED0) return;
#pragma unroll 1
    for (int it = 0; it < SPIN_MAX; it++) {
        if (all(__uint_as_float(ld_relaxed_u32(&g_st.oacc[oidx(bh, 0)].w)) == UPB)) break;
        __nanosleep(300);
    }
}
__device__ __forceinline__ void wait_clock(uint32_t t) { while (!all((int)(clock() - t) >= 0)) {} }
__device__ __forceinline__ void spin_ns(int ns) { wait_clock(clock() + ns * 2); }
__device__ __forceinline__ uint32_t pack_bf16(float lo, float hi) {
    uint32_t r;
    asm("cvt.rn.bf16x2.f32 %0, %1, %2;" : "=r"(r) : "f"(hi), "f"(lo));
    return r;
}
__device__ __forceinline__ float bf16r(float v) { return __uint_as_float(pack_bf16(0.f, v)); }
__device__ __forceinline__ uint32_t nonzero(uint32_t w) { return w ? w : 0x80008000u; }
__device__ __forceinline__ uint32_t pack_neg(float lo, float hi) { return nonzero(pack_bf16(-lo, -hi)); }
__device__ __forceinline__ float lo_f(uint32_t v) { return __uint_as_float(v << 16); }
__device__ __forceinline__ float hi_f(uint32_t v) { return __uint_as_float(v & 0xffff0000u); }
__device__ __forceinline__ float warp_sum(float v) {
#pragma unroll
    for (int o = 16; o; o >>= 1) v += __shfl_xor_sync(0xffffffffu, v, o);
    return v;
}
__device__ __forceinline__ void layernorm20(float (&v)[20]) {
    float s = 0.f;
#pragma unroll
    for (int i = 0; i < 20; i++) s += v[i];
    const float mean = warp_sum(s) * (1.0f / DM);
    float q = 0.f;
#pragma unroll
    for (int i = 0; i < 20; i++) { const float d = v[i] - mean; q += d * d; }
    const float var = bf16r(warp_sum(q) * (1.0f / DM));
    const float m = bf16r(mean);
    const float rden = 1.0f / bf16r(sqrtf(bf16r(var + 1e-5f)));
#pragma unroll
    for (int i = 0; i < 20; i++) v[i] = bf16r(bf16r(v[i] - m) * rden);
}

__device__ __forceinline__ void moments(float m1, float m2, float& nmean, float& rden) {
    m1 *= 1.0f / DM;
    const float var = bf16r(fmaxf(fmaf(-m1, m1, m2 * (1.0f / DM)), 0.f));
    nmean = bf16r(m1);
    rden = rcp_approx(bf16r(sqrt_approx(bf16r(var + 1e-5f))));
}
__device__ __forceinline__ float sel4(int j, float a, float b, float c, float d) {
    float lo, hi, r;
    asm("{\n.reg .pred p;\nsetp.ne.s32 p, %3, 0;\nselp.f32 %0, %2, %1, p;\n}" : "=f"(lo) : "f"(a), "f"(b), "r"(j & 1));
    asm("{\n.reg .pred p;\nsetp.ne.s32 p, %3, 0;\nselp.f32 %0, %2, %1, p;\n}" : "=f"(hi) : "f"(c), "f"(d), "r"(j & 1));
    asm("{\n.reg .pred p;\nsetp.ne.s32 p, %3, 0;\nselp.f32 %0, %2, %1, p;\n}" : "=f"(r) : "f"(lo), "f"(hi), "r"(j & 2));
    return r;
}
template <typename T> __device__ __forceinline__ void pin(T*& p) { asm volatile("" : "+l"(p)); }
__device__ __forceinline__ void pin(uint32_t& v) { asm volatile("" : "+r"(v)); }
__device__ __forceinline__ void pin(float& v) { asm volatile("" : "+f"(v)); }
__device__ __forceinline__ uint32_t after(uint32_t n, float v) {
    asm volatile("{\n.reg .pred p;\nsetp.eq.u32 p, %1, 0x7fc1a5a5;\n@p add.u32 %0, %0, 32;\n}" : "+r"(n) : "r"(__float_as_uint(v)));
    return n;
}
__device__ __forceinline__ float2 lds64f(uint32_t addr) {
    float2 v;
    asm volatile("ld.shared.v2.f32 {%0,%1}, [%2];" : "=f"(v.x), "=f"(v.y) : "r"(addr) : "memory");
    return v;
}
__device__ __forceinline__ void sts32f(uint32_t addr, float v) { asm volatile("st.shared.f32 [%0], %1;" :: "r"(addr), "f"(v) : "memory"); }
template <int ID> __device__ __forceinline__ void fin_arrive() { asm volatile("bar.arrive %0, 288;" :: "n"(ID) : "memory"); }
template <int ID> __device__ __forceinline__ void fin_sync() { asm volatile("bar.sync %0, 288;" :: "n"(ID) : "memory"); }
template <int ID> __device__ __forceinline__ void fin_sync(uint32_t n) { asm volatile("bar.sync %0, %1;" :: "n"(ID), "r"(n) : "memory"); }
__device__ __forceinline__ float2 sum8(uint32_t addr) {
    float2 t[8];
#pragma unroll
    for (int w = 0; w < 8; w++) t[w] = lds64f(addr + w * 128);
    return make_float2(((t[0].x + t[1].x) + (t[2].x + t[3].x)) + ((t[4].x + t[5].x) + (t[6].x + t[7].x)),
                       ((t[0].y + t[1].y) + (t[2].y + t[3].y)) + ((t[4].y + t[5].y) + (t[6].y + t[7].y)));
}
__device__ __forceinline__ float4 sum4x4(uint32_t addr, int pitch) {
    float4 t[4];
#pragma unroll
    for (int w = 0; w < 4; w++)
        asm volatile("ld.shared.v4.f32 {%0,%1,%2,%3}, [%4];" : "=f"(t[w].x), "=f"(t[w].y), "=f"(t[w].z), "=f"(t[w].w) : "r"(addr + w * pitch) : "memory");
    return make_float4((t[0].x + t[1].x) + (t[2].x + t[3].x), (t[0].y + t[1].y) + (t[2].y + t[3].y),
                       (t[0].z + t[1].z) + (t[2].z + t[3].z), (t[0].w + t[1].w) + (t[2].w + t[3].w));
}
__device__ __forceinline__ void sts64f(uint32_t addr, float x, float y) {
    asm volatile("st.shared.v2.f32 [%0], {%1,%2};" :: "r"(addr), "f"(x), "f"(y) : "memory");
}
__device__ __forceinline__ void lds128_if(uint4& v, uint32_t addr, bool pred) {
    asm volatile("{\n.reg .pred p;\nsetp.ne.u32 p, %5, 0;\n@p ld.shared.v4.u32 {%0,%1,%2,%3}, [%4];\n}"
                 : "+r"(v.x), "+r"(v.y), "+r"(v.z), "+r"(v.w) : "r"(addr), "r"((uint32_t)pred) : "memory");
}
__device__ __forceinline__ void sts128f(uint32_t addr, float x, float y, float z, float w) {
    asm volatile("st.shared.v4.f32 [%0], {%1,%2,%3,%4};" :: "r"(addr), "f"(x), "f"(y), "f"(z), "f"(w) : "memory");
}
template <int NJ>
__device__ __forceinline__ void load_o(uint32_t (&ob)[3 * NJ][2], int bh, int J0, int j) {
    float4 v[NJ][4];
    float2 l;
#pragma unroll 1
    for (int it = 0; it < SPIN_MAX; it++) {
#pragma unroll
        for (int J = 0; J < NJ; J++) {
#pragma unroll
            for (int e = 0; e < 4; e++) v[J][e] = ld_relaxed_f4(&g_st.oacc[oidx(bh, j)] + oidx(0, (J0 + J) * 16 + e * 4));
        }
        l = ld_relaxed_f2(g_st.lsum[bh]);
        bool ok = l.y == UPB;
#pragma unroll
        for (int J = 0; J < NJ; J++) {
#pragma unroll
            for (int e = 0; e < 4; e++) ok &= v[J][e].w == UPB;
        }
        if (__all_sync(0xffffffffu, ok)) break;
    }
    const float rl = __fdividef(1.0f, l.x);
#pragma unroll
    for (int J = 0; J < NJ; J++) {
        ob[3 * J][0] = pack_bf16(v[J][0].x * rl, v[J][1].x * rl);     ob[3 * J][1] = pack_bf16(v[J][2].x * rl, v[J][3].x * rl);
        ob[3 * J + 1][0] = pack_bf16(v[J][0].y * rl, v[J][1].y * rl); ob[3 * J + 1][1] = pack_bf16(v[J][2].y * rl, v[J][3].y * rl);
        ob[3 * J + 2][0] = pack_bf16(v[J][0].z * rl, v[J][1].z * rl); ob[3 * J + 2][1] = pack_bf16(v[J][2].z * rl, v[J][3].z * rl);
    }
}
__device__ __forceinline__ int near_side(uint32_t sb) {
    uint32_t v;
    asm volatile("ld.volatile.shared.u32 %0, [%1];" : "=r"(v) : "r"(sb + SM_SIDE) : "memory");
    return v;
}
__device__ __forceinline__ void poll_row(uint4& a, uint4& b, uint2& c, const void* pa, const void* pb, const void* pc, uint32_t sa, uint32_t sc,
                                         bool arrive, bool nap) {
    asm volatile("{\n.reg .pred p, q, r, s;\n.reg .u32 m, n, it;\n"
                 "setp.ne.u32 r, %15, 0;\nsetp.ne.u32 s, %16, 0;\nmov.u32 it, 0;\n"
                 "POLL:\n"
                 "ld.relaxed.gpu.global.v4.u32 {%0,%1,%2,%3}, [%10];\n"
                 "ld.relaxed.gpu.global.v4.u32 {%4,%5,%6,%7}, [%11];\n"
                 "ld.relaxed.gpu.global.v2.u32 {%8,%9}, [%12];\n"
                 "add.u32 it, it, 1;\nsetp.ge.u32 q, it, %17;\n"
                 "st.shared.v4.u32 [%13], {%0,%1,%2,%3};\n"
                 "st.shared.v4.u32 [%13+512], {%4,%5,%6,%7};\n"
                 "st.shared.v2.u32 [%14], {%8,%9};\n"
                 "min.u32 m, %0, %1;\nmin.u32 m, m, %2;\nmin.u32 n, %3, %4;\nmin.u32 n, n, %5;\nmin.u32 m, m, %6;\nmin.u32 m, m, %7;\n"
                 "min.u32 n, n, m;\nmin.u32 m, %8, %9;\nmin.u32 m, m, n;\n"
                 "setp.ne.or.u32 p, m, 0, q;\n"
                 "vote.sync.all.pred p, p, 0xffffffff;\n"
                 "and.pred q, p, r;\n"
                 "@q bar.arrive 7, 288;\n"
                 "@p bra.uni DONE;\n"
                 "@s nanosleep.u32 500;\n"
                 "bra.uni POLL;\n"
                 "DONE:\n}"
                 : "=&r"(a.x), "=&r"(a.y), "=&r"(a.z), "=&r"(a.w), "=&r"(b.x), "=&r"(b.y), "=&r"(b.z), "=&r"(b.w), "=&r"(c.x), "=&r"(c.y)
                 : "l"(pa), "l"(pb), "l"(pc), "r"(sa), "r"(sc), "r"((uint32_t)arrive), "r"((uint32_t)nap), "n"(SPIN_MAX) : "memory");
}
__device__ __forceinline__ void aux_sync() { asm volatile("bar.sync 1, 256;" ::: "memory"); }

__global__ void __launch_bounds__(NTHREADS, 1)
fused_decode_kernel(const __grid_constant__ Params p) {
    extern __shared__ __align__(1024) unsigned char smem[];
    const uint32_t sb = s2u(smem);
    const int tid = threadIdx.x, cta = blockIdx.x;
    if (tid < 32 && cta < NQ_CTAS) {
        asm volatile("{\n.reg .pred p;\nelect.sync _|p, 0xffffffff;\n"
                     "@p mbarrier.init.shared::cta.b64 [%2], 1;\n"
                     "@p fence.mbarrier_init.release.cluster;\n"
                     "@p mbarrier.arrive.expect_tx.shared::cta.b64 _, [%2], 61440;\n"
                     "@p cp.async.bulk.tensor.2d.shared::cluster.global.mbarrier::complete_tx::bytes [%0], [%1, {%3, %4}], [%2];\n"
                     "@p cp.async.bulk.tensor.2d.shared::cluster.global.mbarrier::complete_tx::bytes [%0+15360], [%1, {%3, %5}], [%2];\n"
                     "@p cp.async.bulk.tensor.2d.shared::cluster.global.mbarrier::complete_tx::bytes [%0+30720], [%1, {%3, %6}], [%2];\n"
                     "@p cp.async.bulk.tensor.2d.shared::cluster.global.mbarrier::complete_tx::bytes [%0+46080], [%1, {%3, %7}], [%2];\n}"
                     :: "r"(sb + SM_W), "l"(&p.wq), "r"(sb + BAR_WQ), "r"(cta * 48), "r"(0), "r"(160), "r"(320), "r"(480) : "memory");
    }
    const int warp = __shfl_sync(0xffffffffu, tid >> 5, 0), lane = tid & 31;
    constexpr int grid = NCTAS;
    const int g = lane >> 2, j = lane & 3;
    TS(0);
    if (tid == 160) {
        mbar_init(sb + BAR_WO, 1);
#pragma unroll
        for (int i = 0; i < 8 + 2 * NWORK * NPART; i++) mbar_init(sb + BAR_FW + i * 8, 1);
        sts32f(sb + SM_SIDE, 0.f);
        asm volatile("fence.mbarrier_init.release.cluster;" ::: "memory");
        asm volatile("fence.proxy.async.shared::cta;" ::: "memory");
    }
    __syncthreads();
    if (warp >= NAUX + NWORK) {
        const int fw = warp - (NAUX + NWORK), fi = ffn_slice(cta);
        if (fw == 0) {
            if (cta < NQ_CTAS) {
#pragma unroll
                for (int i = lane; i < STATE_V4; i += 32)
                    if (cta * STATE_V4 + i < (int)(sizeof(State) / 16)) reinterpret_cast<uint4*>(&g_st)[cta * STATE_V4 + i] = make_uint4(0u, 0u, 0u, 0u);
                __syncwarp();
                if (lane == 0) red_release(g_cnt_z);
            }
            TSW(2); wait_count(g_cnt_z, NQ_CTAS); TSW(29);
            asm volatile("bar.arrive 2, %0;" :: "n"((NWORK + 2) * 32) : "memory");
            fin_arrive<3>();
        } else {
            asm volatile("bar.sync 2, %0;" :: "n"((NWORK + 2) * 32) : "memory");
            uint32_t best[2] = {~0u, ~0u};
#pragma unroll 1
            for (int i = 0; i < NPROBE; i++) {
#pragma unroll
                for (int c = 0; c < 2; c++) {
                    uint32_t t0 = clock(), t1 = t0;
                    int v = 0;
                    draw(v, &g_st.hx.w[c][PROBE], lane == 0);
                    asm volatile("{\n.reg .pred p;\nsetp.ne.u32 p, %1, 0xffffffff;\n@p mov.u32 %0, %%clock;\n}" : "+r"(t1) : "r"(v) : "memory");
                    best[c] = min(best[c], t1 - t0);
                }
                __nanosleep(1000);
            }
            if (lane == 0) sts32f(sb + SM_SIDE, __uint_as_float((best[1] < best[0]) ^ SIDE_XOR));
        }
        int job = cta;
        auto sum_rows = [&](int row_end) {
#pragma unroll 1
            for (; job < 8 * min(row_end, RED0); job += NCTAS) {
                const int row = job >> 3, grp = (job & 7) * 8 + (lane & 7);
                wait_row(row, UPB);
                const float4* src = &g_ring[row % RING][lane >> 3][grp];
                float sx = 0.f, sy = 0.f, sz = 0.f;
#pragma unroll 1
                for (int i = 0; i < 2; i++, src += 64 * 64) {
                    float4 v[16];
#pragma unroll 1
                    for (int it = 0; it < SPIN_MAX; it++) {
                        bool ok = true;
#pragma unroll
                        for (int k = 0; k < 16; k++) v[k] = ld_relaxed_b128(src + k * 4 * 64);
#pragma unroll
                        for (int k = 0; k < 16; k++) ok &= v[k].w == (float)(row + 1);
                        if (__all_sync(0xffffffffu, ok)) break;
                    }
#pragma unroll
                    for (int k = 0; k < 16; k++) { sx += v[k].x; sy += v[k].y; sz += v[k].z; }
                }
#pragma unroll
                for (int o = 8; o < 32; o <<= 1) {
                    sx += __shfl_xor_sync(0xffffffffu, sx, o); sy += __shfl_xor_sync(0xffffffffu, sy, o); sz += __shfl_xor_sync(0xffffffffu, sz, o);
                }
                if (lane < 8) st_relaxed_b128(&g_st.oacc[oidx(row, grp)], sx, sy, sz, UPB);
            }
        };
        const int ho0 = lane / 20 * 256 + lane % 20 * 4, ho1 = (lane + 32) / 20 * 256 + (lane + 32) % 20 * 4, ho2 = 3 * 256 + 16 + 2 * lane;
        uint32_t wr[10] = {};
        float wsum = 0.f;
        if (is_g(cta) && fw == 0) {
#pragma unroll
            for (int i = 0; i < 10; i++) {
                const int w = 4 * lane + 128 * (i >> 2) + (i & 3) - (i >= 8 ? 2 * lane : 0);
                wr[i] = *reinterpret_cast<const uint32_t*>(p.wr + (w >> 4) * 32 + (w & 3) * 8 + ((w >> 1) & 6));
                wsum += lo_f(wr[i]) + hi_f(wr[i]);
            }
            wsum = warp_sum(wsum);
        }
        const int fb = lane >> 3, fg = lane & 7;
        if (fw == 0) {
#pragma unroll
            for (int i = lane; i < DM / 2; i += 32) sts32f(sb + SM_X + 4 * HPITCH + i * 4, __uint_as_float(0x3f803f80u));
        }
        float nmean = 0.f, rden = 0.f, sig = 0.f;
#pragma unroll 1
        for (int b = 0; b < NB; b++) {
            const bool ffn = b >= NB - 2;
            if (fw == 0) {
                sum_rows((b + 1) * NH);
                if (ffn) asm volatile("bar.arrive 8, 64;" ::: "memory");
            } else if (ffn) {
                asm volatile("bar.sync 8, 64;" ::: "memory");
                if (b == NB - 1) {
                    uint32_t t0 = 0, now;
#pragma unroll 1
                    for (int it = 0; it < SPIN_MAX; it++) {
                        t0 = ld_relaxed_u32(g_st.fw_time);
                        if (all(t0 != 0)) break;
                        __nanosleep(400);
                    }
                    asm volatile("fence.proxy.async.shared::cta;" ::: "memory");
#pragma unroll 1
                    for (int it = 0; it < SPIN_MAX; it++) {
                        asm volatile("mov.u32 %0, %%globaltimer_lo;" : "=r"(now));
                        if (all((int)(now - t0) >= FW_AT_NS)) break;
                    }
                    TSW(9);
                    uint32_t t = clock() + (is_f(cta) ? (fi & 1) * FW_STAG : FW_MID + (fi & 3) * (FW_GAP2 / 4));
#pragma unroll 1
                    for (int i = 0; i < 8; i++) {
                        const uint32_t bar = sb + BAR_FW + i * 8;
                        if (is_f(cta)) {
                            wait_clock(t);
                            request_box(sb + SM_W + i * 10240, (i & 1) ? &p.wu : &p.wg, fi * 32, (i >> 1) * 160, bar, 10240);
                            t += FW_GAP;
                        } else if (is_g(cta)) {
                            wait_clock(t);
                            asm volatile("{\n.reg .pred p;\nelect.sync _|p, 0xffffffff;\n"
                                         "@p mbarrier.arrive.expect_tx.shared::cta.b64 _, [%2], 6144;\n"
                                         "@p cp.async.bulk.tensor.4d.shared::cluster.global.mbarrier::complete_tx::bytes [%0], [%1, {%3, %4, %4, %5}], [%2];\n}"
                                         :: "r"(sb + SM_W + i * 6144), "l"(&p.wd), "r"(bar), "r"(fi * 16), "r"(0), "r"(i * 12) : "memory");
                            t += FW_GAP2;
                        }
                    }
                }
                if (is_f(cta)) {
                    const uint32_t* src = &g_st.hx.w[near_side(sb)][min(fb, b) * 256 + 96];
                    float4 m;
#pragma unroll 1
                    for (int it = 0; it < SPIN_MAX; it++) {
                        m = ld_relaxed_f4(src);
                        if (__all_sync(0xffffffffu, m.y + m.w == 2 * (NCTAS - NE_CTAS))) break;
                        if (b < NB - 1) __nanosleep(500);
                    }
                    moments(m.x, m.z, m.x, m.z);
                    sts64f(sb + SM_RED + 5120 + fb * 8, m.x, m.z);
                }
            }
            if (fw == 0 && cta >= NE_CTAS) {
                const int lc = cta - NE_CTAS, col = lc * 32 + 2 * (lane & 15);
                const uint32_t xv = *reinterpret_cast<const uint32_t*>(p.x + b * DM + col);
                uint32_t* dst = &(ffn ? g_st.hx.w : g_st.lx.w + 2)[lane >> 4][(b & 1) * 128 + lc / 5 * 256 + lc % 5 * 16 + (col & 6) * 2 + ((col >> 3) & 3)];
                uint32_t part = sb + SM_RED + (lane & 15) * 8;
                wait_row(b * NH + 28, 1);
                float4 early;
#pragma unroll 1
                for (int it = 0; it < SPIN_MAX; it++) {
                    early = ld_relaxed_f4(&g_st.attn[b][col]);
                    if (__all_sync(0xffffffffu, early.y == NE_CTAS / 4 && early.w == NE_CTAS / 4)) break;
                }
                if (early.x != 1.2345f && lane == 0) TS2(6);
                CK(1, __float_as_uint(early.x));
                const float x0 = -(lo_f(xv) + early.x), x1 = -(hi_f(xv) + early.z);
                fin_sync<4>(after(after(288, x0), x1));
                CK(2, lds32(sb + SM_RED));
                const float2 late = sum8(part);
                const uint32_t hv = nonzero(pack_bf16(x0 - late.x, x1 - late.y));
                st_relaxed(dst, hv);
                if (HREP2 && ffn) st_relaxed(dst + 2048, hv);
                CK(3, 0);
                float m = lane < 16 ? lo_f(hv) + hi_f(hv) : fmaf(lo_f(hv), lo_f(hv), hi_f(hv) * hi_f(hv));
#pragma unroll
                for (int o = 1; o < 16; o <<= 1) m += __shfl_xor_sync(0xffffffffu, m, o);
                if ((lane & 14) == 0) red_f2(reinterpret_cast<float*>(&g_st.hx.w[lane & 1][b * 256 + 96 + (lane >> 4) * 2]), m, 1.f);
                fin_arrive<5>();
            }
            if (fw == 0 && (is_g(cta) || is_f(cta))) {
                const uint32_t* src = &(ffn ? g_st.hx.w : g_st.lx.w + 2)[near_side(sb) ^ (HREP2 && ffn && (HREP2 == 1 ? (fi & 1) : is_g(cta)) ? 3 : 0)][(b & 1) * 128];
                const uint32_t hrow = sb + SM_X + b * HPITCH;
                wait_sum(b == NB - 1 ? (const void*)&g_st.lx.w[near_side(sb) ^ 1][3 * 256] : g_st.lsum[b * NH + NH - 1], UPB, 100);
                spin_ns(HGATE);
                uint4 h0, h1;
                uint2 h2;
                poll_row(h0, h1, h2, src + ho0, src + ho1, src + ho2, hrow + lane * 16, hrow + 1024 + lane * 8, ffn, b < NB - 1);
                CK(4, h0.x);
                if (!LSTAT || is_g(cta)) {
                const uint32_t hw[10] = {h0.x, h0.y, h0.z, h0.w, h1.x, h1.y, h1.z, h1.w, h2.x, h2.y};
                float s1[2] = {}, s2[2] = {};
#pragma unroll
                for (int i = 0; i < 10; i++) {
                    const float v0 = lo_f(hw[i]), v1 = hi_f(hw[i]);
                    s1[i & 1] += v0 + v1;
                    s2[i & 1] = fmaf(v0, v0, fmaf(v1, v1, s2[i & 1]));
                }
                float m1 = s1[0] + s1[1], m2 = s2[0] + s2[1];
#pragma unroll
                for (int o = 16; o; o >>= 1) { m1 += __shfl_xor_sync(0xffffffffu, m1, o); m2 += __shfl_xor_sync(0xffffffffu, m2, o); }
                moments(m1, m2, m1, m2);
                {
                    float rr = 0.f;
#pragma unroll
                    for (int i = 0; i < 10; i++) rr = fmaf(lo_f(hw[i]), lo_f(wr[i]), fmaf(hi_f(hw[i]), hi_f(wr[i]), rr));
                    const float sg = bf16r(sigmoid_approx(bf16r((m1 * wsum - warp_sum(rr)) * m2)));
                    if (fb == b) { nmean = m1; rden = m2; sig = sg; }
                    __syncwarp();
                    if (ffn) {
                        const int gi = fi, yj = 2 * (fb & 1) + (fb >> 1);
                        uint32_t ypart = sb + SM_RED2 + yj * 128 + ((fg + 2 * yj) & 7) * 16;
                        __nv_bfloat16* out = p.out + fb * DM + gi * 16 + fg;
                        const float2 hw2 = lds64f(sb + SM_X + fb * HPITCH + ((gi >> 1) * 16 + (fg & 6) * 2 + (gi & 1) * 2) * 4);
                        const uint32_t w0 = __float_as_uint(hw2.x), w1 = __float_as_uint(hw2.y);
                        float nh0 = (fg & 1) ? hi_f(w0) : lo_f(w0), nh1 = (fg & 1) ? hi_f(w1) : lo_f(w1);
                        float ln0 = bf16r(bf16r(nmean - nh0) * rden), ln1 = bf16r(bf16r(nmean - nh1) * rden);
                        ln0 -= nh0; ln1 -= nh1;
                        pin(ypart); pin(out);
                        fin_sync<6>(after(after(after(288, sig), ln0), ln1));
                        CK(10, lds32(ypart));
                        const float4 ya = sum4x4(ypart, 512), yb = sum4x4(ypart + 2048, 512);
                        const float4 y = make_float4(ya.x + yb.x, ya.y + yb.y, ya.z + yb.z, ya.w + yb.w);
                        const float y0 = -(((fb & 1) ? y.y : y.x) + __shfl_xor_sync(0xffffffffu, (fb & 1) ? y.x : y.y, 8));
                        const float y1 = -(((fb & 1) ? y.w : y.z) + __shfl_xor_sync(0xffffffffu, (fb & 1) ? y.z : y.w, 8));
                        const uint32_t ov = pack_bf16(fmaf(y0, sig, ln0), fmaf(y1, sig, ln1));
                        if (b == NB - 1) {
                            asm volatile("st.global.u16 [%0], %1;" :: "l"(out), "h"((unsigned short)(ov & 0xffffu)) : "memory");
                            asm volatile("st.global.u16 [%0], %1;" :: "l"(out + 8), "h"((unsigned short)(ov >> 16)) : "memory");
                        }
                        CK(11, 0);
                        if (lane == 0) TS2(13);
                    }
                }
                }
            }
            if (is_f(cta) && ffn) {
                const int ks = (2 * fi + fw) % 12;
                uint32_t* dst = &g_st.ax[ks >> 2].w[(~b & 1) * 2][((fi / 6) * 32 + ((ks & 1) * 4 + fb) * 4 + (fg & 3)) * 4 + (ks & 2) + (fg >> 2)];
                uint32_t part = sb + SM_RED + fw * 2560 + fb * 128 + ((fg + (fb & 2)) & 7) * 16;
                uint32_t psum = sb + SM_RED + fw * 2560 + 4 * 128 + ((fg + 4) & 7) * 16;
                pin(dst); pin(part); pin(psum);
                asm volatile("bar.sync 4, 320;" ::: "memory");
                CK(6, lds32(part));
                const float4 d = sum4x4(part, 640), cs = sum4x4(psum, 640);
                const float2 mo = lds64f(sb + SM_RED + 5120 + fb * 8);
                nmean = mo.x; rden = mo.y;
                const float g0 = fmaf(nmean, cs.x, -d.x), g1 = fmaf(nmean, cs.y, -d.y), ke = rden * -1.4426950408889634f, r2 = rden * rden;
                const float p0 = g0 * fmaf(-nmean, cs.z, d.z) * r2, p1 = g1 * fmaf(-nmean, cs.w, d.w) * r2;
                const uint32_t av = nonzero(pack_bf16(p0 * rcp_approx(1.0f + ex2_approx(g0 * ke)), p1 * rcp_approx(1.0f + ex2_approx(g1 * ke))));
                st_relaxed(dst, av);
                st_relaxed(dst + 1024, av);
                CK(7, 0);
            }
        }
        if (cta == 0 && tid == (NAUX + NWORK) * 32) { g_work[0] = 0; g_work[32] = 0; g_cnt_z[0] = 0; }
        return;
    }
    if (warp >= NAUX) {
        const int wk = warp - NAUX;
        const uint32_t bar = sb + BAR_KV + wk * (NPART * 8);
        const uint32_t buf = sb + SM_KV + wk * TILE_BYTES;
        uint64_t pol;
        asm volatile("createpolicy.fractional.L2::evict_first.b64 %0, 1.0;" : "=l"(pol));
        const int nstatic = NWORK * grid;
        constexpr int POOL0 = NUNITS - NPOOL;
        int uk = wk * grid + cta;
        spin_ns(K0_DELAY_NS);
        request_tile(buf, &p.k, uk, bar, pol);
        if (wk == 0) {
            spin_ns(WO_AT_NS - K0_DELAY_NS);
#pragma unroll 1
            for (int i = 0; i < (cta < NE_CTAS ? 5 : 4); i++)
                request_box(sb + SM_A + i * 12288, &p.wo, cta < NE_CTAS ? (cta & 3) * 160 + i * 32 : (cta - NE_CTAS) * 32,
                            (cta < NE_CTAS ? cta >> 2 : 28 + i) * DH, sb + BAR_WO, i ? 0 : cta < NE_CTAS ? 61440 : 49152);
        }
        uint32_t koff[3], voff[3];
        {
            const int r = lane & 7, hf = (lane >> 3) & 1;
            const int kkey = hf ? 8 + (r ^ 1) : r;
            const int vh = lane >> 4;
            const int vkey = ((r & 1) ? 8 : 0) + (vh ? (r ^ 1) : r);
#pragma unroll
            for (int b = 0; b < 3; b++) {
                const int rk = 3 * kkey + b, rv = 3 * vkey + b;
                koff[b] = buf + rk * 128 + (((lane >> 4) ^ (rk & 7)) << 4);
                voff[b] = buf + rv * 128 + ((hf ^ (rv & 7)) << 4);
            }
        }
        uint32_t phase = 0, kbar = bar;
        uint4 qf[6];
        auto load_q = [&](int u) {
            const uint32_t* q = &g_early[u / UPB].q[j * 4];
#pragma unroll
            for (int i = 0; i < 6; i++) qf[i] = ld_relaxed_v4(q + i * 16);
        };
        load_q(uk);
        int uq[LAG];
        uint32_t sq[LAG];
#pragma unroll
        for (int i = 0; i < LAG; i++) { uq[i] = -1; sq[i] = 0; }
        uint4 mv = make_uint4(0u, 0u, 0u, 0u);
        float freed = UPB;
        while (true) {
            const int uv = uq[0];
            uint32_t sv = sq[0];
#pragma unroll
            for (int i = 0; i + 1 < LAG; i++) { uq[i] = uq[i + 1]; sq[i] = sq[i + 1]; }
            uq[LAG - 1] = uk;
            if (uk < NUNITS) {
                PH(7);
#pragma unroll 1
                for (int it = 0; it < SPIN_MAX; it++) {
                    uint32_t lo = 0xffffffffu;
#pragma unroll
                    for (int i = 0; i < 6; i++) lo = min(min(lo, min(qf[i].x, qf[i].y)), min(qf[i].z, qf[i].w));
                    if (__all_sync(0xffffffffu, lo != 0)) break;
                    __nanosleep(250);
                    load_q(uk);
                }
#pragma unroll
                for (int t = 0; t < NPART; t++) mbar_wait(kbar + t * 8, phase);
                phase ^= 1;
                PH(0); ARR();
                TSI(0, 16); TSI(1, 18);
                float acc[2][4][4] = {};
#pragma unroll
                for (int ks = 0; ks < 12; ks++) {
                    const uint4 qq = qf[ks >> 1];
                    const uint32_t b0 = (ks & 1) ? qq.z : qq.x, b1 = (ks & 1) ? qq.w : qq.y;
#pragma unroll
                    for (int mt = 0; mt < 4; mt++) {
                        uint32_t a[4];
                        ldsm4(a, (koff[ks >> 2] ^ ((ks & 3) << 5)) + mt * 6144);
                        mma16816(acc[ks & 1][mt], a, b0, b1);
                    }
                }
                PH(1);
                TSI(0, 17); TSI(1, 19);
                if (uv < NUNITS && kbar == bar) request_tile(buf, uv >= 0 ? &p.v : &p.k, uv >= 0 ? uv : uk + (wk < NSPARE ? 2 : 1) * nstatic, bar, pol);
                const float sa = sel4(j, acc[0][0][0], acc[0][1][0], acc[0][2][0], acc[0][3][0]) + sel4(j, acc[1][0][0], acc[1][1][0], acc[1][2][0], acc[1][3][0]);
                const float sc = sel4(j, acc[0][0][2], acc[0][1][2], acc[0][2][2], acc[0][3][2]) + sel4(j, acc[1][0][2], acc[1][1][2], acc[1][2][2], acc[1][3][2]);
                const uint32_t raw = pack_bf16(sa, sc);
                const float scale = -0.07216878364870322f;
                const uint32_t sk = pack_bf16(lo_f(raw) * scale, hi_f(raw) * scale);
                sq[LAG - 1] = sk;
                if (uk >= POOL0) st_relaxed(&g_st.score[uk - POOL0][lane], sk ? sk : 0x80008000u);
                int a = (int)(sk << 16), b = (int)(sk & 0xffff0000u);
                a ^= (a >> 31) & 0x7fff0000; b ^= (b >> 31) & 0x7fff0000;
                const int mx = __reduce_max_sync(0xffffffffu, max(a, b));
                if (lane == 0) st_relaxed(&g_early[uk / UPB].umax[uk % UPB], (uint32_t)mx | 1u);
            }
            if (uv < 0) {
                if (wk < NSPARE) {
                    const int d = uk < nstatic ? SM_W - SM_KV : SM_KV - SM_W;
#pragma unroll
                    for (int b = 0; b < 3; b++) koff[b] += d;
                    kbar = uk < nstatic ? bar + NWORK * NPART * 8 : bar;
                    phase = uk >= nstatic;
                }
                uk += nstatic;
                load_q(uk);
                continue;
            }
            if (uv >= NUNITS) break;
            const int bh = uv / UPB;
#pragma unroll 1
            for (int it = 0; it < SPIN_MAX; it++) {
                if (__all_sync(0xffffffffu, (mv.x & mv.y & mv.z & mv.w & 1u) && (uv < POOL0 || sv != 0) && freed == UPB)) break;
                mv = ld_relaxed_v4(&g_early[bh].umax[lane * 4]);
                if (bh >= RING && bh < RED0) freed = __uint_as_float(ld_relaxed_u32(&g_st.oacc[oidx(bh - RING, (lane & 7) * 8)].w));
                if (uv >= POOL0) sv = ld_relaxed_u32(&g_st.score[uv - POOL0][lane]);
            }
            PH(2);
            int un = NUNITS, vn = 0;
            draw(un, g_work, uk < NUNITS && lane == 0);
            uint32_t tdraw;
            asm volatile("mov.u32 %0, %%globaltimer_lo;" : "=r"(tdraw));
            draw(vn, g_work + 32, uq[0] >= POOL0 && lane == 0);
            int mx = __reduce_max_sync(0xffffffffu, max(max((int)mv.x, (int)mv.y), max((int)mv.z, (int)mv.w))) & 0xffff0000;
            mx ^= (mx >> 31) & 0x7fff0000;
            const float m = __int_as_float(mx);
            const float l2e = 1.4426950408889634f;
            const uint32_t pp = pack_bf16(exp2f((lo_f(sv) - m) * l2e), exp2f((hi_f(sv) - m) * l2e));
            uint32_t pb[8];
#pragma unroll
            for (int t = 0; t < 4; t++) {
                pb[2 * t] = __shfl_sync(0xffffffffu, pp, 8 * j + t);
                pb[2 * t + 1] = __shfl_sync(0xffffffffu, pp, 8 * j + 4 + t);
            }
            float lacc[4] = {};
            const uint32_t ones[4] = {0x3f803f80u, 0x3f803f80u, 0x3f803f80u, 0x3f803f80u};
#pragma unroll
            for (int t = 0; t < 4; t++) mma16816(lacc, ones, pb[2 * t], pb[2 * t + 1]);
            if (uv < nstatic) {
                asm volatile("bar.sync 2, %0;" :: "n"((NWORK + 2) * 32) : "memory");
                TSW(3);
            }
            const int grp = 16 * j + 4 * (g & 1) + (g >> 1);
            uint32_t mode = (bh >= RED0) + (bh >= NBH - 4);
            float tag = mode ? 1.f : (float)(bh + 1), tag2 = tag;
            void* dst = mode == 0 ? (void*)&g_ring[bh % RING][uv % UPB][grp] :
                        mode == 1 ? (void*)&g_st.oacc[oidx(bh, grp)] : (void*)&g_st.ox[uv % OREP].w[0][oidx(bh & 3, grp) * 4];
            if (mode == 2 && lane < 2) red_f2(reinterpret_cast<float*>(&g_st.lx.w[lane][(bh & 3) * 256]), lacc[0], 1.f);
            un = __shfl_sync(0xffffffffu, un, 0) + (LAG + 1) * nstatic;
            vn = __shfl_sync(0xffffffffu, vn, 0);
            if (uq[0] >= POOL0) uq[0] = POOL0 + vn;
            if (vn == FW_TICKET && lane == 0) st_relaxed(g_st.fw_time, tdraw | 1u);
            pin(dst); pin(mode); pin(tag); pin(tag2); pin(voff[0]); pin(voff[1]); pin(voff[2]);
            PH(3);
            float acc[12][4] = {};
#pragma unroll
            for (int t = 0; t < 4; t++) {
                if (t % (4 / NPART) == 0) mbar_wait(bar + t / (4 / NPART) * 8, phase);
                if (t == 4 - 4 / NPART) { PH(4); ARR(); CK(12, lds32(buf)); }
#pragma unroll
                for (int mt = 0; mt < 12; mt++) {
                    uint32_t a[4];
                    ldsm4t(a, (voff[mt >> 2] ^ ((mt & 3) << 5)) + t * 6144);
                    mma16816(acc[mt], a, pb[2 * t], pb[2 * t + 1]);
                }
            }
            phase ^= 1;
            PH(5);
            if (lane == 0) PROG(un);
            if (un < NUNITS || uq[0] < NUNITS) request_tile(buf, un < NUNITS ? &p.k : &p.v, un < NUNITS ? un : uq[0], bar, pol);
            float o[6];
#pragma unroll
            for (int e = 0; e < 6; e++) {
                const int q = e % 3, c = (e / 3) * 2;
                o[e] = sel4(j, acc[q][c], acc[3 + q][c], acc[6 + q][c], acc[9 + q][c]);
            }
            put_groups(dst, mode, o, tag, tag2);
            CK(13, 0);
            if (un < NUNITS) load_q(un);
            if (lane == 0) red_f2(&g_st.lsum[bh][0].x, lacc[0], 1.f);
            PH(6);
            if (uq[0] >= NUNITS && un >= NUNITS) break;
            uk = un;
            if (uq[0] < NUNITS) {
                const int nb = uq[0] / UPB;
                mv = ld_relaxed_v4(&g_early[nb].umax[lane * 4]);
                freed = nb >= RING && nb < RED0 ? __uint_as_float(ld_relaxed_u32(&g_st.oacc[oidx(nb - RING, (lane & 7) * 8)].w)) : UPB;
                if (uq[0] >= POOL0) sq[0] = ld_relaxed_u32(&g_st.score[uq[0] - POOL0][lane]);
            }
        }
        TSW(4 + wk);
        return;
    }

    __nv_bfloat16* xs = reinterpret_cast<__nv_bfloat16*>(smem + SM_X);
    float* red = reinterpret_cast<float*>(smem + SM_RED);
    const int frow = (lane & 7) + ((lane >> 4) << 3), fcol = (lane >> 3) & 1;
    const uint32_t f32b = sb + (frow * 2 + (fcol ^ ((frow >> 2) & 1))) * 16;
    const uint32_t f64b = sb + (frow * 4 + (fcol ^ ((frow >> 1) & 3))) * 16;
    if (cta < NQ_CTAS) {
        uint2 xr[5];
        if (warp < NB) {
#pragma unroll
            for (int i = 0; i < 5; i++) xr[i] = *reinterpret_cast<const uint2*>(p.x + warp * DM + i * 128 + lane * 4);
        }
        TS(26);
        if (warp < NB) {
            float v[20];
#pragma unroll
            for (int i = 0; i < 5; i++) {
                v[4 * i] = lo_f(xr[i].x); v[4 * i + 1] = hi_f(xr[i].x); v[4 * i + 2] = lo_f(xr[i].y); v[4 * i + 3] = hi_f(xr[i].y);
            }
            layernorm20(v);
#pragma unroll
            for (int i = 0; i < 5; i++)
                *reinterpret_cast<uint2*>(xs + warp * XPITCH + i * 128 + lane * 4) =
                    make_uint2(pack_bf16(v[4 * i], v[4 * i + 1]), pack_bf16(v[4 * i + 2], v[4 * i + 3]));
        }
        TS(27);
        aux_sync();
        mbar_wait(sb + BAR_WQ, 0);
        TS(1);
        const uint32_t xfrag = sb + SM_X + ((g & 3) * XPITCH + 2 * j) * 2;
        float acc[3][4] = {};
#pragma unroll
        for (int s = 0; s < 5; s++) {
            const int ks = warp * 5 + s;
            const uint32_t b0 = lds32(xfrag + ks * 32), b1 = lds32(xfrag + ks * 32 + 16);
            const int row = ks * 16 + frow;
#pragma unroll
            for (int mt = 0; mt < 3; mt++) {
                uint32_t a[4];
                ldsm4t(a, sb + SM_W + (row * 6 + 2 * mt + fcol) * 16);
                mma16816(acc[mt], a, b0, b1);
            }
        }
        if (j < 2) {
#pragma unroll
            for (int mt = 0; mt < 3; mt++) {
                *reinterpret_cast<float2*>(red + (warp * 48 + mt * 16 + g) * 4 + 2 * j) = make_float2(acc[mt][0], acc[mt][1]);
                *reinterpret_cast<float2*>(red + (warp * 48 + mt * 16 + 8 + g) * 4 + 2 * j) = make_float2(acc[mt][2], acc[mt][3]);
            }
        }
        aux_sync();
        if (tid < 96) {
            const int b = tid & 3, cp = tid >> 2;
            float s0 = 0.f, s1 = 0.f;
#pragma unroll
            for (int w = 0; w < 8; w++) { s0 += red[(w * 48 + 2 * cp) * 4 + b]; s1 += red[(w * 48 + 2 * cp + 1) * 4 + b]; }
            const int h = cta >> 2, d = (cta & 3) * 48 + 2 * cp;
            const int ch = d >> 3, jj = (d & 7) >> 1;
            st_relaxed(&g_early[b * NH + h].q[(ch >> 2) * 16 + jj * 4 + (ch & 3)], pack_neg(s0, s1));
        }
        TS(28);
    }
    if (warp >= 4 && warp < 4 + NSPARE) {
        uint64_t pol;
        asm volatile("createpolicy.fractional.L2::evict_first.b64 %0, 1.0;" : "=l"(pol));
        spin_ns(cta < NQ_CTAS ? SPARE_NS : WO_AT_NS + SPARE_NS);
        asm volatile("fence.proxy.async.shared::cta;" ::: "memory");
        request_tile(sb + SM_W + (warp - 4) * TILE_BYTES, &p.k, (NWORK + warp - 4) * grid + cta, sb + BAR_KV + (NWORK + warp - 4) * (NPART * 8), pol);
    }
    fin_sync<3>();
    mbar_wait(sb + BAR_WO, 0);
    TS(7);
    uint32_t part = sb + SM_RED + (warp * 32 + 8 * j + g) * 4;

#pragma unroll 1
    for (int b = 0; b < NB; b++) {
        if (cta >= NE_CTAS) {
            uint32_t a[6][2][4];
#pragma unroll
            for (int s = 0; s < 6; s++) {
#pragma unroll
                for (int mt = 0; mt < 2; mt++) ldsm4t(a[s][mt], (f64b ^ (mt * 32)) + SM_A + (warp * 6 + s) * 1024);
            }
            const int bh = b * NH + 28 + (warp >> 1);
            const int side = near_side(sb) ^ 1;
            const void* osrc[OREP];
#pragma unroll
            for (int c = 0; c < OREP; c++)
                osrc[c] = b == NB - 1 ? (const void*)&g_st.ox[c].w[side][oidx(bh & 3, (warp & 1) * 32 + lane) * 4] : &g_st.oacc[oidx(bh, (warp & 1) * 32 + lane)];
            const void* lsrc = b == NB - 1 ? (const void*)&g_st.lx.w[side][(bh & 3) * 256] : g_st.lsum[bh];
            wait_row_o(bh, 1);
            const float rl = rcp_approx(wait_sum(lsrc, UPB)) * (b == NB - 1 ? 1.f : 1.f / OREP), full = b == NB - 1 ? UPB : UPB * OREP;
            float4 ov;
            float px, py, pz;
#pragma unroll 1
            for (int it = 0; it < SPIN_MAX; it++) {
                float4 oc[OREP];
#pragma unroll
                for (int c = 0; c < OREP; c++) oc[c] = ld_relaxed_f4(osrc[c]);
                ov = oc[0];
#pragma unroll
                for (int c = 1; c < OREP; c++) { ov.x += oc[c].x; ov.y += oc[c].y; ov.z += oc[c].z; ov.w += oc[c].w; }
                ov.x *= rl; ov.y *= rl; ov.z *= rl;
                px = __shfl_xor_sync(0xffffffffu, ov.x, 4); py = __shfl_xor_sync(0xffffffffu, ov.y, 4); pz = __shfl_xor_sync(0xffffffffu, ov.z, 4);
                if (all(ov.w == full)) break;
            }
            CK(0, __float_as_uint(ov.x));
            if (ov.x != 1.2345f && warp == 7) TSW(14);
            const uint32_t w[3] = {pack_bf16(ov.x, px), pack_bf16(ov.y, py), pack_bf16(ov.z, pz)};
            float acc[2][2][4] = {};
#pragma unroll
            for (int s = 0; s < 6; s++) {
                const uint32_t b0 = __shfl_sync(0xffffffffu, w[s % 3], (s / 3) * 16 + j);
                const uint32_t b1 = __shfl_sync(0xffffffffu, w[s % 3], (s / 3) * 16 + 8 + j);
#pragma unroll
                for (int mt = 0; mt < 2; mt++) mma16816(acc[mt][s & 1], a[s][mt], b0, b1);
            }
            sts32f(part, sel4(j, acc[0][0][0] + acc[0][1][0], acc[0][0][2] + acc[0][1][2], acc[1][0][0] + acc[1][1][0], acc[1][0][2] + acc[1][1][2]));
            CK(1, 0);
            fin_arrive<4>();
            fin_sync<5>();
            if (cta < NE_CTAS + 4 && tid < 56) reinterpret_cast<uint4*>(&g_early[b * NH + 28 + cta - NE_CTAS])[tid] = make_uint4(0u, 0u, 0u, 0u);
        } else {
            const int bh = b * NH + (cta >> 2);
            if (warp == 0) wait_row_o(bh, UPB);
            aux_sync();
            if (warp < 5) {
                uint32_t ob[12][2];
                load_o<4>(ob, bh, 0, j);
                float acc[2][2][4] = {};
#pragma unroll
                for (int ks = 0; ks < 12; ks++) {
#pragma unroll
                    for (int mt = 0; mt < 2; mt++) {
                        uint32_t a[4];
                        ldsm4t(a, (f64b ^ (mt * 32)) + SM_A + warp * 12288 + ks * 1024);
                        mma16816(acc[mt][ks & 1], a, ob[ks][0], ob[ks][1]);
                    }
                }
                red_f2(&g_st.attn[b][(cta & 3) * 160 + warp * 32 + 8 * j + g].x,
                       sel4(j, acc[0][0][0] + acc[0][1][0], acc[0][0][2] + acc[0][1][2], acc[1][0][0] + acc[1][1][0], acc[1][0][2] + acc[1][1][2]), 1.f);
                TS(8);
            } else if (warp > 5 && (cta & 3) == 0 && tid - 192 < 56) {
                reinterpret_cast<uint4*>(&g_early[bh])[tid - 192] = make_uint4(0u, 0u, 0u, 0u);
            }
        }
        if (b < NB - 2) continue;

        if (is_f(cta)) {
            uint32_t ga[10][2][4];
            uint4 hv[5] = {};
            const uint32_t hfrag = sb + SM_X + min(g, 4) * HPITCH + ((warp >> 1) * 80 + 4 * j) * 4;
#pragma unroll
            for (int s = 0; s < 5; s++) lds128_if(hv[s], hfrag + s * 64, b == NB - 1);
            if (b == NB - 1) mbar_wait(sb + BAR_FW + warp * 8, 0);
            if (warp == 7) TSW(10);
            CK(12, lds32(sb + SM_W));
#pragma unroll
            for (int s = 0; s < 10; s++) {
#pragma unroll
                for (int mt = 0; mt < 2; mt++) ldsm4t(ga[s][mt], (f64b ^ (mt * 32)) + SM_W + (warp * 10 + s) * 1024);
            }
            const uint32_t gpart = sb + SM_RED + (warp >> 1) * 640 + j * 256 + ((g + 2 * j) & 7) * 16 + (warp & 1) * 8;
            fin_sync<7>();
#pragma unroll
            for (int s = 0; s < 5; s++) lds128_if(hv[s], hfrag + s * 64, g == b);
            CK(4, hv[0].x);
            float acc[2][2][4] = {};
#pragma unroll
            for (int s = 0; s < 10; s++) {
#pragma unroll
                for (int mt = 0; mt < 2; mt++)
                    mma16816(acc[mt][s & 1], ga[s][mt], (s & 1) ? hv[s >> 1].z : hv[s >> 1].x, (s & 1) ? hv[s >> 1].w : hv[s >> 1].y);
            }
#pragma unroll
            for (int mt = 0; mt < 2; mt++) {
                if (j < 3) sts64f(gpart + mt * 2560, acc[mt][0][0] + acc[mt][1][0], acc[mt][0][2] + acc[mt][1][2]);
                if (j < 2) sts64f(gpart + mt * 2560 + 128, acc[mt][0][1] + acc[mt][1][1], acc[mt][0][3] + acc[mt][1][3]);
            }
            CK(5, 0);
            asm volatile("bar.arrive 4, 320;" ::: "memory");
        } else if (is_g(cta)) {
            uint32_t wb[12][4];
            if (b == NB - 1) mbar_wait(sb + BAR_FW + warp * 8, 0);
            if (warp == 7) TSW(11);
            CK(13, lds32(sb + SM_W));
#pragma unroll
            for (int s = 0; s < 12; s++) ldsm4t(wb[s], f32b + SM_W + (warp * 12 + s) * 512);
            const uint32_t* asrc = &g_st.ax[0].w[(~b & 1) * 2 + near_side(sb)][(warp * 32 + lane) * 4];
            uint32_t ypart = sb + SM_RED2 + warp * 512 + j * 128 + ((g + 2 * j) & 7) * 16;
            pin(ypart);
            fin_sync<7>();
            uint4 va[3];
#pragma unroll 1
            for (int it = 0; it < SPIN_MAX; it++) {
                uint32_t lo = 0xffffffffu;
#pragma unroll
                for (int i = 0; i < 3; i++) va[i] = ld_relaxed_v4(asrc + i * 4096);
#pragma unroll
                for (int i = 0; i < 3; i++) lo = min(min(lo, min(va[i].x, va[i].y)), min(va[i].z, va[i].w));
                if (__all_sync(0xffffffffu, lo != 0)) break;
            }
            CK(8, va[0].x);
            if (va[0].x != 0x12345 && warp == 7) TSW(15);
            float acc[4][4] = {};
#pragma unroll
            for (int s = 0; s < 12; s++) {
                const uint4 v = va[s >> 2];
                mma16816(acc[s & 3], wb[s], (s & 2) ? v.z : v.x, (s & 2) ? v.w : v.y);
            }
            float y[4];
#pragma unroll
            for (int e = 0; e < 4; e++) y[e] = j < 2 ? acc[0][e] + acc[2][e] : acc[1][e] + acc[3][e];
            sts128f(ypart, y[0], y[1], y[2], y[3]);
            CK(9, 0);
            fin_arrive<6>();
        }
    }
}

typedef CUresult (*EncodeFn)(CUtensorMap*, CUtensorMapDataType, cuuint32_t, void*, const cuuint64_t*, const cuuint64_t*,
                             const cuuint32_t*, const cuuint32_t*, CUtensorMapInterleave, CUtensorMapSwizzle,
                             CUtensorMapL2promotion, CUtensorMapFloatOOBfill);

CUtensorMap make_map(EncodeFn enc, void* ptr, uint64_t cols, uint64_t rows, uint32_t bcols, uint32_t brows,
                     CUtensorMapSwizzle sw, CUtensorMapL2promotion promo) {
    CUtensorMap m;
    const cuuint64_t dims[2] = {cols, rows};
    const cuuint64_t strides[1] = {cols * 2};
    const cuuint32_t box[2] = {bcols, brows};
    const cuuint32_t es[2] = {1, 1};
    enc(&m, CU_TENSOR_MAP_DATA_TYPE_BFLOAT16, 2, ptr, dims, strides, box, es, CU_TENSOR_MAP_INTERLEAVE_NONE, sw, promo,
        CU_TENSOR_MAP_FLOAT_OOB_FILL_NONE);
    return m;
}

}

extern "C" void kernel_launch(void* const* d_in, const int* in_sizes, int n_in, void* d_out, int out_size) {
    (void)in_sizes; (void)n_in; (void)out_size;
    static EncodeFn enc = nullptr;
    static int sms = 0;
    if (!enc) {
        cudaDriverEntryPointQueryResult qr;
        cudaGetDriverEntryPoint("cuTensorMapEncodeTiled", (void**)&enc, cudaEnableDefault, &qr);
        int dev = 0;
        cudaGetDevice(&dev);
        cudaDeviceGetAttribute(&sms, cudaDevAttrMultiProcessorCount, dev);
        cudaFuncSetAttribute(fused_decode_kernel, cudaFuncAttributeMaxDynamicSharedMemorySize, SM_TOTAL);
    }
    if (sms < NCTAS) return;
    const CUtensorMapL2promotion WPROMO = CU_TENSOR_MAP_L2_PROMOTION_L2_128B;
#define GPROMO 2
#define DPROMO 2
    Params p;
    p.k = make_map(enc, d_in[1], 64, (uint64_t)NBH * SK * 3, 64, TILE_ROWS / NPART, CU_TENSOR_MAP_SWIZZLE_128B, CU_TENSOR_MAP_L2_PROMOTION_NONE);
    p.v = make_map(enc, d_in[2], 64, (uint64_t)NBH * SK * 3, 64, TILE_ROWS / NPART, CU_TENSOR_MAP_SWIZZLE_128B, CU_TENSOR_MAP_L2_PROMOTION_NONE);
    p.wq = make_map(enc, d_in[3], NH * DH, DM, 48, 160, CU_TENSOR_MAP_SWIZZLE_NONE, WPROMO);
    p.wo = make_map(enc, d_in[4], DM, NH * DH, 32, DH, CU_TENSOR_MAP_SWIZZLE_64B, WPROMO);
    p.wg = make_map(enc, d_in[7], FF, DM, 32, 160, CU_TENSOR_MAP_SWIZZLE_64B, (CUtensorMapL2promotion)GPROMO);
    p.wu = make_map(enc, d_in[8], FF, DM, 32, 160, CU_TENSOR_MAP_SWIZZLE_64B, (CUtensorMapL2promotion)GPROMO);
    {
        const cuuint64_t dims[4] = {DM, 2, 8, FF / 16}, strides[3] = {8 * DM * 2, DM * 2, 16 * DM * 2};
        const cuuint32_t box[4] = {16, 2, 8, 12}, es[4] = {1, 1, 1, 1};
        enc(&p.wd, CU_TENSOR_MAP_DATA_TYPE_BFLOAT16, 4, d_in[9], dims, strides, box, es, CU_TENSOR_MAP_INTERLEAVE_NONE,
            CU_TENSOR_MAP_SWIZZLE_32B, (CUtensorMapL2promotion)DPROMO, CU_TENSOR_MAP_FLOAT_OOB_FILL_NONE);
    }
    p.x = (const __nv_bfloat16*)d_in[0];
    p.wr = (const __nv_bfloat16*)d_in[6];
    p.out = (__nv_bfloat16*)d_out;
    fused_decode_kernel<<<NCTAS, NTHREADS, SM_TOTAL, cudaStreamPerThread>>>(p);
}
```

```cpp
#include <cuda_runtime.h>
#include <cuda_bf16.h>
#include <cuda.h>
#include <stdint.h>

namespace {

constexpr int NB = 4, NH = 32, SK = 8192, DH = 192, DM = 640, FF = 1536;
constexpr int NBH = NB * NH;
constexpr int TILE = 64;
constexpr int UPB = SK / TILE;
constexpr int NUNITS = NBH * UPB;
constexpr int TILE_BYTES = TILE * DH * 2;
constexpr int TILE_ROWS = TILE * 3;
constexpr int NCTAS = 132;
constexpr int NQ_CTAS = 128;
constexpr int NE_CTAS = 112;
#define ROLES 1
__host__ __device__ constexpr bool is_f(int cta) { return cta < 96 && !(cta & 2); }
__host__ __device__ constexpr bool is_g(int cta) { return cta < 80 && (cta & 2); }
__host__ __device__ constexpr int ffn_slice(int cta) { return (cta >> 2) * 2 + (cta & 1); }

#define NWORK 2
#define NPART 1
#define NSPARE 1
#define SPARE_NS 0
#define LAG 2
#define NPOOL 768
#define RED0 116
#define RING 12
#define OREP 3
#define K0_DELAY_NS 1200
#define WO_AT_NS 3800
#define FW_TICKET 648
#define FW_AT_NS 3300
#define FW_GAP 280
#define FW_GAP2 160
#define FW_STAG (FW_GAP / 2)
#define HREP2 2
#define LSTAT 1
#define WQ_FENCE 0
#define TRIM 7
#define HGATE 700
#define EARLY_LOOK 1
#define ALINE 1
#define FARFIRST 1
#define GCH 6
#define NPROBE 24
#define SIDE_XOR 0
#define FW_MID 2100
constexpr int NAUX = 8;
constexpr int NTHREADS = (NAUX + NWORK + 2) * 32;
constexpr int SPIN_MAX = 1 << 22;

constexpr int SM_KV = 0;
constexpr int SM_A = SM_KV + NWORK * TILE_BYTES;
constexpr int SM_W = SM_A + 61440;
constexpr int SM_X = SM_W + 81920;
constexpr int XPITCH = 648;
constexpr int HPITCH = 1344;
constexpr int SM_RED = SM_X + 5 * HPITCH + 64;
constexpr int SM_RED2 = SM_RED + 8 * 48 * 4 * 4;
constexpr int SM_MISC = SM_RED2 + 4096;
constexpr int BAR_WQ = SM_MISC + 32, BAR_WO = SM_MISC + 40, SM_SIDE = SM_MISC + 48, BAR_H = SM_MISC + 56, BAR_FW = SM_MISC + 64;
constexpr int BAR_KV = BAR_FW + 64;
constexpr int SM_TOTAL = BAR_KV + 2 * NWORK * NPART * 8;
static_assert(LAG == 2 && SM_W % 1024 == 0 && NB * XPITCH * 2 <= 4 * HPITCH && SM_RED % 128 == 0, "smem layout");

struct Params {
    CUtensorMap k, v;
    CUtensorMap wq;
    CUtensorMap wo;
    CUtensorMap wg, wu;
    CUtensorMap wd;
    const __nv_bfloat16 *x, *wr;
    __nv_bfloat16* out;
};

struct Early {
    uint32_t q[96];
    uint32_t umax[UPB];
};
struct Twin { uint32_t w[4][1024]; };
constexpr int PROBE = 1024 - 32;
#define LSTRIDE 16
struct State {
    Twin ax[3];
    Twin hx;
    Twin ox[OREP];
    Twin lx;
    float4 oacc[NBH * 64];
    float2 attn[NB][DM];
    uint32_t fw_time[32];
    float2 lsum[NBH][LSTRIDE];
    uint32_t score[NPOOL][32];
};
__host__ __device__ constexpr int oidx(int row, int grp) {
    return (row >> 2) * 256 + ((row & 1) * 2 + (grp >> 5)) * 64 + (row & 2) * 16 + (grp & 31);
}
constexpr int STATE_V4 = ((sizeof(State) / 32 + NQ_CTAS - 1) / NQ_CTAS) * 2;
static_assert(sizeof(State) % 32 == 0, "State is cleared in whole sectors");
static_assert(sizeof(Early) == 56 * 16, "an Early entry is cleared by 56 threads");
struct Scratch {
    State st;
    unsigned work[64];
    unsigned cnt_z[32];
    Early early[NBH];
    alignas(4096) float4 ring[RING][UPB][64];
};
constexpr size_t PAGE = 2u << 20;
static_assert(sizeof(Scratch) <= PAGE, "scratch must fit one page");
__device__ __align__(128) unsigned char g_raw[2 * PAGE];
__device__ __forceinline__ Scratch* scratch() {
    return reinterpret_cast<Scratch*>((reinterpret_cast<uintptr_t>(g_raw) + PAGE - 1) & ~(uintptr_t)(PAGE - 1));
}
#define g_early scratch()->early
#define g_st scratch()->st
#define g_ring scratch()->ring
#define g_cnt_z scratch()->cnt_z
#define g_work scratch()->work
#define TS(i)
#define TSW(i)
#define TS2(i)
#define TSI(n, i)
#define PH(i)
#define CK(i, dep)
#define ARR()
#define PROG(u)

__device__ __forceinline__ uint32_t s2u(const void* p) { return (uint32_t)__cvta_generic_to_shared(p); }
__device__ __forceinline__ void mbar_init(uint32_t bar, int cnt) {
    asm volatile("mbarrier.init.shared::cta.b64 [%0], %1;" :: "r"(bar), "r"(cnt) : "memory");
}
__device__ __forceinline__ void mbar_expect_tx(uint32_t bar, uint32_t bytes) {
    asm volatile("mbarrier.arrive.expect_tx.shared::cta.b64 _, [%0], %1;" :: "r"(bar), "r"(bytes) : "memory");
}
__device__ __forceinline__ void mbar_wait(uint32_t bar, uint32_t parity) {
    asm volatile("{\n.reg .pred p;\n.reg .u32 n;\nmov.u32 n, 0;\nWAIT_LOOP:\n"
                 "mbarrier.try_wait.parity.shared::cta.b64 p, [%0], %1;\n"
                 "@p bra WAIT_DONE;\nadd.u32 n, n, 1;\nsetp.lt.u32 p, n, %2;\n@p bra WAIT_LOOP;\nWAIT_DONE:\n}"
                 :: "r"(bar), "r"(parity), "n"(SPIN_MAX) : "memory");
}
__device__ __forceinline__ void request_tile(uint32_t dst, const CUtensorMap* tm, int unit, uint32_t bar, uint64_t pol) {
#pragma unroll
    for (int i = 0; i < NPART; i++)
        asm volatile("{\n.reg .pred p;\nelect.sync _|p, 0xffffffff;\n"
                     "@p mbarrier.arrive.expect_tx.shared::cta.b64 _, [%2], %6;\n"
                     "@p cp.async.bulk.tensor.2d.shared::cluster.global.mbarrier::complete_tx::bytes.L2::cache_hint "
                     "[%0], [%1, {%3, %4}], [%2], %5;\n}"
                     :: "r"(dst + i * (TILE_BYTES / NPART)), "l"(tm), "r"(bar + i * 8), "r"(0), "r"(unit * TILE_ROWS + i * (TILE_ROWS / NPART)),
                        "l"(pol), "n"(TILE_BYTES / NPART) : "memory");
}
__device__ __forceinline__ void put_groups(void* dst, int mode, const float (&o)[6], float tag, float tag2) {
    asm volatile("{\n.reg .pred s, r, t;\n.reg .b128 u, v;\n.reg .b64 a, b;\n"
                 "setp.eq.s32 s|r, %1, 0;\nsetp.eq.s32 t, %1, 2;\n"
                 "@r red.relaxed.gpu.global.add.v4.f32 [%0], {%2,%3,%4,%8};\n"
                 "@t red.relaxed.gpu.global.add.v4.f32 [%0+4096], {%2,%3,%4,%8};\n"
                 "@r red.relaxed.gpu.global.add.v4.f32 [%0+128], {%5,%6,%7,%9};\n"
                 "@t red.relaxed.gpu.global.add.v4.f32 [%0+4224], {%5,%6,%7,%9};\n"
                 "mov.b64 a, {%2, %3};\nmov.b64 b, {%4, %8};\nmov.b128 u, {a, b};\n"
                 "mov.b64 a, {%5, %6};\nmov.b64 b, {%7, %9};\nmov.b128 v, {a, b};\n"
                 "@s st.relaxed.gpu.global.b128 [%0], u;\n@s st.relaxed.gpu.global.b128 [%0+128], v;\n}"
                 :: "l"(dst), "r"(mode), "f"(o[0]), "f"(o[1]), "f"(o[2]), "f"(o[3]), "f"(o[4]), "f"(o[5]), "f"(tag), "f"(tag2) : "memory");
}
__device__ __forceinline__ void request_box(uint32_t dst, const CUtensorMap* tm, int col, int row, uint32_t bar, uint32_t bytes) {
    asm volatile("{\n.reg .pred p, q;\nelect.sync _|p, 0xffffffff;\nsetp.ne.and.u32 q, %5, 0, p;\n"
                 "@q mbarrier.arrive.expect_tx.shared::cta.b64 _, [%2], %5;\n"
                 "@p cp.async.bulk.tensor.2d.shared::cluster.global.mbarrier::complete_tx::bytes [%0], [%1, {%3, %4}], [%2];\n}"
                 :: "r"(dst), "l"(tm), "r"(bar), "r"(col), "r"(row), "r"(bytes) : "memory");
}
__device__ __forceinline__ uint32_t lds32(uint32_t addr) {
    uint32_t v;
    asm volatile("ld.shared.u32 %0, [%1];" : "=r"(v) : "r"(addr) : "memory");
    return v;
}
__device__ __forceinline__ void ldsm4(uint32_t (&r)[4], uint32_t addr) {
    asm volatile("ldmatrix.sync.aligned.m8n8.x4.shared.b16 {%0,%1,%2,%3}, [%4];"
                 : "=r"(r[0]), "=r"(r[1]), "=r"(r[2]), "=r"(r[3]) : "r"(addr) : "memory");
}
__device__ __forceinline__ void ldsm4t(uint32_t (&r)[4], uint32_t addr) {
    asm volatile("ldmatrix.sync.aligned.m8n8.x4.trans.shared.b16 {%0,%1,%2,%3}, [%4];"
                 : "=r"(r[0]), "=r"(r[1]), "=r"(r[2]), "=r"(r[3]) : "r"(addr) : "memory");
}
__device__ __forceinline__ void mma16816(float (&c)[4], const uint32_t (&a)[4], uint32_t b0, uint32_t b1) {
    asm volatile("mma.sync.aligned.m16n8k16.row.col.f32.bf16.bf16.f32 {%0,%1,%2,%3}, {%4,%5,%6,%7}, {%8,%9}, {%0,%1,%2,%3};"
                 : "+f"(c[0]), "+f"(c[1]), "+f"(c[2]), "+f"(c[3])
                 : "r"(a[0]), "r"(a[1]), "r"(a[2]), "r"(a[3]), "r"(b0), "r"(b1));
}
__device__ __forceinline__ uint4 ld_relaxed_v4(const void* p) {
    uint4 v;
    asm volatile("ld.relaxed.gpu.global.v4.u32 {%0,%1,%2,%3}, [%4];" : "=r"(v.x), "=r"(v.y), "=r"(v.z), "=r"(v.w) : "l"(p) : "memory");
    return v;
}
__device__ __forceinline__ float4 ld_relaxed_f4(const void* p) {
    float4 v;
    asm volatile("ld.relaxed.gpu.global.v4.f32 {%0,%1,%2,%3}, [%4];" : "=f"(v.x), "=f"(v.y), "=f"(v.z), "=f"(v.w) : "l"(p) : "memory");
    return v;
}
__device__ __forceinline__ float2 ld_relaxed_f2(const void* p) {
    float2 v;
    asm volatile("ld.relaxed.gpu.global.v2.f32 {%0,%1}, [%2];" : "=f"(v.x), "=f"(v.y) : "l"(p) : "memory");
    return v;
}
__device__ __forceinline__ float4 ld_relaxed_b128(const void* p) {
    float4 v;
    asm volatile("{\n.reg .b128 t;\n.reg .b64 a, b;\nld.relaxed.gpu.global.b128 t, [%4];\nmov.b128 {a, b}, t;\n"
                 "mov.b64 {%0, %1}, a;\nmov.b64 {%2, %3}, b;\n}" : "=f"(v.x), "=f"(v.y), "=f"(v.z), "=f"(v.w) : "l"(p) : "memory");
    return v;
}
__device__ __forceinline__ void st_relaxed_b128(void* p, float x, float y, float z, float w) {
    asm volatile("{\n.reg .b128 t;\n.reg .b64 a, b;\nmov.b64 a, {%1, %2};\nmov.b64 b, {%3, %4};\nmov.b128 t, {a, b};\n"
                 "st.relaxed.gpu.global.b128 [%0], t;\n}" :: "l"(p), "f"(x), "f"(y), "f"(z), "f"(w) : "memory");
}
__device__ __forceinline__ unsigned ld_acquire(const unsigned* p) {
    unsigned v;
    asm volatile("ld.acquire.gpu.global.u32 %0, [%1];" : "=r"(v) : "l"(p) : "memory");
    return v;
}
__device__ __forceinline__ void st_relaxed(void* p, uint32_t v) {
    asm volatile("st.relaxed.gpu.global.u32 [%0], %1;" :: "l"(p), "r"(v) : "memory");
}
__device__ __forceinline__ void red_f2(float* p, float a, float b) {
    asm volatile("red.relaxed.gpu.global.add.v2.f32 [%0], {%1,%2};" :: "l"(p), "f"(a), "f"(b) : "memory");
}
__device__ __forceinline__ void draw(int& ticket, unsigned* ctr, bool pred) {
    asm volatile("{\n.reg .pred p;\nsetp.ne.u32 p, %2, 0;\n@p atom.relaxed.gpu.global.inc.u32 %0, [%1], 0x7fffffff;\n}"
                 : "+r"(ticket) : "l"(ctr), "r"((uint32_t)pred) : "memory");
}
__device__ __forceinline__ void red_release(unsigned* p) {
    asm volatile("red.release.gpu.global.add.u32 [%0], 1;" :: "l"(p) : "memory");
}
__device__ __forceinline__ uint32_t ld_relaxed_u32(const void* p) {
    uint32_t v;
    asm volatile("ld.relaxed.gpu.global.u32 %0, [%1];" : "=r"(v) : "l"(p) : "memory");
    return v;
}
__device__ __forceinline__ float rcp_approx(float v) {
    float r;
    asm("rcp.approx.ftz.f32 %0, %1;" : "=f"(r) : "f"(v));
    return r;
}
__device__ __forceinline__ float ex2_approx(float v) {
    float e;
    asm("ex2.approx.ftz.f32 %0, %1;" : "=f"(e) : "f"(v));
    return e;
}
__device__ __forceinline__ float sigmoid_approx(float v) { return rcp_approx(1.0f + ex2_approx(v * -1.4426950408889634f)); }
__device__ __forceinline__ float sqrt_approx(float v) {
    float r;
    asm("sqrt.approx.ftz.f32 %0, %1;" : "=f"(r) : "f"(v));
    return r;
}
__device__ __forceinline__ bool all(bool v) { return __all_sync(0xffffffffu, v); }
__device__ __forceinline__ void wait_count(const unsigned* p, unsigned target) {
#pragma unroll 1
    for (int it = 0; it < SPIN_MAX; it++) {
        if (all(ld_acquire(p) >= target)) break;
        __nanosleep(400);
    }
}
__device__ __forceinline__ float wait_sum(const void* p, float n, int nap = 0) {
    float2 v;
#pragma unroll 1
    for (int it = 0; it < SPIN_MAX; it++) {
        v = ld_relaxed_f2(p);
        if (all(v.y >= n)) break;
        if (all(v.y == 0.f)) __nanosleep(600);
        else if (nap) __nanosleep(nap);
    }
    return v.x;
}
__device__ __forceinline__ void wait_row(int bh, float n) { wait_sum(g_st.lsum[bh], n); }
__device__ __forceinline__ void wait_row_o(int bh, float n) {
    wait_row(bh, n);
    if (bh >= RED0) return;
#pragma unroll 1
    for (int it = 0; it < SPIN_MAX; it++) {
        if (all(__uint_as_float(ld_relaxed_u32(&g_st.oacc[oidx(bh, 0)].w)) == UPB)) break;
        __nanosleep(300);
    }
}
__device__ __forceinline__ void wait_clock(uint32_t t) { while (!all((int)(clock() - t) >= 0)) {} }
__device__ __forceinline__ void spin_ns(int ns) { wait_clock(clock() + ns * 2); }
__device__ __forceinline__ uint32_t pack_bf16(float lo, float hi) {
    uint32_t r;
    asm("cvt.rn.bf16x2.f32 %0, %1, %2;" : "=r"(r) : "f"(hi), "f"(lo));
    return r;
}
__device__ __forceinline__ float bf16r(float v) { return __uint_as_float(pack_bf16(0.f, v)); }
__device__ __forceinline__ uint32_t nonzero(uint32_t w) { return w ? w : 0x80008000u; }
__device__ __forceinline__ uint32_t pack_neg(float lo, float hi) { return nonzero(pack_bf16(-lo, -hi)); }
__device__ __forceinline__ float lo_f(uint32_t v) { return __uint_as_float(v << 16); }
__device__ __forceinline__ float hi_f(uint32_t v) { return __uint_as_float(v & 0xffff0000u); }
__device__ __forceinline__ float warp_sum(float v) {
#pragma unroll
    for (int o = 16; o; o >>= 1) v += __shfl_xor_sync(0xffffffffu, v, o);
    return v;
}
__device__ __forceinline__ void layernorm20(float (&v)[20]) {
    float s = 0.f;
#pragma unroll
    for (int i = 0; i < 20; i++) s += v[i];
    const float mean = warp_sum(s) * (1.0f / DM);
    float q = 0.f;
#pragma unroll
    for (int i = 0; i < 20; i++) { const float d = v[i] - mean; q += d * d; }
    const float var = bf16r(warp_sum(q) * (1.0f / DM));
    const float m = bf16r(mean);
    const float rden = 1.0f / bf16r(sqrtf(bf16r(var + 1e-5f)));
#pragma unroll
    for (int i = 0; i < 20; i++) v[i] = bf16r(bf16r(v[i] - m) * rden);
}

__device__ __forceinline__ void moments(float m1, float m2, float& nmean, float& rden) {
    m1 *= 1.0f / DM;
    const float var = bf16r(fmaxf(fmaf(-m1, m1, m2 * (1.0f / DM)), 0.f));
    nmean = bf16r(m1);
    rden = rcp_approx(bf16r(sqrt_approx(bf16r(var + 1e-5f))));
}
__device__ __forceinline__ float sel4(int j, float a, float b, float c, float d) {
    float lo, hi, r;
    asm("{\n.reg .pred p;\nsetp.ne.s32 p, %3, 0;\nselp.f32 %0, %2, %1, p;\n}" : "=f"(lo) : "f"(a), "f"(b), "r"(j & 1));
    asm("{\n.reg .pred p;\nsetp.ne.s32 p, %3, 0;\nselp.f32 %0, %2, %1, p;\n}" : "=f"(hi) : "f"(c), "f"(d), "r"(j & 1));
    asm("{\n.reg .pred p;\nsetp.ne.s32 p, %3, 0;\nselp.f32 %0, %2, %1, p;\n}" : "=f"(r) : "f"(lo), "f"(hi), "r"(j & 2));
    return r;
}
template <typename T> __device__ __forceinline__ void pin(T*& p) { asm volatile("" : "+l"(p)); }
__device__ __forceinline__ void pin(uint32_t& v) { asm volatile("" : "+r"(v)); }
__device__ __forceinline__ void pin(float& v) { asm volatile("" : "+f"(v)); }
__device__ __forceinline__ uint32_t after(uint32_t n, float v) {
    asm volatile("{\n.reg .pred p;\nsetp.eq.u32 p, %1, 0x7fc1a5a5;\n@p add.u32 %0, %0, 32;\n}" : "+r"(n) : "r"(__float_as_uint(v)));
    return n;
}
__device__ __forceinline__ float2 lds64f(uint32_t addr) {
    float2 v;
    asm volatile("ld.shared.v2.f32 {%0,%1}, [%2];" : "=f"(v.x), "=f"(v.y) : "r"(addr) : "memory");
    return v;
}
__device__ __forceinline__ void sts32f(uint32_t addr, float v) { asm volatile("st.shared.f32 [%0], %1;" :: "r"(addr), "f"(v) : "memory"); }
template <int ID> __device__ __forceinline__ void fin_arrive() { asm volatile("bar.arrive %0, 288;" :: "n"(ID) : "memory"); }
template <int ID> __device__ __forceinline__ void fin_sync() { asm volatile("bar.sync %0, 288;" :: "n"(ID) : "memory"); }
template <int ID> __device__ __forceinline__ void fin_sync(uint32_t n) { asm volatile("bar.sync %0, %1;" :: "n"(ID), "r"(n) : "memory"); }
__device__ __forceinline__ float2 sum8(uint32_t addr) {
    float2 t[8];
#pragma unroll
    for (int w = 0; w < 8; w++) t[w] = lds64f(addr + w * 128);
    return make_float2(((t[0].x + t[1].x) + (t[2].x + t[3].x)) + ((t[4].x + t[5].x) + (t[6].x + t[7].x)),
                       ((t[0].y + t[1].y) + (t[2].y + t[3].y)) + ((t[4].y + t[5].y) + (t[6].y + t[7].y)));
}
__device__ __forceinline__ float4 sum4x4(uint32_t addr, int pitch) {
    float4 t[4];
#pragma unroll
    for (int w = 0; w < 4; w++)
        asm volatile("ld.shared.v4.f32 {%0,%1,%2,%3}, [%4];" : "=f"(t[w].x), "=f"(t[w].y), "=f"(t[w].z), "=f"(t[w].w) : "r"(addr + w * pitch) : "memory");
    return make_float4((t[0].x + t[1].x) + (t[2].x + t[3].x), (t[0].y + t[1].y) + (t[2].y + t[3].y),
                       (t[0].z + t[1].z) + (t[2].z + t[3].z), (t[0].w + t[1].w) + (t[2].w + t[3].w));
}
__device__ __forceinline__ void sts64f(uint32_t addr, float x, float y) {
    asm volatile("st.shared.v2.f32 [%0], {%1,%2};" :: "r"(addr), "f"(x), "f"(y) : "memory");
}
__device__ __forceinline__ void lds128_if(uint4& v, uint32_t addr, bool pred) {
    asm volatile("{\n.reg .pred p;\nsetp.ne.u32 p, %5, 0;\n@p ld.shared.v4.u32 {%0,%1,%2,%3}, [%4];\n}"
                 : "+r"(v.x), "+r"(v.y), "+r"(v.z), "+r"(v.w) : "r"(addr), "r"((uint32_t)pred) : "memory");
}
__device__ __forceinline__ void sts128f(uint32_t addr, float x, float y, float z, float w) {
    asm volatile("st.shared.v4.f32 [%0], {%1,%2,%3,%4};" :: "r"(addr), "f"(x), "f"(y), "f"(z), "f"(w) : "memory");
}
template <int NJ>
__device__ __forceinline__ void load_o(uint32_t (&ob)[3 * NJ][2], int bh, int J0, int j) {
    float4 v[NJ][4];
    float2 l;
#pragma unroll 1
    for (int it = 0; it < SPIN_MAX; it++) {
#pragma unroll
        for (int J = 0; J < NJ; J++) {
#pragma unroll
            for (int e = 0; e < 4; e++) v[J][e] = ld_relaxed_f4(&g_st.oacc[oidx(bh, j)] + oidx(0, (J0 + J) * 16 + e * 4));
        }
        l = ld_relaxed_f2(g_st.lsum[bh]);
        bool ok = l.y == UPB;
#pragma unroll
        for (int J = 0; J < NJ; J++) {
#pragma unroll
            for (int e = 0; e < 4; e++) ok &= v[J][e].w == UPB;
        }
        if (__all_sync(0xffffffffu, ok)) break;
    }
    const float rl = __fdividef(1.0f, l.x);
#pragma unroll
    for (int J = 0; J < NJ; J++) {
        ob[3 * J][0] = pack_bf16(v[J][0].x * rl, v[J][1].x * rl);     ob[3 * J][1] = pack_bf16(v[J][2].x * rl, v[J][3].x * rl);
        ob[3 * J + 1][0] = pack_bf16(v[J][0].y * rl, v[J][1].y * rl); ob[3 * J + 1][1] = pack_bf16(v[J][2].y * rl, v[J][3].y * rl);
        ob[3 * J + 2][0] = pack_bf16(v[J][0].z * rl, v[J][1].z * rl); ob[3 * J + 2][1] = pack_bf16(v[J][2].z * rl, v[J][3].z * rl);
    }
}
__device__ __forceinline__ int near_side(uint32_t sb) {
    uint32_t v;
    asm volatile("ld.volatile.shared.u32 %0, [%1];" : "=r"(v) : "r"(sb + SM_SIDE) : "memory");
    return v;
}
__device__ __forceinline__ void poll_row(uint4& a, uint4& b, uint2& c, const void* pa, const void* pb, const void* pc, uint32_t sa, uint32_t sc,
                                         bool arrive, bool nap, uint32_t bar) {
    asm volatile("{\n.reg .pred p, q, r, s;\n.reg .u32 m, n, it;\n"
                 "setp.ne.u32 r, %15, 0;\nsetp.ne.u32 s, %16, 0;\nmov.u32 it, 0;\n"
                 "POLL:\n"
                 "ld.relaxed.gpu.global.v4.u32 {%0,%1,%2,%3}, [%10];\n"
                 "ld.relaxed.gpu.global.v4.u32 {%4,%5,%6,%7}, [%11];\n"
                 "ld.relaxed.gpu.global.v2.u32 {%8,%9}, [%12];\n"
                 "add.u32 it, it, 1;\nsetp.ge.u32 q, it, %17;\n"
                 "st.shared.v4.u32 [%13], {%0,%1,%2,%3};\n"
                 "st.shared.v4.u32 [%13+512], {%4,%5,%6,%7};\n"
                 "st.shared.v2.u32 [%14], {%8,%9};\n"
                 "min.u32 m, %0, %1;\nmin.u32 m, m, %2;\nmin.u32 n, %3, %4;\nmin.u32 n, n, %5;\nmin.u32 m, m, %6;\nmin.u32 m, m, %7;\n"
                 "min.u32 n, n, m;\nmin.u32 m, %8, %9;\nmin.u32 m, m, n;\n"
                 "setp.ne.or.u32 p, m, 0, q;\n"
                 "vote.sync.all.pred p, p, 0xffffffff;\n"
                 "and.pred q, p, r;\n"
                 "bar.warp.sync 0xffffffff;\n"
                 "@q mbarrier.arrive.shared::cta.b64 _, [%18];\n"
                 "@p bra.uni DONE;\n"
                 "@s nanosleep.u32 500;\n"
                 "bra.uni POLL;\n"
                 "DONE:\n}"
                 : "=&r"(a.x), "=&r"(a.y), "=&r"(a.z), "=&r"(a.w), "=&r"(b.x), "=&r"(b.y), "=&r"(b.z), "=&r"(b.w), "=&r"(c.x), "=&r"(c.y)
                 : "l"(pa), "l"(pb), "l"(pc), "r"(sa), "r"(sc), "r"((uint32_t)arrive), "r"((uint32_t)nap), "n"(SPIN_MAX), "r"(bar) : "memory");
}
__device__ __forceinline__ void aux_sync() { asm volatile("bar.sync 1, 256;" ::: "memory"); }

__global__ void __launch_bounds__(NTHREADS, 1)
fused_decode_kernel(const __grid_constant__ Params p) {
    extern __shared__ __align__(1024) unsigned char smem[];
    const uint32_t sb = s2u(smem);
    const int tid = threadIdx.x, cta = blockIdx.x;
    if (tid < 32 && cta < NQ_CTAS) {
        asm volatile("{\n.reg .pred p;\nelect.sync _|p, 0xffffffff;\n"
                     "@p mbarrier.init.shared::cta.b64 [%2], 1;\n"
                     "@p fence.mbarrier_init.release.cluster;\n"
                     "@p mbarrier.arrive.expect_tx.shared::cta.b64 _, [%2], 61440;\n"
                     "@p cp.async.bulk.tensor.2d.shared::cluster.global.mbarrier::complete_tx::bytes [%0], [%1, {%3, %4}], [%2];\n"
                     "@p cp.async.bulk.tensor.2d.shared::cluster.global.mbarrier::complete_tx::bytes [%0+15360], [%1, {%3, %5}], [%2];\n"
                     "@p cp.async.bulk.tensor.2d.shared::cluster.global.mbarrier::complete_tx::bytes [%0+30720], [%1, {%3, %6}], [%2];\n"
                     "@p cp.async.bulk.tensor.2d.shared::cluster.global.mbarrier::complete_tx::bytes [%0+46080], [%1, {%3, %7}], [%2];\n}"
                     :: "r"(sb + SM_W), "l"(&p.wq), "r"(sb + BAR_WQ), "r"(cta * 48), "r"(0), "r"(160), "r"(320), "r"(480) : "memory");
    }
    const int warp = __shfl_sync(0xffffffffu, tid >> 5, 0), lane = tid & 31;
    constexpr int grid = NCTAS;
    const int g = lane >> 2, j = lane & 3;
    TS(0);
    if (tid == 160) {
        mbar_init(sb + BAR_WO, 1);
        mbar_init(sb + BAR_H, 1);
#pragma unroll
        for (int i = 0; i < 8 + 2 * NWORK * NPART; i++) mbar_init(sb + BAR_FW + i * 8, 1);
        sts32f(sb + SM_SIDE, 0.f);
        asm volatile("fence.mbarrier_init.release.cluster;" ::: "memory");
        asm volatile("fence.proxy.async.shared::cta;" ::: "memory");
    }
    __syncthreads();
    if (warp >= NAUX + NWORK) {
        const int fw = warp - (NAUX + NWORK), fi = ffn_slice(cta);
        if (fw == 0) {
            if (cta < NQ_CTAS) {
#pragma unroll
                for (int i = lane; i < STATE_V4; i += 32)
                    if (cta * STATE_V4 + i < (int)(sizeof(State) / 16)) reinterpret_cast<uint4*>(&g_st)[cta * STATE_V4 + i] = make_uint4(0u, 0u, 0u, 0u);
                __syncwarp();
                if (lane == 0) red_release(g_cnt_z);
            }
            TSW(2); wait_count(g_cnt_z, NQ_CTAS); TSW(29);
            asm volatile("bar.arrive 2, %0;" :: "n"((NWORK + 2) * 32) : "memory");
            fin_arrive<3>();
        } else {
            asm volatile("bar.sync 2, %0;" :: "n"((NWORK + 2) * 32) : "memory");
            uint32_t best[2] = {~0u, ~0u};
#pragma unroll 1
            for (int i = 0; i < NPROBE; i++) {
#pragma unroll
                for (int c = 0; c < 2; c++) {
                    uint32_t t0 = clock(), t1 = t0;
                    int v = 0;
                    draw(v, &g_st.hx.w[c][PROBE], lane == 0);
                    asm volatile("{\n.reg .pred p;\nsetp.ne.u32 p, %1, 0xffffffff;\n@p mov.u32 %0, %%clock;\n}" : "+r"(t1) : "r"(v) : "memory");
                    best[c] = min(best[c], t1 - t0);
                }
                __nanosleep(1000);
            }
            if (lane == 0) sts32f(sb + SM_SIDE, __uint_as_float((best[1] < best[0]) ^ SIDE_XOR));
        }
        int job = cta;
        auto sum_rows = [&](int row_end) {
#pragma unroll 1
            for (; job < 8 * min(row_end, RED0); job += NCTAS) {
                const int row = job >> 3, grp = (job & 7) * 8 + (lane & 7);
                wait_row(row, UPB);
                const float4* src = &g_ring[row % RING][lane >> 3][grp];
                float sx = 0.f, sy = 0.f, sz = 0.f;
#pragma unroll 1
                for (int i = 0; i < 2; i++, src += 64 * 64) {
                    float4 v[16];
#pragma unroll 1
                    for (int it = 0; it < SPIN_MAX; it++) {
                        bool ok = true;
#pragma unroll
                        for (int k = 0; k < 16; k++) v[k] = ld_relaxed_b128(src + k * 4 * 64);
#pragma unroll
                        for (int k = 0; k < 16; k++) ok &= v[k].w == (float)(row + 1);
                        if (__all_sync(0xffffffffu, ok)) break;
                    }
#pragma unroll
                    for (int k = 0; k < 16; k++) { sx += v[k].x; sy += v[k].y; sz += v[k].z; }
                }
#pragma unroll
                for (int o = 8; o < 32; o <<= 1) {
                    sx += __shfl_xor_sync(0xffffffffu, sx, o); sy += __shfl_xor_sync(0xffffffffu, sy, o); sz += __shfl_xor_sync(0xffffffffu, sz, o);
                }
                if (lane < 8) st_relaxed_b128(&g_st.oacc[oidx(row, grp)], sx, sy, sz, UPB);
            }
        };
        const int ho0 = lane / 20 * 256 + lane % 20 * 4, ho1 = (lane + 32) / 20 * 256 + (lane + 32) % 20 * 4, ho2 = 3 * 256 + 16 + 2 * lane;
        uint32_t wr[10] = {};
        float wsum = 0.f;
        if (is_g(cta) && fw == 0) {
#pragma unroll
            for (int i = 0; i < 10; i++) {
                const int w = 4 * lane + 128 * (i >> 2) + (i & 3) - (i >= 8 ? 2 * lane : 0);
                wr[i] = *reinterpret_cast<const uint32_t*>(p.wr + (w >> 4) * 32 + (w & 3) * 8 + ((w >> 1) & 6));
                wsum += lo_f(wr[i]) + hi_f(wr[i]);
            }
            wsum = warp_sum(wsum);
        }
        const int fb = lane >> 3, fg = lane & 7;
        if (fw == 0) {
#pragma unroll
            for (int i = lane; i < DM / 2; i += 32) sts32f(sb + SM_X + 4 * HPITCH + i * 4, __uint_as_float(0x3f803f80u));
        }
        float nmean = 0.f, rden = 0.f, sig = 0.f;
#pragma unroll 1
        for (int b = 0; b < NB; b++) {
            const bool ffn = b >= NB - 2;
            if (fw == 0) {
                sum_rows((b + 1) * NH);
                if (ffn) asm volatile("bar.arrive 8, 64;" ::: "memory");
            } else if (ffn) {
                asm volatile("bar.sync 8, 64;" ::: "memory");
                if (b == NB - 1) {
                    uint32_t t0 = 0, now;
#pragma unroll 1
                    for (int it = 0; it < SPIN_MAX; it++) {
                        t0 = ld_relaxed_u32(g_st.fw_time);
                        if (all(t0 != 0)) break;
                        __nanosleep(400);
                    }
                    asm volatile("fence.proxy.async.shared::cta;" ::: "memory");
#pragma unroll 1
                    for (int it = 0; it < SPIN_MAX; it++) {
                        asm volatile("mov.u32 %0, %%globaltimer_lo;" : "=r"(now));
                        if (all((int)(now - t0) >= FW_AT_NS)) break;
                    }
                    TSW(9);
                    uint32_t t = clock() + (is_f(cta) ? (fi & 1) * FW_STAG : FW_MID + (fi & 3) * (FW_GAP2 / 4));
#pragma unroll 1
                    for (int i = 0; i < 8; i++) {
                        const uint32_t bar = sb + BAR_FW + i * 8;
                        if (is_f(cta)) {
                            wait_clock(t);
                            request_box(sb + SM_W + i * 10240, (i & 1) ? &p.wu : &p.wg, fi * 32, (i >> 1) * 160, bar, 10240);
                            t += FW_GAP;
                        } else if (is_g(cta)) {
                            wait_clock(t);
                            asm volatile("{\n.reg .pred p;\nelect.sync _|p, 0xffffffff;\n"
                                         "@p mbarrier.arrive.expect_tx.shared::cta.b64 _, [%2], 6144;\n"
                                         "@p cp.async.bulk.tensor.4d.shared::cluster.global.mbarrier::complete_tx::bytes [%0], [%1, {%3, %4, %4, %5}], [%2];\n}"
                                         :: "r"(sb + SM_W + i * 6144), "l"(&p.wd), "r"(bar), "r"(fi * 16), "r"(0), "r"(i * 12) : "memory");
                            t += FW_GAP2;
                        }
                    }
                }
                if (is_f(cta)) {
                    const uint32_t* src = &g_st.hx.w[near_side(sb)][min(fb, b) * 256 + 96];
                    float4 m;
#pragma unroll 1
                    for (int it = 0; it < SPIN_MAX; it++) {
                        m = ld_relaxed_f4(src);
                        if (__all_sync(0xffffffffu, m.y + m.w == 2 * (NCTAS - NE_CTAS))) break;
                        if (b < NB - 1) __nanosleep(500);
                    }
                    moments(m.x, m.z, m.x, m.z);
                    sts64f(sb + SM_RED + 5120 + fb * 8, m.x, m.z);
                }
            }
            if (fw == 0 && cta >= NE_CTAS) {
                const int lc = cta - NE_CTAS, col = lc * 32 + 2 * (lane & 15);
                const uint32_t xv = *reinterpret_cast<const uint32_t*>(p.x + b * DM + col);
                uint32_t* dst = &(ffn ? g_st.hx.w : g_st.lx.w + 2)[lane >> 4][(b & 1) * 128 + lc / 5 * 256 + lc % 5 * 16 + (col & 6) * 2 + ((col >> 3) & 3)];
                uint32_t part = sb + SM_RED + (lane & 15) * 8;
                wait_row(b * NH + 28, 1);
                float4 early;
#pragma unroll 1
                for (int it = 0; it < SPIN_MAX; it++) {
                    early = ld_relaxed_f4(&g_st.attn[b][col]);
                    if (__all_sync(0xffffffffu, early.y == NE_CTAS / 4 && early.w == NE_CTAS / 4)) break;
                }
                if (early.x != 1.2345f && lane == 0) TS2(6);
                CK(1, __float_as_uint(early.x));
                const float x0 = -(lo_f(xv) + early.x), x1 = -(hi_f(xv) + early.z);
                fin_sync<4>(after(after(288, x0), x1));
                CK(2, lds32(sb + SM_RED));
                const float2 late = sum8(part);
                const uint32_t hv = nonzero(pack_bf16(x0 - late.x, x1 - late.y));
                st_relaxed(dst, hv);
                if (HREP2 && ffn) st_relaxed(dst + 2048, hv);
                CK(3, 0);
                float m = lane < 16 ? lo_f(hv) + hi_f(hv) : fmaf(lo_f(hv), lo_f(hv), hi_f(hv) * hi_f(hv));
#pragma unroll
                for (int o = 1; o < 16; o <<= 1) m += __shfl_xor_sync(0xffffffffu, m, o);
                if ((lane & 14) == 0) red_f2(reinterpret_cast<float*>(&g_st.hx.w[lane & 1][b * 256 + 96 + (lane >> 4) * 2]), m, 1.f);
                fin_arrive<5>();
            }
            if (fw == 0 && (is_g(cta) || is_f(cta))) {
                const uint32_t* src = &(ffn ? g_st.hx.w : g_st.lx.w + 2)[near_side(sb) ^ (HREP2 && ffn && (HREP2 == 1 ? (fi & 1) : is_g(cta)) ? 3 : 0)][(b & 1) * 128];
                const uint32_t hrow = sb + SM_X + b * HPITCH;
                wait_sum(b == NB - 1 ? (const void*)&g_st.lx.w[near_side(sb) ^ 1][3 * 256] : g_st.lsum[b * NH + NH - 1], UPB, 100);
                spin_ns(HGATE);
                uint4 h0, h1;
                uint2 h2;
                poll_row(h0, h1, h2, src + ho0, src + ho1, src + ho2, hrow + lane * 16, hrow + 1024 + lane * 8, ffn && lane == 0, b < NB - 1, sb + BAR_H);
                CK(4, h0.x);
                if (!LSTAT || is_g(cta)) {
                const uint32_t hw[10] = {h0.x, h0.y, h0.z, h0.w, h1.x, h1.y, h1.z, h1.w, h2.x, h2.y};
                float s1[2] = {}, s2[2] = {};
#pragma unroll
                for (int i = 0; i < 10; i++) {
                    const float v0 = lo_f(hw[i]), v1 = hi_f(hw[i]);
                    s1[i & 1] += v0 + v1;
                    s2[i & 1] = fmaf(v0, v0, fmaf(v1, v1, s2[i & 1]));
                }
                float m1 = s1[0] + s1[1], m2 = s2[0] + s2[1];
#pragma unroll
                for (int o = 16; o; o >>= 1) { m1 += __shfl_xor_sync(0xffffffffu, m1, o); m2 += __shfl_xor_sync(0xffffffffu, m2, o); }
                moments(m1, m2, m1, m2);
                {
                    float rr = 0.f;
#pragma unroll
                    for (int i = 0; i < 10; i++) rr = fmaf(lo_f(hw[i]), lo_f(wr[i]), fmaf(hi_f(hw[i]), hi_f(wr[i]), rr));
                    const float sg = bf16r(sigmoid_approx(bf16r((m1 * wsum - warp_sum(rr)) * m2)));
                    if (fb == b) { nmean = m1; rden = m2; sig = sg; }
                    __syncwarp();
                    if (ffn) {
                        const int gi = fi, yj = 2 * (fb & 1) + (fb >> 1);
                        uint32_t ypart = sb + SM_RED2 + yj * 128 + ((fg + 2 * yj) & 7) * 16;
                        __nv_bfloat16* out = p.out + fb * DM + gi * 16 + fg;
                        const float2 hw2 = lds64f(sb + SM_X + fb * HPITCH + ((gi >> 1) * 16 + (fg & 6) * 2 + (gi & 1) * 2) * 4);
                        const uint32_t w0 = __float_as_uint(hw2.x), w1 = __float_as_uint(hw2.y);
                        float nh0 = (fg & 1) ? hi_f(w0) : lo_f(w0), nh1 = (fg & 1) ? hi_f(w1) : lo_f(w1);
                        float ln0 = bf16r(bf16r(nmean - nh0) * rden), ln1 = bf16r(bf16r(nmean - nh1) * rden);
                        ln0 -= nh0; ln1 -= nh1;
                        pin(ypart); pin(out);
                        fin_sync<6>(after(after(after(288, sig), ln0), ln1));
                        CK(10, lds32(ypart));
                        const float4 ya = sum4x4(ypart, 512), yb = sum4x4(ypart + 2048, 512);
                        const float4 y = make_float4(ya.x + yb.x, ya.y + yb.y, ya.z + yb.z, ya.w + yb.w);
                        const float y0 = -(((fb & 1) ? y.y : y.x) + __shfl_xor_sync(0xffffffffu, (fb & 1) ? y.x : y.y, 8));
                        const float y1 = -(((fb & 1) ? y.w : y.z) + __shfl_xor_sync(0xffffffffu, (fb & 1) ? y.z : y.w, 8));
                        const uint32_t ov = pack_bf16(fmaf(y0, sig, ln0), fmaf(y1, sig, ln1));
                        if (b == NB - 1) {
                            asm volatile("st.global.u16 [%0], %1;" :: "l"(out), "h"((unsigned short)(ov & 0xffffu)) : "memory");
                            asm volatile("st.global.u16 [%0], %1;" :: "l"(out + 8), "h"((unsigned short)(ov >> 16)) : "memory");
                        }
                        CK(11, 0);
                        if (lane == 0) TS2(13);
                    }
                }
                }
            }
            if (is_f(cta) && ffn) {
                const int ks = (2 * fi + fw) % 12;
                const int far = FARFIRST ? near_side(sb) ^ 1 : 0;
                uint32_t* dst = &g_st.ax[ks >> 2].w[(~b & 1) * 2 + far][ALINE ? (fi / 6) * 128 + (ks & 3) * 32 + fb * 8 + (fg & 1) * 4 + ((fg >> 1) ^ (ks & 1)) :
                                                                        ((fi / 6) * 32 + ((ks & 1) * 4 + fb) * 4 + (fg & 3)) * 4 + (ks & 2) + (fg >> 2)];
                uint32_t* dst2 = dst + (far ? -1024 : 1024);
                uint32_t part = sb + SM_RED + fw * 2560 + fb * 128 + ((fg + (fb & 2)) & 7) * 16;
                uint32_t psum = sb + SM_RED + fw * 2560 + 4 * 128 + ((fg + 4) & 7) * 16;
                pin(dst); pin(part); pin(psum);
                asm volatile("bar.sync 4, 320;" ::: "memory");
                CK(6, lds32(part));
                const float4 d = sum4x4(part, 640), cs = sum4x4(psum, 640);
                const float2 mo = lds64f(sb + SM_RED + 5120 + fb * 8);
                nmean = mo.x; rden = mo.y;
                const float g0 = fmaf(nmean, cs.x, -d.x), g1 = fmaf(nmean, cs.y, -d.y), ke = rden * -1.4426950408889634f, r2 = rden * rden;
                const float p0 = g0 * fmaf(-nmean, cs.z, d.z) * r2, p1 = g1 * fmaf(-nmean, cs.w, d.w) * r2;
                const uint32_t av = nonzero(pack_bf16(p0 * rcp_approx(1.0f + ex2_approx(g0 * ke)), p1 * rcp_approx(1.0f + ex2_approx(g1 * ke))));
                st_relaxed(dst, av);
                st_relaxed(dst2, av);
                CK(7, 0);
            }
        }
        if (cta == 0 && tid == (NAUX + NWORK) * 32) { g_work[0] = 0; g_work[32] = 0; g_cnt_z[0] = 0; }
        return;
    }
    if (warp >= NAUX) {
        const int wk = warp - NAUX;
        const uint32_t bar = sb + BAR_KV + wk * (NPART * 8);
        const uint32_t buf = sb + SM_KV + wk * TILE_BYTES;
        uint64_t pol;
        asm volatile("createpolicy.fractional.L2::evict_first.b64 %0, 1.0;" : "=l"(pol));
        const int nstatic = NWORK * grid;
        constexpr int POOL0 = NUNITS - NPOOL;
        int uk = wk * grid + cta;
        spin_ns(K0_DELAY_NS);
        request_tile(buf, &p.k, uk, bar, pol);
        if (wk == 0) {
            spin_ns(WO_AT_NS - K0_DELAY_NS);
#pragma unroll 1
            for (int i = 0; i < (cta < NE_CTAS ? 5 : 4); i++)
                request_box(sb + SM_A + i * 12288, &p.wo, cta < NE_CTAS ? (cta & 3) * 160 + i * 32 : (cta - NE_CTAS) * 32,
                            (cta < NE_CTAS ? cta >> 2 : 28 + i) * DH, sb + BAR_WO, i ? 0 : cta < NE_CTAS ? 61440 : 49152);
        }
        uint32_t koff[3], voff[3];
        {
            const int r = lane & 7, hf = (lane >> 3) & 1;
            const int kkey = hf ? 8 + (r ^ 1) : r;
            const int vh = lane >> 4;
            const int vkey = ((r & 1) ? 8 : 0) + (vh ? (r ^ 1) : r);
#pragma unroll
            for (int b = 0; b < 3; b++) {
                const int rk = 3 * kkey + b, rv = 3 * vkey + b;
                koff[b] = buf + rk * 128 + (((lane >> 4) ^ (rk & 7)) << 4);
                voff[b] = buf + rv * 128 + ((hf ^ (rv & 7)) << 4);
            }
        }
        uint32_t phase = 0, kbar = bar;
        uint4 qf[6];
        auto load_q = [&](int u) {
            const uint32_t* q = &g_early[u / UPB].q[j * 4];
#pragma unroll
            for (int i = 0; i < 6; i++) qf[i] = ld_relaxed_v4(q + i * 16);
        };
        load_q(uk);
        int uq[LAG];
        uint32_t sq[LAG];
#pragma unroll
        for (int i = 0; i < LAG; i++) { uq[i] = -1; sq[i] = 0; }
        uint4 mv = make_uint4(0u, 0u, 0u, 0u);
        float freed = UPB;
        while (true) {
            const int uv = uq[0];
            uint32_t sv = sq[0];
#pragma unroll
            for (int i = 0; i + 1 < LAG; i++) { uq[i] = uq[i + 1]; sq[i] = sq[i + 1]; }
            uq[LAG - 1] = uk;
            if (uk < NUNITS) {
                PH(7);
#pragma unroll 1
                for (int it = 0; it < SPIN_MAX; it++) {
                    uint32_t lo = 0xffffffffu;
#pragma unroll
                    for (int i = 0; i < 6; i++) lo = min(min(lo, min(qf[i].x, qf[i].y)), min(qf[i].z, qf[i].w));
                    if (__all_sync(0xffffffffu, lo != 0)) break;
                    __nanosleep(250);
                    load_q(uk);
                }
#pragma unroll
                for (int t = 0; t < NPART; t++) mbar_wait(kbar + t * 8, phase);
                phase ^= 1;
                PH(0); ARR();
                TSI(0, 16); TSI(1, 18);
                float acc[2][4][4] = {};
#pragma unroll
                for (int ks = 0; ks < 12; ks++) {
                    const uint4 qq = qf[ks >> 1];
                    const uint32_t b0 = (ks & 1) ? qq.z : qq.x, b1 = (ks & 1) ? qq.w : qq.y;
#pragma unroll
                    for (int mt = 0; mt < 4; mt++) {
                        uint32_t a[4];
                        ldsm4(a, (koff[ks >> 2] ^ ((ks & 3) << 5)) + mt * 6144);
                        mma16816(acc[ks & 1][mt], a, b0, b1);
                    }
                }
                PH(1);
                TSI(0, 17); TSI(1, 19);
                if (uv < NUNITS && kbar == bar) request_tile(buf, uv >= 0 ? &p.v : &p.k, uv >= 0 ? uv : uk + (wk < NSPARE ? 2 : 1) * nstatic, bar, pol);
                const float sa = sel4(j, acc[0][0][0], acc[0][1][0], acc[0][2][0], acc[0][3][0]) + sel4(j, acc[1][0][0], acc[1][1][0], acc[1][2][0], acc[1][3][0]);
                const float sc = sel4(j, acc[0][0][2], acc[0][1][2], acc[0][2][2], acc[0][3][2]) + sel4(j, acc[1][0][2], acc[1][1][2], acc[1][2][2], acc[1][3][2]);
                const uint32_t raw = pack_bf16(sa, sc);
                const float scale = -0.07216878364870322f;
                const uint32_t sk = pack_bf16(lo_f(raw) * scale, hi_f(raw) * scale);
                sq[LAG - 1] = sk;
                if (uk >= POOL0) st_relaxed(&g_st.score[uk - POOL0][lane], sk ? sk : 0x80008000u);
                int a = (int)(sk << 16), b = (int)(sk & 0xffff0000u);
                a ^= (a >> 31) & 0x7fff0000; b ^= (b >> 31) & 0x7fff0000;
                const int mx = __reduce_max_sync(0xffffffffu, max(a, b));
                if (lane == 0) st_relaxed(&g_early[uk / UPB].umax[uk % UPB], (uint32_t)mx | 1u);
            }
            if (uv < 0) {
                if (wk < NSPARE) {
                    const int d = uk < nstatic ? SM_W - SM_KV : SM_KV - SM_W;
#pragma unroll
                    for (int b = 0; b < 3; b++) koff[b] += d;
                    kbar = uk < nstatic ? bar + NWORK * NPART * 8 : bar;
                    phase = uk >= nstatic;
                }
                uk += nstatic;
                load_q(uk);
                continue;
            }
            if (uv >= NUNITS) break;
            const int bh = uv / UPB;
#pragma unroll 1
            for (int it = 0; it < SPIN_MAX; it++) {
                if (__all_sync(0xffffffffu, (mv.x & mv.y & mv.z & mv.w & 1u) && (uv < POOL0 || sv != 0) && freed == UPB)) break;
                mv = ld_relaxed_v4(&g_early[bh].umax[lane * 4]);
                if (bh >= RING && bh < RED0) freed = __uint_as_float(ld_relaxed_u32(&g_st.oacc[oidx(bh - RING, (lane & 7) * 8)].w));
                if (uv >= POOL0) sv = ld_relaxed_u32(&g_st.score[uv - POOL0][lane]);
            }
            PH(2);
            int un = NUNITS, vn = 0;
            draw(un, g_work, uk < NUNITS && lane == 0);
            uint32_t tdraw;
            asm volatile("mov.u32 %0, %%globaltimer_lo;" : "=r"(tdraw));
            draw(vn, g_work + 32, uq[0] >= POOL0 && lane == 0);
            int mx = __reduce_max_sync(0xffffffffu, max(max((int)mv.x, (int)mv.y), max((int)mv.z, (int)mv.w))) & 0xffff0000;
            mx ^= (mx >> 31) & 0x7fff0000;
            const float m = __int_as_float(mx);
            const float l2e = 1.4426950408889634f;
            const uint32_t pp = pack_bf16(exp2f((lo_f(sv) - m) * l2e), exp2f((hi_f(sv) - m) * l2e));
            uint32_t pb[8];
#pragma unroll
            for (int t = 0; t < 4; t++) {
                pb[2 * t] = __shfl_sync(0xffffffffu, pp, 8 * j + t);
                pb[2 * t + 1] = __shfl_sync(0xffffffffu, pp, 8 * j + 4 + t);
            }
            float lacc[4] = {};
            const uint32_t ones[4] = {0x3f803f80u, 0x3f803f80u, 0x3f803f80u, 0x3f803f80u};
#pragma unroll
            for (int t = 0; t < 4; t++) mma16816(lacc, ones, pb[2 * t], pb[2 * t + 1]);
            if (uv < nstatic) {
                asm volatile("bar.sync 2, %0;" :: "n"((NWORK + 2) * 32) : "memory");
                TSW(3);
            }
            const int grp = 16 * j + 4 * (g & 1) + (g >> 1);
            uint32_t mode = (bh >= RED0) + (bh >= NBH - 4);
            float tag = mode ? 1.f : (float)(bh + 1), tag2 = tag;
            void* dst = mode == 0 ? (void*)&g_ring[bh % RING][uv % UPB][grp] :
                        mode == 1 ? (void*)&g_st.oacc[oidx(bh, grp)] : (void*)&g_st.ox[uv % OREP].w[0][oidx(bh & 3, grp) * 4];
            if (mode == 2 && lane < 2) red_f2(reinterpret_cast<float*>(&g_st.lx.w[lane][(bh & 3) * 256]), lacc[0], 1.f);
            un = __shfl_sync(0xffffffffu, un, 0) + (LAG + 1) * nstatic;
            vn = __shfl_sync(0xffffffffu, vn, 0);
            if (uq[0] >= POOL0) uq[0] = POOL0 + vn;
            if (vn == FW_TICKET && lane == 0) st_relaxed(g_st.fw_time, tdraw | 1u);
            if (EARLY_LOOK && uq[0] < NUNITS && un >= NUNITS) {
                mv = ld_relaxed_v4(&g_early[uq[0] / UPB].umax[lane * 4]);
                if (uq[0] < RED0 * UPB) freed = 0.f;
                if (uq[0] >= POOL0) sq[0] = ld_relaxed_u32(&g_st.score[uq[0] - POOL0][lane]);
            }
            pin(dst); pin(mode); pin(tag); pin(tag2); pin(voff[0]); pin(voff[1]); pin(voff[2]);
            PH(3);
            float acc[12][4] = {};
#pragma unroll
            for (int t = 0; t < 4; t++) {
                if (t % (4 / NPART) == 0) mbar_wait(bar + t / (4 / NPART) * 8, phase);
                if (t == 4 - 4 / NPART) { PH(4); ARR(); CK(12, lds32(buf)); }
#pragma unroll
                for (int mt = 0; mt < 12; mt++) {
                    uint32_t a[4];
                    ldsm4t(a, (voff[mt >> 2] ^ ((mt & 3) << 5)) + t * 6144);
                    mma16816(acc[mt], a, pb[2 * t], pb[2 * t + 1]);
                }
            }
            phase ^= 1;
            PH(5);
            if (lane == 0) PROG(un);
            if (un < NUNITS || uq[0] < NUNITS) request_tile(buf, un < NUNITS ? &p.k : &p.v, un < NUNITS ? un : uq[0], bar, pol);
            if (un < NUNITS || uq[0] < NUNITS) CK(11, 0);
            float o[6];
#pragma unroll
            for (int e = 0; e < 6; e++) {
                const int q = e % 3, c = (e / 3) * 2;
                o[e] = sel4(j, acc[q][c], acc[3 + q][c], acc[6 + q][c], acc[9 + q][c]);
            }
            put_groups(dst, mode, o, tag, tag2);
            CK(13, 0);
            if (un < NUNITS) load_q(un);
            if (lane == 0) red_f2(&g_st.lsum[bh][0].x, lacc[0], 1.f);
            PH(6);
            if (uq[0] >= NUNITS && un >= NUNITS) break;
            uk = un;
            if (uq[0] < NUNITS && (!EARLY_LOOK || un < NUNITS)) {
                const int nb = uq[0] / UPB;
                mv = ld_relaxed_v4(&g_early[nb].umax[lane * 4]);
                freed = nb >= RING && nb < RED0 ? __uint_as_float(ld_relaxed_u32(&g_st.oacc[oidx(nb - RING, (lane & 7) * 8)].w)) : UPB;
                if (uq[0] >= POOL0) sq[0] = ld_relaxed_u32(&g_st.score[uq[0] - POOL0][lane]);
            }
        }
        TSW(4 + wk);
        return;
    }

    __nv_bfloat16* xs = reinterpret_cast<__nv_bfloat16*>(smem + SM_X);
    float* red = reinterpret_cast<float*>(smem + SM_RED);
    const int frow = (lane & 7) + ((lane >> 4) << 3), fcol = (lane >> 3) & 1;
    const uint32_t f32b = sb + (frow * 2 + (fcol ^ ((frow >> 2) & 1))) * 16;
    const uint32_t f64b = sb + (frow * 4 + (fcol ^ ((frow >> 1) & 3))) * 16;
    if (cta < NQ_CTAS) {
        uint2 xr[5];
        if (warp < NB) {
#pragma unroll
            for (int i = 0; i < 5; i++) xr[i] = *reinterpret_cast<const uint2*>(p.x + warp * DM + i * 128 + lane * 4);
        }
        TS(26);
        if (warp < NB) {
            float v[20];
#pragma unroll
            for (int i = 0; i < 5; i++) {
                v[4 * i] = lo_f(xr[i].x); v[4 * i + 1] = hi_f(xr[i].x); v[4 * i + 2] = lo_f(xr[i].y); v[4 * i + 3] = hi_f(xr[i].y);
            }
            layernorm20(v);
#pragma unroll
            for (int i = 0; i < 5; i++)
                *reinterpret_cast<uint2*>(xs + warp * XPITCH + i * 128 + lane * 4) =
                    make_uint2(pack_bf16(v[4 * i], v[4 * i + 1]), pack_bf16(v[4 * i + 2], v[4 * i + 3]));
        }
        TS(27);
        aux_sync();
        mbar_wait(sb + BAR_WQ, 0);
        TS(1);
        const uint32_t xfrag = sb + SM_X + ((g & 3) * XPITCH + 2 * j) * 2;
        float acc[3][4] = {};
#pragma unroll
        for (int s = 0; s < 5; s++) {
            const int ks = warp * 5 + s;
            const uint32_t b0 = lds32(xfrag + ks * 32), b1 = lds32(xfrag + ks * 32 + 16);
            const int row = ks * 16 + frow;
#pragma unroll
            for (int mt = 0; mt < 3; mt++) {
                uint32_t a[4];
                ldsm4t(a, sb + SM_W + (row * 6 + 2 * mt + fcol) * 16);
                mma16816(acc[mt], a, b0, b1);
            }
        }
        if (j < 2) {
#pragma unroll
            for (int mt = 0; mt < 3; mt++) {
                *reinterpret_cast<float2*>(red + (warp * 48 + mt * 16 + g) * 4 + 2 * j) = make_float2(acc[mt][0], acc[mt][1]);
                *reinterpret_cast<float2*>(red + (warp * 48 + mt * 16 + 8 + g) * 4 + 2 * j) = make_float2(acc[mt][2], acc[mt][3]);
            }
        }
        aux_sync();
        if (tid < 96) {
            const int b = tid & 3, cp = tid >> 2;
            float s0 = 0.f, s1 = 0.f;
#pragma unroll
            for (int w = 0; w < 8; w++) { s0 += red[(w * 48 + 2 * cp) * 4 + b]; s1 += red[(w * 48 + 2 * cp + 1) * 4 + b]; }
            const int h = cta >> 2, d = (cta & 3) * 48 + 2 * cp;
            const int ch = d >> 3, jj = (d & 7) >> 1;
            st_relaxed(&g_early[b * NH + h].q[(ch >> 2) * 16 + jj * 4 + (ch & 3)], pack_neg(s0, s1));
        }
        TS(28);
    }
    if (warp >= 4 && warp < 4 + NSPARE) {
        uint64_t pol;
        asm volatile("createpolicy.fractional.L2::evict_first.b64 %0, 1.0;" : "=l"(pol));
        spin_ns(cta < NQ_CTAS ? SPARE_NS : WO_AT_NS + SPARE_NS);
        asm volatile("fence.proxy.async.shared::cta;" ::: "memory");
        request_tile(sb + SM_W + (warp - 4) * TILE_BYTES, &p.k, (NWORK + warp - 4) * grid + cta, sb + BAR_KV + (NWORK + warp - 4) * (NPART * 8), pol);
    }
    fin_sync<3>();
    mbar_wait(sb + BAR_WO, 0);
    TS(7);
    uint32_t part = sb + SM_RED + (warp * 32 + 8 * j + g) * 4;

#pragma unroll 1
    for (int b = 0; b < NB; b++) {
        if (cta >= NE_CTAS) {
            uint32_t a[6][2][4];
#pragma unroll
            for (int s = 0; s < 6; s++) {
#pragma unroll
                for (int mt = 0; mt < 2; mt++) ldsm4t(a[s][mt], (f64b ^ (mt * 32)) + SM_A + (warp * 6 + s) * 1024);
            }
            const int bh = b * NH + 28 + (warp >> 1);
            const int side = near_side(sb) ^ 1;
            const void* osrc[OREP];
#pragma unroll
            for (int c = 0; c < OREP; c++)
                osrc[c] = b == NB - 1 ? (const void*)&g_st.ox[c].w[side][oidx(bh & 3, (warp & 1) * 32 + lane) * 4] : &g_st.oacc[oidx(bh, (warp & 1) * 32 + lane)];
            const void* lsrc = b == NB - 1 ? (const void*)&g_st.lx.w[side][(bh & 3) * 256] : g_st.lsum[bh];
            wait_row_o(bh, 1);
            const float rl = rcp_approx(wait_sum(lsrc, UPB)) * (b == NB - 1 ? 1.f : 1.f / OREP), full = b == NB - 1 ? UPB : UPB * OREP;
            float4 ov;
            float px, py, pz;
#pragma unroll 1
            for (int it = 0; it < SPIN_MAX; it++) {
                float4 oc[OREP];
#pragma unroll
                for (int c = 0; c < OREP; c++) oc[c] = ld_relaxed_f4(osrc[c]);
                ov = oc[0];
#pragma unroll
                for (int c = 1; c < OREP; c++) { ov.x += oc[c].x; ov.y += oc[c].y; ov.z += oc[c].z; ov.w += oc[c].w; }
                ov.x *= rl; ov.y *= rl; ov.z *= rl;
                px = __shfl_xor_sync(0xffffffffu, ov.x, 4); py = __shfl_xor_sync(0xffffffffu, ov.y, 4); pz = __shfl_xor_sync(0xffffffffu, ov.z, 4);
                if (all(ov.w == full)) break;
            }
            CK(0, __float_as_uint(ov.x));
            if (ov.x != 1.2345f && warp == 7) TSW(14);
            const uint32_t w[3] = {pack_bf16(ov.x, px), pack_bf16(ov.y, py), pack_bf16(ov.z, pz)};
            float acc[2][2][4] = {};
#pragma unroll
            for (int s = 0; s < 6; s++) {
                const uint32_t b0 = __shfl_sync(0xffffffffu, w[s % 3], (s / 3) * 16 + j);
                const uint32_t b1 = __shfl_sync(0xffffffffu, w[s % 3], (s / 3) * 16 + 8 + j);
#pragma unroll
                for (int mt = 0; mt < 2; mt++) mma16816(acc[mt][s & 1], a[s][mt], b0, b1);
            }
            sts32f(part, sel4(j, acc[0][0][0] + acc[0][1][0], acc[0][0][2] + acc[0][1][2], acc[1][0][0] + acc[1][1][0], acc[1][0][2] + acc[1][1][2]));
            CK(1, 0);
            fin_arrive<4>();
            fin_sync<5>();
            if (cta < NE_CTAS + 4 && tid < 56) reinterpret_cast<uint4*>(&g_early[b * NH + 28 + cta - NE_CTAS])[tid] = make_uint4(0u, 0u, 0u, 0u);
        } else {
            const int bh = b * NH + (cta >> 2);
            if (warp == 0) wait_row_o(bh, UPB);
            aux_sync();
            if (warp < 5) {
                uint32_t ob[12][2];
                load_o<4>(ob, bh, 0, j);
                float acc[2][2][4] = {};
#pragma unroll
                for (int ks = 0; ks < 12; ks++) {
#pragma unroll
                    for (int mt = 0; mt < 2; mt++) {
                        uint32_t a[4];
                        ldsm4t(a, (f64b ^ (mt * 32)) + SM_A + warp * 12288 + ks * 1024);
                        mma16816(acc[mt][ks & 1], a, ob[ks][0], ob[ks][1]);
                    }
                }
                red_f2(&g_st.attn[b][(cta & 3) * 160 + warp * 32 + 8 * j + g].x,
                       sel4(j, acc[0][0][0] + acc[0][1][0], acc[0][0][2] + acc[0][1][2], acc[1][0][0] + acc[1][1][0], acc[1][0][2] + acc[1][1][2]), 1.f);
                TS(8);
            } else if (warp > 5 && (cta & 3) == 0 && tid - 192 < 56) {
                reinterpret_cast<uint4*>(&g_early[bh])[tid - 192] = make_uint4(0u, 0u, 0u, 0u);
            }
        }
        if (b < NB - 2) continue;

        if (is_f(cta)) {
            uint32_t ga[10][2][4];
            uint4 hv[5] = {};
            const uint32_t hfrag = sb + SM_X + min(g, 4) * HPITCH + ((warp >> 1) * 80 + 4 * j) * 4;
#pragma unroll
            for (int s = 0; s < 5; s++) lds128_if(hv[s], hfrag + s * 64, b == NB - 1);
            if (b == NB - 1) mbar_wait(sb + BAR_FW + warp * 8, 0);
            if (warp == 7) TSW(10);
            CK(12, lds32(sb + SM_W));
#pragma unroll
            for (int s = 0; s < 10; s++) {
#pragma unroll
                for (int mt = 0; mt < 2; mt++) ldsm4t(ga[s][mt], (f64b ^ (mt * 32)) + SM_W + (warp * 10 + s) * 1024);
            }
            const uint32_t gpart = sb + SM_RED + (warp >> 1) * 640 + j * 256 + ((g + 2 * j) & 7) * 16 + (warp & 1) * 8;
            mbar_wait(sb + BAR_H, b & 1);
#pragma unroll
            for (int s = 0; s < 5; s++) lds128_if(hv[s], hfrag + s * 64, g == b);
            CK(4, hv[0].x);
            float acc[2][2][4] = {};
#pragma unroll
            for (int s = 0; s < 10; s++) {
#pragma unroll
                for (int mt = 0; mt < 2; mt++)
                    mma16816(acc[mt][s & 1], ga[s][mt], (s & 1) ? hv[s >> 1].z : hv[s >> 1].x, (s & 1) ? hv[s >> 1].w : hv[s >> 1].y);
            }
#pragma unroll
            for (int mt = 0; mt < 2; mt++) {
                if (j < 3) sts64f(gpart + mt * 2560, acc[mt][0][0] + acc[mt][1][0], acc[mt][0][2] + acc[mt][1][2]);
                if (j < 2) sts64f(gpart + mt * 2560 + 128, acc[mt][0][1] + acc[mt][1][1], acc[mt][0][3] + acc[mt][1][3]);
            }
            CK(5, 0);
            asm volatile("bar.arrive 4, 320;" ::: "memory");
        } else if (is_g(cta)) {
            const uint32_t* asrc = &g_st.ax[0].w[(~b & 1) * 2 + near_side(sb)][ALINE ? warp * 128 + ((g >> 2) * 2 + (j >> 1)) * 32 + (g & 3) * 8 + (j & 1) * 4 : (warp * 32 + lane) * 4];
            const uint32_t ypart = sb + SM_RED2 + warp * 512 + j * 128 + ((g + 2 * j) & 7) * 16;
            uint32_t wb[12][4];
            if (b == NB - 1) mbar_wait(sb + BAR_FW + warp * 8, 0);
            if (warp == 7) TSW(11);
            CK(13, lds32(sb + SM_W));
            {
                const int jj = (lane & 7) >> 1, q = jj >> 1, hi = lane >> 4;
                const uint32_t base = sb + SM_W + warp * 6144 + q * 512 + ((hi ^ q) * 4 + (jj & 1) * 2 + (lane & 1)) * 32 + ((fcol ^ hi ^ q) << 4);
#pragma unroll
                for (int s = 0; s < 12; s++) ldsm4t(wb[s], base + (s >> 2) * 2048 + (s & 1) * 1024 + (s & 2) * 128);
            }
            mbar_wait(sb + BAR_H, b & 1);
            uint4 va[3];
#pragma unroll 1
            for (int it = 0; it < SPIN_MAX; it++) {
                uint32_t lo = 0xffffffffu;
#pragma unroll
                for (int i = 0; i < 3; i++) va[i] = ld_relaxed_v4(asrc + i * 4096);
#pragma unroll
                for (int i = 0; i < 3; i++) lo = min(min(lo, min(va[i].x, va[i].y)), min(va[i].z, va[i].w));
                if (all(lo != 0)) break;
            }
            CK(8, va[0].x);
            if (va[0].x != 0x12345 && warp == 7) TSW(15);
            float acc[GCH][4] = {};
#pragma unroll
            for (int s = 0; s < 12; s++) {
                const uint4 v = va[s >> 2];
                mma16816(acc[s % GCH], wb[s], (s & 2) ? v.z : v.x, (s & 2) ? v.w : v.y);
            }
            float y[4];
#pragma unroll
            for (int e = 0; e < 4; e++) {
                y[e] = j < 2 ? acc[0][e] + acc[2][e] : acc[1][e] + acc[3][e];
                if (GCH == 6) y[e] += j < 2 ? acc[GCH - 2][e] : acc[GCH - 1][e];
            }
            sts128f(ypart, y[0], y[1], y[2], y[3]);
            CK(9, 0);
            fin_arrive<6>();
        }
    }
}

typedef CUresult (*EncodeFn)(CUtensorMap*, CUtensorMapDataType, cuuint32_t, void*, const cuuint64_t*, const cuuint64_t*,
                             const cuuint32_t*, const cuuint32_t*, CUtensorMapInterleave, CUtensorMapSwizzle,
                             CUtensorMapL2promotion, CUtensorMapFloatOOBfill);

CUtensorMap make_map(EncodeFn enc, void* ptr, uint64_t cols, uint64_t rows, uint32_t bcols, uint32_t brows,
                     CUtensorMapSwizzle sw, CUtensorMapL2promotion promo) {
    CUtensorMap m;
    const cuuint64_t dims[2] = {cols, rows};
    const cuuint64_t strides[1] = {cols * 2};
    const cuuint32_t box[2] = {bcols, brows};
    const cuuint32_t es[2] = {1, 1};
    enc(&m, CU_TENSOR_MAP_DATA_TYPE_BFLOAT16, 2, ptr, dims, strides, box, es, CU_TENSOR_MAP_INTERLEAVE_NONE, sw, promo,
        CU_TENSOR_MAP_FLOAT_OOB_FILL_NONE);
    return m;
}

}

extern "C" void kernel_launch(void* const* d_in, const int* in_sizes, int n_in, void* d_out, int out_size) {
    (void)in_sizes; (void)n_in; (void)out_size;
    static EncodeFn enc = nullptr;
    static int sms = 0;
    if (!enc) {
        cudaDriverEntryPointQueryResult qr;
        cudaGetDriverEntryPoint("cuTensorMapEncodeTiled", (void**)&enc, cudaEnableDefault, &qr);
        int dev = 0;
        cudaGetDevice(&dev);
        cudaDeviceGetAttribute(&sms, cudaDevAttrMultiProcessorCount, dev);
        cudaFuncSetAttribute(fused_decode_kernel, cudaFuncAttributeMaxDynamicSharedMemorySize, SM_TOTAL);
    }
    if (sms < NCTAS) return;
    const CUtensorMapL2promotion WPROMO = CU_TENSOR_MAP_L2_PROMOTION_L2_128B;
#define GPROMO 2
#define DPROMO 2
    Params p;
    p.k = make_map(enc, d_in[1], 64, (uint64_t)NBH * SK * 3, 64, TILE_ROWS / NPART, CU_TENSOR_MAP_SWIZZLE_128B, CU_TENSOR_MAP_L2_PROMOTION_NONE);
    p.v = make_map(enc, d_in[2], 64, (uint64_t)NBH * SK * 3, 64, TILE_ROWS / NPART, CU_TENSOR_MAP_SWIZZLE_128B, CU_TENSOR_MAP_L2_PROMOTION_NONE);
    p.wq = make_map(enc, d_in[3], NH * DH, DM, 48, 160, CU_TENSOR_MAP_SWIZZLE_NONE, WPROMO);
    p.wo = make_map(enc, d_in[4], DM, NH * DH, 32, DH, CU_TENSOR_MAP_SWIZZLE_64B, WPROMO);
    p.wg = make_map(enc, d_in[7], FF, DM, 32, 160, CU_TENSOR_MAP_SWIZZLE_64B, (CUtensorMapL2promotion)GPROMO);
    p.wu = make_map(enc, d_in[8], FF, DM, 32, 160, CU_TENSOR_MAP_SWIZZLE_64B, (CUtensorMapL2promotion)GPROMO);
    {
        const cuuint64_t dims[4] = {DM, 2, 8, FF / 16}, strides[3] = {8 * DM * 2, DM * 2, 16 * DM * 2};
        const cuuint32_t box[4] = {16, 2, 8, 12}, es[4] = {1, 1, 1, 1};
        enc(&p.wd, CU_TENSOR_MAP_DATA_TYPE_BFLOAT16, 4, d_in[9], dims, strides, box, es, CU_TENSOR_MAP_INTERLEAVE_NONE,
            CU_TENSOR_MAP_SWIZZLE_32B, (CUtensorMapL2promotion)DPROMO, CU_TENSOR_MAP_FLOAT_OOB_FILL_NONE);
    }
    p.x = (const __nv_bfloat16*)d_in[0];
    p.wr = (const __nv_bfloat16*)d_in[6];
    p.out = (__nv_bfloat16*)d_out;
    fused_decode_kernel<<<NCTAS, NTHREADS, SM_TOTAL, cudaStreamPerThread>>>(p);
}
```

```cpp
#include <cuda_runtime.h>
#include <cuda_bf16.h>
#include <cuda.h>
#include <stdint.h>

namespace {

constexpr int NB = 4, NH = 32, SK = 8192, DH = 192, DM = 640, FF = 1536;
constexpr int NBH = NB * NH;
constexpr int TILE = 64;
constexpr int UPB = SK / TILE;
constexpr int NUNITS = NBH * UPB;
constexpr int TILE_BYTES = TILE * DH * 2;
constexpr int TILE_ROWS = TILE * 3;
constexpr int NCTAS = 132;
constexpr int NQ_CTAS = 128;
constexpr int NE_CTAS = 112;
#define ROLES 1
__host__ __device__ constexpr bool is_f(int cta) { return cta < 96 && !(cta & 2); }
__host__ __device__ constexpr bool is_g(int cta) { return cta < 80 && (cta & 2); }
__host__ __device__ constexpr int ffn_slice(int cta) { return (cta >> 2) * 2 + (cta & 1); }

#define NWORK 2
#define NPART 1
#define NSPARE 1
#define SPARE_NS 0
#define LAG 2
#define NPOOL 768
#define RED0 116
#define RING 12
#define OREP 3
#define K0_DELAY_NS 1200
#define WO_AT_NS 3800
#define FW_TICKET 648
#define FW_AT_NS 3300
#define FW_GAP 280
#define FW_GAP2 160
#define FW_STAG (FW_GAP / 2)
#define HREP2 2
#define LSTAT 1
#define WQ_FENCE 0
#define TRIM 7
#define HGATE 700
#define EARLY_LOOK 1
#define ALINE 1
#define FARFIRST 1
#define GCH 6
#define WARM 31
#define NPROBE 24
#define SIDE_XOR 0
#define FW_MID 2100
constexpr int NAUX = 8;
constexpr int NTHREADS = (NAUX + NWORK + 2) * 32;
constexpr int SPIN_MAX = 1 << 22;

constexpr int SM_KV = 0;
constexpr int SM_A = SM_KV + NWORK * TILE_BYTES;
constexpr int SM_W = SM_A + 61440;
constexpr int SM_X = SM_W + 81920;
constexpr int XPITCH = 648;
constexpr int HPITCH = 1344;
constexpr int SM_RED = SM_X + 5 * HPITCH + 64;
constexpr int SM_RED2 = SM_RED + 8 * 48 * 4 * 4;
constexpr int SM_MISC = SM_RED2 + 4096;
constexpr int BAR_WQ = SM_MISC + 32, BAR_WO = SM_MISC + 40, SM_SIDE = SM_MISC + 48, BAR_H = SM_MISC + 56, BAR_FW = SM_MISC + 64;
constexpr int BAR_KV = BAR_FW + 64;
constexpr int SM_TOTAL = BAR_KV + 2 * NWORK * NPART * 8;
static_assert(LAG == 2 && SM_W % 1024 == 0 && NB * XPITCH * 2 <= 4 * HPITCH && SM_RED % 128 == 0, "smem layout");

struct Params {
    CUtensorMap k, v;
    CUtensorMap wq;
    CUtensorMap wo;
    CUtensorMap wg, wu;
    CUtensorMap wd;
    const __nv_bfloat16 *x, *wr;
    __nv_bfloat16* out;
};

struct Early {
    uint32_t q[96];
    uint32_t umax[UPB];
};
struct Twin { uint32_t w[4][1024]; };
constexpr int PROBE = 1024 - 32;
#define LSTRIDE 16
struct State {
    Twin ax[3];
    Twin hx;
    Twin ox[OREP];
    Twin lx;
    float4 oacc[NBH * 64];
    float2 attn[NB][DM];
    uint32_t fw_time[32];
    float2 lsum[NBH][LSTRIDE];
    uint32_t score[NPOOL][32];
};
__host__ __device__ constexpr int oidx(int row, int grp) {
    return (row >> 2) * 256 + ((row & 1) * 2 + (grp >> 5)) * 64 + (row & 2) * 16 + (grp & 31);
}
constexpr int STATE_V4 = ((sizeof(State) / 32 + NQ_CTAS - 1) / NQ_CTAS) * 2;
static_assert(sizeof(State) % 32 == 0, "State is cleared in whole sectors");
static_assert(sizeof(Early) == 56 * 16, "an Early entry is cleared by 56 threads");
struct Scratch {
    State st;
    unsigned work[64];
    unsigned cnt_z[32];
    Early early[NBH];
    alignas(4096) float4 ring[RING][UPB][64];
};
constexpr size_t PAGE = 2u << 20;
static_assert(sizeof(Scratch) <= PAGE, "scratch must fit one page");
__device__ __align__(128) unsigned char g_raw[2 * PAGE];
__device__ __forceinline__ Scratch* scratch() {
    return reinterpret_cast<Scratch*>((reinterpret_cast<uintptr_t>(g_raw) + PAGE - 1) & ~(uintptr_t)(PAGE - 1));
}
#define g_early scratch()->early
#define g_st scratch()->st
#define g_ring scratch()->ring
#define g_cnt_z scratch()->cnt_z
#define g_work scratch()->work
#define TS(i)
#define TSW(i)
#define TS2(i)
#define TSI(n, i)
#define PH(i)
#define CK(i, dep)
#define ARR()
#define PROG(u)

__device__ __forceinline__ uint32_t s2u(const void* p) { return (uint32_t)__cvta_generic_to_shared(p); }
__device__ __forceinline__ void mbar_init(uint32_t bar, int cnt) {
    asm volatile("mbarrier.init.shared::cta.b64 [%0], %1;" :: "r"(bar), "r"(cnt) : "memory");
}
__device__ __forceinline__ void mbar_expect_tx(uint32_t bar, uint32_t bytes) {
    asm volatile("mbarrier.arrive.expect_tx.shared::cta.b64 _, [%0], %1;" :: "r"(bar), "r"(bytes) : "memory");
}
__device__ __forceinline__ void mbar_wait(uint32_t bar, uint32_t parity) {
    asm volatile("{\n.reg .pred p;\n.reg .u32 n;\nmov.u32 n, 0;\nWAIT_LOOP:\n"
                 "mbarrier.try_wait.parity.shared::cta.b64 p, [%0], %1;\n"
                 "@p bra WAIT_DONE;\nadd.u32 n, n, 1;\nsetp.lt.u32 p, n, %2;\n@p bra WAIT_LOOP;\nWAIT_DONE:\n}"
                 :: "r"(bar), "r"(parity), "n"(SPIN_MAX) : "memory");
}
__device__ __forceinline__ void request_tile(uint32_t dst, const CUtensorMap* tm, int unit, uint32_t bar, uint64_t pol) {
#pragma unroll
    for (int i = 0; i < NPART; i++)
        asm volatile("{\n.reg .pred p;\nelect.sync _|p, 0xffffffff;\n"
                     "@p mbarrier.arrive.expect_tx.shared::cta.b64 _, [%2], %6;\n"
                     "@p cp.async.bulk.tensor.2d.shared::cluster.global.mbarrier::complete_tx::bytes.L2::cache_hint "
                     "[%0], [%1, {%3, %4}], [%2], %5;\n}"
                     :: "r"(dst + i * (TILE_BYTES / NPART)), "l"(tm), "r"(bar + i * 8), "r"(0), "r"(unit * TILE_ROWS + i * (TILE_ROWS / NPART)),
                        "l"(pol), "n"(TILE_BYTES / NPART) : "memory");
}
__device__ __forceinline__ void put_groups(void* dst, int mode, const float (&o)[6], float tag, float tag2) {
    asm volatile("{\n.reg .pred s, r, t;\n.reg .b128 u, v;\n.reg .b64 a, b;\n"
                 "setp.eq.s32 s|r, %1, 0;\nsetp.eq.s32 t, %1, 2;\n"
                 "@r red.relaxed.gpu.global.add.v4.f32 [%0], {%2,%3,%4,%8};\n"
                 "@t red.relaxed.gpu.global.add.v4.f32 [%0+4096], {%2,%3,%4,%8};\n"
                 "@r red.relaxed.gpu.global.add.v4.f32 [%0+128], {%5,%6,%7,%9};\n"
                 "@t red.relaxed.gpu.global.add.v4.f32 [%0+4224], {%5,%6,%7,%9};\n"
                 "mov.b64 a, {%2, %3};\nmov.b64 b, {%4, %8};\nmov.b128 u, {a, b};\n"
                 "mov.b64 a, {%5, %6};\nmov.b64 b, {%7, %9};\nmov.b128 v, {a, b};\n"
                 "@s st.relaxed.gpu.global.b128 [%0], u;\n@s st.relaxed.gpu.global.b128 [%0+128], v;\n}"
                 :: "l"(dst), "r"(mode), "f"(o[0]), "f"(o[1]), "f"(o[2]), "f"(o[3]), "f"(o[4]), "f"(o[5]), "f"(tag), "f"(tag2) : "memory");
}
__device__ __forceinline__ void request_box(uint32_t dst, const CUtensorMap* tm, int col, int row, uint32_t bar, uint32_t bytes) {
    asm volatile("{\n.reg .pred p, q;\nelect.sync _|p, 0xffffffff;\nsetp.ne.and.u32 q, %5, 0, p;\n"
                 "@q mbarrier.arrive.expect_tx.shared::cta.b64 _, [%2], %5;\n"
                 "@p cp.async.bulk.tensor.2d.shared::cluster.global.mbarrier::complete_tx::bytes [%0], [%1, {%3, %4}], [%2];\n}"
                 :: "r"(dst), "l"(tm), "r"(bar), "r"(col), "r"(row), "r"(bytes) : "memory");
}
__device__ __forceinline__ uint32_t lds32(uint32_t addr) {
    uint32_t v;
    asm volatile("ld.shared.u32 %0, [%1];" : "=r"(v) : "r"(addr) : "memory");
    return v;
}
__device__ __forceinline__ void ldsm4(uint32_t (&r)[4], uint32_t addr) {
    asm volatile("ldmatrix.sync.aligned.m8n8.x4.shared.b16 {%0,%1,%2,%3}, [%4];"
                 : "=r"(r[0]), "=r"(r[1]), "=r"(r[2]), "=r"(r[3]) : "r"(addr) : "memory");
}
__device__ __forceinline__ void ldsm4t(uint32_t (&r)[4], uint32_t addr) {
    asm volatile("ldmatrix.sync.aligned.m8n8.x4.trans.shared.b16 {%0,%1,%2,%3}, [%4];"
                 : "=r"(r[0]), "=r"(r[1]), "=r"(r[2]), "=r"(r[3]) : "r"(addr) : "memory");
}
__device__ __forceinline__ void mma16816(float (&c)[4], const uint32_t (&a)[4], uint32_t b0, uint32_t b1) {
    asm volatile("mma.sync.aligned.m16n8k16.row.col.f32.bf16.bf16.f32 {%0,%1,%2,%3}, {%4,%5,%6,%7}, {%8,%9}, {%0,%1,%2,%3};"
                 : "+f"(c[0]), "+f"(c[1]), "+f"(c[2]), "+f"(c[3])
                 : "r"(a[0]), "r"(a[1]), "r"(a[2]), "r"(a[3]), "r"(b0), "r"(b1));
}
struct Warm {
    float c[4] = {};
    __device__ __forceinline__ void operator()() {
        asm volatile("mma.sync.aligned.m16n8k8.row.col.f32.bf16.bf16.f32 {%0,%1,%2,%3}, {%4,%4}, {%4}, {%0,%1,%2,%3};"
                     : "+f"(c[0]), "+f"(c[1]), "+f"(c[2]), "+f"(c[3]) : "r"(0));
    }
    __device__ __forceinline__ void done(uint32_t scrap) {
        asm volatile("{\n.reg .pred p;\nsetp.gt.f32 p, %1, 0f3f800000;\n@p st.shared.f32 [%0], %1;\n}" :: "r"(scrap), "f"(c[0]) : "memory");
    }
};
__device__ __forceinline__ uint4 ld_relaxed_v4(const void* p) {
    uint4 v;
    asm volatile("ld.relaxed.gpu.global.v4.u32 {%0,%1,%2,%3}, [%4];" : "=r"(v.x), "=r"(v.y), "=r"(v.z), "=r"(v.w) : "l"(p) : "memory");
    return v;
}
__device__ __forceinline__ float4 ld_relaxed_f4(const void* p) {
    float4 v;
    asm volatile("ld.relaxed.gpu.global.v4.f32 {%0,%1,%2,%3}, [%4];" : "=f"(v.x), "=f"(v.y), "=f"(v.z), "=f"(v.w) : "l"(p) : "memory");
    return v;
}
__device__ __forceinline__ float2 ld_relaxed_f2(const void* p) {
    float2 v;
    asm volatile("ld.relaxed.gpu.global.v2.f32 {%0,%1}, [%2];" : "=f"(v.x), "=f"(v.y) : "l"(p) : "memory");
    return v;
}
__device__ __forceinline__ float4 ld_relaxed_b128(const void* p) {
    float4 v;
    asm volatile("{\n.reg .b128 t;\n.reg .b64 a, b;\nld.relaxed.gpu.global.b128 t, [%4];\nmov.b128 {a, b}, t;\n"
                 "mov.b64 {%0, %1}, a;\nmov.b64 {%2, %3}, b;\n}" : "=f"(v.x), "=f"(v.y), "=f"(v.z), "=f"(v.w) : "l"(p) : "memory");
    return v;
}
__device__ __forceinline__ void st_relaxed_b128(void* p, float x, float y, float z, float w) {
    asm volatile("{\n.reg .b128 t;\n.reg .b64 a, b;\nmov.b64 a, {%1, %2};\nmov.b64 b, {%3, %4};\nmov.b128 t, {a, b};\n"
                 "st.relaxed.gpu.global.b128 [%0], t;\n}" :: "l"(p), "f"(x), "f"(y), "f"(z), "f"(w) : "memory");
}
__device__ __forceinline__ unsigned ld_acquire(const unsigned* p) {
    unsigned v;
    asm volatile("ld.acquire.gpu.global.u32 %0, [%1];" : "=r"(v) : "l"(p) : "memory");
    return v;
}
__device__ __forceinline__ void st_relaxed(void* p, uint32_t v) {
    asm volatile("st.relaxed.gpu.global.u32 [%0], %1;" :: "l"(p), "r"(v) : "memory");
}
__device__ __forceinline__ void red_f2(float* p, float a, float b) {
    asm volatile("red.relaxed.gpu.global.add.v2.f32 [%0], {%1,%2};" :: "l"(p), "f"(a), "f"(b) : "memory");
}
__device__ __forceinline__ void draw(int& ticket, unsigned* ctr, bool pred) {
    asm volatile("{\n.reg .pred p;\nsetp.ne.u32 p, %2, 0;\n@p atom.relaxed.gpu.global.inc.u32 %0, [%1], 0x7fffffff;\n}"
                 : "+r"(ticket) : "l"(ctr), "r"((uint32_t)pred) : "memory");
}
__device__ __forceinline__ void red_release(unsigned* p) {
    asm volatile("red.release.gpu.global.add.u32 [%0], 1;" :: "l"(p) : "memory");
}
__device__ __forceinline__ uint32_t ld_relaxed_u32(const void* p) {
    uint32_t v;
    asm volatile("ld.relaxed.gpu.global.u32 %0, [%1];" : "=r"(v) : "l"(p) : "memory");
    return v;
}
__device__ __forceinline__ float rcp_approx(float v) {
    float r;
    asm("rcp.approx.ftz.f32 %0, %1;" : "=f"(r) : "f"(v));
    return r;
}
__device__ __forceinline__ float ex2_approx(float v) {
    float e;
    asm("ex2.approx.ftz.f32 %0, %1;" : "=f"(e) : "f"(v));
    return e;
}
__device__ __forceinline__ float sigmoid_approx(float v) { return rcp_approx(1.0f + ex2_approx(v * -1.4426950408889634f)); }
__device__ __forceinline__ float sqrt_approx(float v) {
    float r;
    asm("sqrt.approx.ftz.f32 %0, %1;" : "=f"(r) : "f"(v));
    return r;
}
__device__ __forceinline__ bool all(bool v) { return __all_sync(0xffffffffu, v); }
__device__ __forceinline__ void wait_count(const unsigned* p, unsigned target) {
#pragma unroll 1
    for (int it = 0; it < SPIN_MAX; it++) {
        if (all(ld_acquire(p) >= target)) break;
        __nanosleep(400);
    }
}
__device__ __forceinline__ float wait_sum(const void* p, float n, int nap = 0) {
    float2 v;
#pragma unroll 1
    for (int it = 0; it < SPIN_MAX; it++) {
        v = ld_relaxed_f2(p);
        if (all(v.y >= n)) break;
        if (all(v.y == 0.f)) __nanosleep(600);
        else if (nap) __nanosleep(nap);
    }
    return v.x;
}
__device__ __forceinline__ void wait_row(int bh, float n) { wait_sum(g_st.lsum[bh], n); }
__device__ __forceinline__ void wait_row_o(int bh, float n) {
    wait_row(bh, n);
    if (bh >= RED0) return;
#pragma unroll 1
    for (int it = 0; it < SPIN_MAX; it++) {
        if (all(__uint_as_float(ld_relaxed_u32(&g_st.oacc[oidx(bh, 0)].w)) == UPB)) break;
        __nanosleep(300);
    }
}
__device__ __forceinline__ void wait_clock(uint32_t t, Warm& warm) { while (!all((int)(clock() - t) >= 0)) { if (WARM & 1) warm(); } }
__device__ __forceinline__ void spin_ns(int ns) { const uint32_t t = clock() + ns * 2; while (!all((int)(clock() - t) >= 0)) {} }
__device__ __forceinline__ uint32_t pack_bf16(float lo, float hi) {
    uint32_t r;
    asm("cvt.rn.bf16x2.f32 %0, %1, %2;" : "=r"(r) : "f"(hi), "f"(lo));
    return r;
}
__device__ __forceinline__ float bf16r(float v) { return __uint_as_float(pack_bf16(0.f, v)); }
__device__ __forceinline__ uint32_t nonzero(uint32_t w) { return w ? w : 0x80008000u; }
__device__ __forceinline__ uint32_t pack_neg(float lo, float hi) { return nonzero(pack_bf16(-lo, -hi)); }
__device__ __forceinline__ float lo_f(uint32_t v) { return __uint_as_float(v << 16); }
__device__ __forceinline__ float hi_f(uint32_t v) { return __uint_as_float(v & 0xffff0000u); }
__device__ __forceinline__ float warp_sum(float v) {
#pragma unroll
    for (int o = 16; o; o >>= 1) v += __shfl_xor_sync(0xffffffffu, v, o);
    return v;
}
__device__ __forceinline__ void layernorm20(float (&v)[20]) {
    float s = 0.f;
#pragma unroll
    for (int i = 0; i < 20; i++) s += v[i];
    const float mean = warp_sum(s) * (1.0f / DM);
    float q = 0.f;
#pragma unroll
    for (int i = 0; i < 20; i++) { const float d = v[i] - mean; q += d * d; }
    const float var = bf16r(warp_sum(q) * (1.0f / DM));
    const float m = bf16r(mean);
    const float rden = 1.0f / bf16r(sqrtf(bf16r(var + 1e-5f)));
#pragma unroll
    for (int i = 0; i < 20; i++) v[i] = bf16r(bf16r(v[i] - m) * rden);
}

__device__ __forceinline__ void moments(float m1, float m2, float& nmean, float& rden) {
    m1 *= 1.0f / DM;
    const float var = bf16r(fmaxf(fmaf(-m1, m1, m2 * (1.0f / DM)), 0.f));
    nmean = bf16r(m1);
    rden = rcp_approx(bf16r(sqrt_approx(bf16r(var + 1e-5f))));
}
__device__ __forceinline__ float sel4(int j, float a, float b, float c, float d) {
    float lo, hi, r;
    asm("{\n.reg .pred p;\nsetp.ne.s32 p, %3, 0;\nselp.f32 %0, %2, %1, p;\n}" : "=f"(lo) : "f"(a), "f"(b), "r"(j & 1));
    asm("{\n.reg .pred p;\nsetp.ne.s32 p, %3, 0;\nselp.f32 %0, %2, %1, p;\n}" : "=f"(hi) : "f"(c), "f"(d), "r"(j & 1));
    asm("{\n.reg .pred p;\nsetp.ne.s32 p, %3, 0;\nselp.f32 %0, %2, %1, p;\n}" : "=f"(r) : "f"(lo), "f"(hi), "r"(j & 2));
    return r;
}
template <typename T> __device__ __forceinline__ void pin(T*& p) { asm volatile("" : "+l"(p)); }
__device__ __forceinline__ void pin(uint32_t& v) { asm volatile("" : "+r"(v)); }
__device__ __forceinline__ void pin(float& v) { asm volatile("" : "+f"(v)); }
__device__ __forceinline__ uint32_t after(uint32_t n, float v) {
    asm volatile("{\n.reg .pred p;\nsetp.eq.u32 p, %1, 0x7fc1a5a5;\n@p add.u32 %0, %0, 32;\n}" : "+r"(n) : "r"(__float_as_uint(v)));
    return n;
}
__device__ __forceinline__ float2 lds64f(uint32_t addr) {
    float2 v;
    asm volatile("ld.shared.v2.f32 {%0,%1}, [%2];" : "=f"(v.x), "=f"(v.y) : "r"(addr) : "memory");
    return v;
}
__device__ __forceinline__ void sts32f(uint32_t addr, float v) { asm volatile("st.shared.f32 [%0], %1;" :: "r"(addr), "f"(v) : "memory"); }
template <int ID> __device__ __forceinline__ void fin_arrive() { asm volatile("bar.arrive %0, 288;" :: "n"(ID) : "memory"); }
template <int ID> __device__ __forceinline__ void fin_sync() { asm volatile("bar.sync %0, 288;" :: "n"(ID) : "memory"); }
template <int ID> __device__ __forceinline__ void fin_sync(uint32_t n) { asm volatile("bar.sync %0, %1;" :: "n"(ID), "r"(n) : "memory"); }
__device__ __forceinline__ float2 sum8(uint32_t addr) {
    float2 t[8];
#pragma unroll
    for (int w = 0; w < 8; w++) t[w] = lds64f(addr + w * 128);
    return make_float2(((t[0].x + t[1].x) + (t[2].x + t[3].x)) + ((t[4].x + t[5].x) + (t[6].x + t[7].x)),
                       ((t[0].y + t[1].y) + (t[2].y + t[3].y)) + ((t[4].y + t[5].y) + (t[6].y + t[7].y)));
}
__device__ __forceinline__ float4 sum4x4(uint32_t addr, int pitch) {
    float4 t[4];
#pragma unroll
    for (int w = 0; w < 4; w++)
        asm volatile("ld.shared.v4.f32 {%0,%1,%2,%3}, [%4];" : "=f"(t[w].x), "=f"(t[w].y), "=f"(t[w].z), "=f"(t[w].w) : "r"(addr + w * pitch) : "memory");
    return make_float4((t[0].x + t[1].x) + (t[2].x + t[3].x), (t[0].y + t[1].y) + (t[2].y + t[3].y),
                       (t[0].z + t[1].z) + (t[2].z + t[3].z), (t[0].w + t[1].w) + (t[2].w + t[3].w));
}
__device__ __forceinline__ void sts64f(uint32_t addr, float x, float y) {
    asm volatile("st.shared.v2.f32 [%0], {%1,%2};" :: "r"(addr), "f"(x), "f"(y) : "memory");
}
__device__ __forceinline__ void lds128_if(uint4& v, uint32_t addr, bool pred) {
    asm volatile("{\n.reg .pred p;\nsetp.ne.u32 p, %5, 0;\n@p ld.shared.v4.u32 {%0,%1,%2,%3}, [%4];\n}"
                 : "+r"(v.x), "+r"(v.y), "+r"(v.z), "+r"(v.w) : "r"(addr), "r"((uint32_t)pred) : "memory");
}
__device__ __forceinline__ void sts128f(uint32_t addr, float x, float y, float z, float w) {
    asm volatile("st.shared.v4.f32 [%0], {%1,%2,%3,%4};" :: "r"(addr), "f"(x), "f"(y), "f"(z), "f"(w) : "memory");
}
template <int NJ>
__device__ __forceinline__ void load_o(uint32_t (&ob)[3 * NJ][2], int bh, int J0, int j) {
    float4 v[NJ][4];
    float2 l;
#pragma unroll 1
    for (int it = 0; it < SPIN_MAX; it++) {
#pragma unroll
        for (int J = 0; J < NJ; J++) {
#pragma unroll
            for (int e = 0; e < 4; e++) v[J][e] = ld_relaxed_f4(&g_st.oacc[oidx(bh, j)] + oidx(0, (J0 + J) * 16 + e * 4));
        }
        l = ld_relaxed_f2(g_st.lsum[bh]);
        bool ok = l.y == UPB;
#pragma unroll
        for (int J = 0; J < NJ; J++) {
#pragma unroll
            for (int e = 0; e < 4; e++) ok &= v[J][e].w == UPB;
        }
        if (__all_sync(0xffffffffu, ok)) break;
    }
    const float rl = __fdividef(1.0f, l.x);
#pragma unroll
    for (int J = 0; J < NJ; J++) {
        ob[3 * J][0] = pack_bf16(v[J][0].x * rl, v[J][1].x * rl);     ob[3 * J][1] = pack_bf16(v[J][2].x * rl, v[J][3].x * rl);
        ob[3 * J + 1][0] = pack_bf16(v[J][0].y * rl, v[J][1].y * rl); ob[3 * J + 1][1] = pack_bf16(v[J][2].y * rl, v[J][3].y * rl);
        ob[3 * J + 2][0] = pack_bf16(v[J][0].z * rl, v[J][1].z * rl); ob[3 * J + 2][1] = pack_bf16(v[J][2].z * rl, v[J][3].z * rl);
    }
}
__device__ __forceinline__ int near_side(uint32_t sb) {
    uint32_t v;
    asm volatile("ld.volatile.shared.u32 %0, [%1];" : "=r"(v) : "r"(sb + SM_SIDE) : "memory");
    return v;
}
__device__ __forceinline__ void poll_row(uint4& a, uint4& b, uint2& c, const void* pa, const void* pb, const void* pc, uint32_t sa, uint32_t sc,
                                         bool arrive, bool nap, uint32_t bar, Warm& warm) {
    asm volatile("{\n.reg .pred p, q, r, s;\n.reg .b32 m, n, it;\n"
                 "setp.ne.u32 r, %19, 0;\nsetp.ne.u32 s, %20, 0;\nmov.u32 it, 0;\n"
                 "POLL:\n"
                 "ld.relaxed.gpu.global.v4.u32 {%0,%1,%2,%3}, [%14];\n"
                 "ld.relaxed.gpu.global.v4.u32 {%4,%5,%6,%7}, [%15];\n"
                 "ld.relaxed.gpu.global.v2.u32 {%8,%9}, [%16];\n"
                 "add.u32 it, it, 1;\nsetp.ge.u32 q, it, %21;\n"
                 "mov.u32 m, 0;\nmma.sync.aligned.m16n8k8.row.col.f32.bf16.bf16.f32 {%10,%11,%12,%13}, {m,m}, {m}, {%10,%11,%12,%13};\n"
                 "st.shared.v4.u32 [%17], {%0,%1,%2,%3};\n"
                 "st.shared.v4.u32 [%17+512], {%4,%5,%6,%7};\n"
                 "st.shared.v2.u32 [%18], {%8,%9};\n"
                 "min.u32 m, %0, %1;\nmin.u32 m, m, %2;\nmin.u32 n, %3, %4;\nmin.u32 n, n, %5;\nmin.u32 m, m, %6;\nmin.u32 m, m, %7;\n"
                 "min.u32 n, n, m;\nmin.u32 m, %8, %9;\nmin.u32 m, m, n;\n"
                 "setp.ne.or.u32 p, m, 0, q;\n"
                 "vote.sync.all.pred p, p, 0xffffffff;\n"
                 "and.pred q, p, r;\n"
                 "bar.warp.sync 0xffffffff;\n"
                 "@q mbarrier.arrive.shared::cta.b64 _, [%22];\n"
                 "@p bra.uni DONE;\n"
                 "@s nanosleep.u32 500;\n"
                 "bra.uni POLL;\n"
                 "DONE:\n}"
                 : "=&r"(a.x), "=&r"(a.y), "=&r"(a.z), "=&r"(a.w), "=&r"(b.x), "=&r"(b.y), "=&r"(b.z), "=&r"(b.w), "=&r"(c.x), "=&r"(c.y),
                   "+f"(warm.c[0]), "+f"(warm.c[1]), "+f"(warm.c[2]), "+f"(warm.c[3])
                 : "l"(pa), "l"(pb), "l"(pc), "r"(sa), "r"(sc), "r"((uint32_t)arrive), "r"((uint32_t)nap), "n"(SPIN_MAX), "r"(bar) : "memory");
}
__device__ __forceinline__ void aux_sync() { asm volatile("bar.sync 1, 256;" ::: "memory"); }

__global__ void __launch_bounds__(NTHREADS, 1)
fused_decode_kernel(const __grid_constant__ Params p) {
    extern __shared__ __align__(1024) unsigned char smem[];
    const uint32_t sb = s2u(smem);
    const int tid = threadIdx.x, cta = blockIdx.x;
    if (tid < 32 && cta < NQ_CTAS) {
        asm volatile("{\n.reg .pred p;\nelect.sync _|p, 0xffffffff;\n"
                     "@p mbarrier.init.shared::cta.b64 [%2], 1;\n"
                     "@p fence.mbarrier_init.release.cluster;\n"
                     "@p mbarrier.arrive.expect_tx.shared::cta.b64 _, [%2], 61440;\n"
                     "@p cp.async.bulk.tensor.2d.shared::cluster.global.mbarrier::complete_tx::bytes [%0], [%1, {%3, %4}], [%2];\n"
                     "@p cp.async.bulk.tensor.2d.shared::cluster.global.mbarrier::complete_tx::bytes [%0+15360], [%1, {%3, %5}], [%2];\n"
                     "@p cp.async.bulk.tensor.2d.shared::cluster.global.mbarrier::complete_tx::bytes [%0+30720], [%1, {%3, %6}], [%2];\n"
                     "@p cp.async.bulk.tensor.2d.shared::cluster.global.mbarrier::complete_tx::bytes [%0+46080], [%1, {%3, %7}], [%2];\n}"
                     :: "r"(sb + SM_W), "l"(&p.wq), "r"(sb + BAR_WQ), "r"(cta * 48), "r"(0), "r"(160), "r"(320), "r"(480) : "memory");
    }
    const int warp = __shfl_sync(0xffffffffu, tid >> 5, 0), lane = tid & 31;
    constexpr int grid = NCTAS;
    const int g = lane >> 2, j = lane & 3;
    TS(0);
    if (tid == 160) {
        mbar_init(sb + BAR_WO, 1);
        mbar_init(sb + BAR_H, 1);
#pragma unroll
        for (int i = 0; i < 8 + 2 * NWORK * NPART; i++) mbar_init(sb + BAR_FW + i * 8, 1);
        sts32f(sb + SM_SIDE, 0.f);
        asm volatile("fence.mbarrier_init.release.cluster;" ::: "memory");
        asm volatile("fence.proxy.async.shared::cta;" ::: "memory");
    }
    __syncthreads();
    if (warp >= NAUX + NWORK) {
        const int fw = warp - (NAUX + NWORK), fi = ffn_slice(cta);
        if (fw == 0) {
            if (cta < NQ_CTAS) {
#pragma unroll
                for (int i = lane; i < STATE_V4; i += 32)
                    if (cta * STATE_V4 + i < (int)(sizeof(State) / 16)) reinterpret_cast<uint4*>(&g_st)[cta * STATE_V4 + i] = make_uint4(0u, 0u, 0u, 0u);
                __syncwarp();
                if (lane == 0) red_release(g_cnt_z);
            }
            TSW(2); wait_count(g_cnt_z, NQ_CTAS); TSW(29);
            asm volatile("bar.arrive 2, %0;" :: "n"((NWORK + 2) * 32) : "memory");
            fin_arrive<3>();
        } else {
            asm volatile("bar.sync 2, %0;" :: "n"((NWORK + 2) * 32) : "memory");
            uint32_t best[2] = {~0u, ~0u};
#pragma unroll 1
            for (int i = 0; i < NPROBE; i++) {
#pragma unroll
                for (int c = 0; c < 2; c++) {
                    uint32_t t0 = clock(), t1 = t0;
                    int v = 0;
                    draw(v, &g_st.hx.w[c][PROBE], lane == 0);
                    asm volatile("{\n.reg .pred p;\nsetp.ne.u32 p, %1, 0xffffffff;\n@p mov.u32 %0, %%clock;\n}" : "+r"(t1) : "r"(v) : "memory");
                    best[c] = min(best[c], t1 - t0);
                }
                __nanosleep(1000);
            }
            if (lane == 0) sts32f(sb + SM_SIDE, __uint_as_float((best[1] < best[0]) ^ SIDE_XOR));
        }
        int job = cta;
        auto sum_rows = [&](int row_end) {
#pragma unroll 1
            for (; job < 8 * min(row_end, RED0); job += NCTAS) {
                const int row = job >> 3, grp = (job & 7) * 8 + (lane & 7);
                wait_row(row, UPB);
                const float4* src = &g_ring[row % RING][lane >> 3][grp];
                float sx = 0.f, sy = 0.f, sz = 0.f;
#pragma unroll 1
                for (int i = 0; i < 2; i++, src += 64 * 64) {
                    float4 v[16];
#pragma unroll 1
                    for (int it = 0; it < SPIN_MAX; it++) {
                        bool ok = true;
#pragma unroll
                        for (int k = 0; k < 16; k++) v[k] = ld_relaxed_b128(src + k * 4 * 64);
#pragma unroll
                        for (int k = 0; k < 16; k++) ok &= v[k].w == (float)(row + 1);
                        if (__all_sync(0xffffffffu, ok)) break;
                    }
#pragma unroll
                    for (int k = 0; k < 16; k++) { sx += v[k].x; sy += v[k].y; sz += v[k].z; }
                }
#pragma unroll
                for (int o = 8; o < 32; o <<= 1) {
                    sx += __shfl_xor_sync(0xffffffffu, sx, o); sy += __shfl_xor_sync(0xffffffffu, sy, o); sz += __shfl_xor_sync(0xffffffffu, sz, o);
                }
                if (lane < 8) st_relaxed_b128(&g_st.oacc[oidx(row, grp)], sx, sy, sz, UPB);
            }
        };
        const int ho0 = lane / 20 * 256 + lane % 20 * 4, ho1 = (lane + 32) / 20 * 256 + (lane + 32) % 20 * 4, ho2 = 3 * 256 + 16 + 2 * lane;
        uint32_t wr[10] = {};
        float wsum = 0.f;
        if (is_g(cta) && fw == 0) {
#pragma unroll
            for (int i = 0; i < 10; i++) {
                const int w = 4 * lane + 128 * (i >> 2) + (i & 3) - (i >= 8 ? 2 * lane : 0);
                wr[i] = *reinterpret_cast<const uint32_t*>(p.wr + (w >> 4) * 32 + (w & 3) * 8 + ((w >> 1) & 6));
                wsum += lo_f(wr[i]) + hi_f(wr[i]);
            }
            wsum = warp_sum(wsum);
        }
        const int fb = lane >> 3, fg = lane & 7;
        if (fw == 0) {
#pragma unroll
            for (int i = lane; i < DM / 2; i += 32) sts32f(sb + SM_X + 4 * HPITCH + i * 4, __uint_as_float(0x3f803f80u));
        }
        Warm warm;
        float nmean = 0.f, rden = 0.f, sig = 0.f;
#pragma unroll 1
        for (int b = 0; b < NB; b++) {
            const bool ffn = b >= NB - 2;
            if (fw == 0) {
                sum_rows((b + 1) * NH);
                if (ffn) asm volatile("bar.arrive 8, 64;" ::: "memory");
            } else if (ffn) {
                asm volatile("bar.sync 8, 64;" ::: "memory");
                if (b == NB - 1) {
                    uint32_t t0 = 0, now;
#pragma unroll 1
                    for (int it = 0; it < SPIN_MAX; it++) {
                        t0 = ld_relaxed_u32(g_st.fw_time);
                        if (all(t0 != 0)) break;
                        __nanosleep(400);
                    }
                    asm volatile("fence.proxy.async.shared::cta;" ::: "memory");
#pragma unroll 1
                    for (int it = 0; it < SPIN_MAX; it++) {
                        asm volatile("mov.u32 %0, %%globaltimer_lo;" : "=r"(now));
                        if (all((int)(now - t0) >= FW_AT_NS)) break;
                    }
                    TSW(9);
                    uint32_t t = clock() + (is_f(cta) ? (fi & 1) * FW_STAG : FW_MID + (fi & 3) * (FW_GAP2 / 4));
#pragma unroll 1
                    for (int i = 0; i < 8; i++) {
                        const uint32_t bar = sb + BAR_FW + i * 8;
                        if (is_f(cta)) {
                            wait_clock(t, warm);
                            request_box(sb + SM_W + i * 10240, (i & 1) ? &p.wu : &p.wg, fi * 32, (i >> 1) * 160, bar, 10240);
                            t += FW_GAP;
                        } else if (is_g(cta)) {
                            wait_clock(t, warm);
                            asm volatile("{\n.reg .pred p;\nelect.sync _|p, 0xffffffff;\n"
                                         "@p mbarrier.arrive.expect_tx.shared::cta.b64 _, [%2], 6144;\n"
                                         "@p cp.async.bulk.tensor.4d.shared::cluster.global.mbarrier::complete_tx::bytes [%0], [%1, {%3, %4, %4, %5}], [%2];\n}"
                                         :: "r"(sb + SM_W + i * 6144), "l"(&p.wd), "r"(bar), "r"(fi * 16), "r"(0), "r"(i * 12) : "memory");
                            t += FW_GAP2;
                        }
                    }
                }
                if (is_f(cta)) {
                    const uint32_t* src = &g_st.hx.w[near_side(sb)][min(fb, b) * 256 + 96];
                    float4 m;
#pragma unroll 1
                    for (int it = 0; it < SPIN_MAX; it++) {
                        m = ld_relaxed_f4(src);
                        if (WARM & 2) warm();
                        if (__all_sync(0xffffffffu, m.y + m.w == 2 * (NCTAS - NE_CTAS))) break;
                        if (b < NB - 1) __nanosleep(500);
                    }
                    moments(m.x, m.z, m.x, m.z);
                    sts64f(sb + SM_RED + 5120 + fb * 8, m.x, m.z);
                }
            }
            if (fw == 0 && cta >= NE_CTAS) {
                const int lc = cta - NE_CTAS, col = lc * 32 + 2 * (lane & 15);
                const uint32_t xv = *reinterpret_cast<const uint32_t*>(p.x + b * DM + col);
                uint32_t* dst = &(ffn ? g_st.hx.w : g_st.lx.w + 2)[lane >> 4][(b & 1) * 128 + lc / 5 * 256 + lc % 5 * 16 + (col & 6) * 2 + ((col >> 3) & 3)];
                uint32_t part = sb + SM_RED + (lane & 15) * 8;
                wait_row(b * NH + 28, 1);
                float4 early;
#pragma unroll 1
                for (int it = 0; it < SPIN_MAX; it++) {
                    early = ld_relaxed_f4(&g_st.attn[b][col]);
                    if (__all_sync(0xffffffffu, early.y == NE_CTAS / 4 && early.w == NE_CTAS / 4)) break;
                }
                if (early.x != 1.2345f && lane == 0) TS2(6);
                CK(1, __float_as_uint(early.x));
                const float x0 = -(lo_f(xv) + early.x), x1 = -(hi_f(xv) + early.z);
                fin_sync<4>(after(after(288, x0), x1));
                CK(2, lds32(sb + SM_RED));
                const float2 late = sum8(part);
                const uint32_t hv = nonzero(pack_bf16(x0 - late.x, x1 - late.y));
                st_relaxed(dst, hv);
                if (HREP2 && ffn) st_relaxed(dst + 2048, hv);
                CK(3, 0);
                float m = lane < 16 ? lo_f(hv) + hi_f(hv) : fmaf(lo_f(hv), lo_f(hv), hi_f(hv) * hi_f(hv));
#pragma unroll
                for (int o = 1; o < 16; o <<= 1) m += __shfl_xor_sync(0xffffffffu, m, o);
                if ((lane & 14) == 0) red_f2(reinterpret_cast<float*>(&g_st.hx.w[lane & 1][b * 256 + 96 + (lane >> 4) * 2]), m, 1.f);
                fin_arrive<5>();
            }
            if (fw == 0 && (is_g(cta) || is_f(cta))) {
                const uint32_t* src = &(ffn ? g_st.hx.w : g_st.lx.w + 2)[near_side(sb) ^ (HREP2 && ffn && (HREP2 == 1 ? (fi & 1) : is_g(cta)) ? 3 : 0)][(b & 1) * 128];
                const uint32_t hrow = sb + SM_X + b * HPITCH;
                wait_sum(b == NB - 1 ? (const void*)&g_st.lx.w[near_side(sb) ^ 1][3 * 256] : g_st.lsum[b * NH + NH - 1], UPB, 100);
                wait_clock(clock() + HGATE * 2, warm);
                uint4 h0, h1;
                uint2 h2;
                poll_row(h0, h1, h2, src + ho0, src + ho1, src + ho2, hrow + lane * 16, hrow + 1024 + lane * 8, ffn && lane == 0, b < NB - 1, sb + BAR_H, warm);
                CK(4, h0.x);
                if (!LSTAT || is_g(cta)) {
                const uint32_t hw[10] = {h0.x, h0.y, h0.z, h0.w, h1.x, h1.y, h1.z, h1.w, h2.x, h2.y};
                float s1[2] = {}, s2[2] = {};
#pragma unroll
                for (int i = 0; i < 10; i++) {
                    const float v0 = lo_f(hw[i]), v1 = hi_f(hw[i]);
                    s1[i & 1] += v0 + v1;
                    s2[i & 1] = fmaf(v0, v0, fmaf(v1, v1, s2[i & 1]));
                }
                float m1 = s1[0] + s1[1], m2 = s2[0] + s2[1];
#pragma unroll
                for (int o = 16; o; o >>= 1) { m1 += __shfl_xor_sync(0xffffffffu, m1, o); m2 += __shfl_xor_sync(0xffffffffu, m2, o); }
                moments(m1, m2, m1, m2);
                {
                    float rr = 0.f;
#pragma unroll
                    for (int i = 0; i < 10; i++) rr = fmaf(lo_f(hw[i]), lo_f(wr[i]), fmaf(hi_f(hw[i]), hi_f(wr[i]), rr));
                    const float sg = bf16r(sigmoid_approx(bf16r((m1 * wsum - warp_sum(rr)) * m2)));
                    if (fb == b) { nmean = m1; rden = m2; sig = sg; }
                    __syncwarp();
                    if (ffn) {
                        const int gi = fi, yj = 2 * (fb & 1) + (fb >> 1);
                        uint32_t ypart = sb + SM_RED2 + yj * 128 + ((fg + 2 * yj) & 7) * 16;
                        __nv_bfloat16* out = p.out + fb * DM + gi * 16 + fg;
                        const float2 hw2 = lds64f(sb + SM_X + fb * HPITCH + ((gi >> 1) * 16 + (fg & 6) * 2 + (gi & 1) * 2) * 4);
                        const uint32_t w0 = __float_as_uint(hw2.x), w1 = __float_as_uint(hw2.y);
                        float nh0 = (fg & 1) ? hi_f(w0) : lo_f(w0), nh1 = (fg & 1) ? hi_f(w1) : lo_f(w1);
                        float ln0 = bf16r(bf16r(nmean - nh0) * rden), ln1 = bf16r(bf16r(nmean - nh1) * rden);
                        ln0 -= nh0; ln1 -= nh1;
                        pin(ypart); pin(out);
                        fin_sync<6>(after(after(after(288, sig), ln0), ln1));
                        CK(10, lds32(ypart));
                        const float4 ya = sum4x4(ypart, 512), yb = sum4x4(ypart + 2048, 512);
                        const float4 y = make_float4(ya.x + yb.x, ya.y + yb.y, ya.z + yb.z, ya.w + yb.w);
                        const float y0 = -(((fb & 1) ? y.y : y.x) + __shfl_xor_sync(0xffffffffu, (fb & 1) ? y.x : y.y, 8));
                        const float y1 = -(((fb & 1) ? y.w : y.z) + __shfl_xor_sync(0xffffffffu, (fb & 1) ? y.z : y.w, 8));
                        const uint32_t ov = pack_bf16(fmaf(y0, sig, ln0), fmaf(y1, sig, ln1));
                        if (b == NB - 1) {
                            asm volatile("st.global.u16 [%0], %1;" :: "l"(out), "h"((unsigned short)(ov & 0xffffu)) : "memory");
                            asm volatile("st.global.u16 [%0], %1;" :: "l"(out + 8), "h"((unsigned short)(ov >> 16)) : "memory");
                        }
                        CK(11, 0);
                        if (lane == 0) TS2(13);
                    }
                }
                }
            }
            if (is_f(cta) && ffn) {
                const int ks = (2 * fi + fw) % 12;
                const int far = FARFIRST ? near_side(sb) ^ 1 : 0;
                uint32_t* dst = &g_st.ax[ks >> 2].w[(~b & 1) * 2 + far][ALINE ? (fi / 6) * 128 + (ks & 3) * 32 + fb * 8 + (fg & 1) * 4 + ((fg >> 1) ^ (ks & 1)) :
                                                                        ((fi / 6) * 32 + ((ks & 1) * 4 + fb) * 4 + (fg & 3)) * 4 + (ks & 2) + (fg >> 2)];
                uint32_t* dst2 = dst + (far ? -1024 : 1024);
                uint32_t part = sb + SM_RED + fw * 2560 + fb * 128 + ((fg + (fb & 2)) & 7) * 16;
                uint32_t psum = sb + SM_RED + fw * 2560 + 4 * 128 + ((fg + 4) & 7) * 16;
                pin(dst); pin(part); pin(psum);
                asm volatile("bar.sync 4, 320;" ::: "memory");
                CK(6, lds32(part));
                const float4 d = sum4x4(part, 640), cs = sum4x4(psum, 640);
                const float2 mo = lds64f(sb + SM_RED + 5120 + fb * 8);
                nmean = mo.x; rden = mo.y;
                const float g0 = fmaf(nmean, cs.x, -d.x), g1 = fmaf(nmean, cs.y, -d.y), ke = rden * -1.4426950408889634f, r2 = rden * rden;
                const float p0 = g0 * fmaf(-nmean, cs.z, d.z) * r2, p1 = g1 * fmaf(-nmean, cs.w, d.w) * r2;
                const uint32_t av = nonzero(pack_bf16(p0 * rcp_approx(1.0f + ex2_approx(g0 * ke)), p1 * rcp_approx(1.0f + ex2_approx(g1 * ke))));
                st_relaxed(dst, av);
                st_relaxed(dst2, av);
                CK(7, 0);
            }
        }
        warm.done(sb + SM_MISC);
        if (cta == 0 && tid == (NAUX + NWORK) * 32) { g_work[0] = 0; g_work[32] = 0; g_cnt_z[0] = 0; }
        return;
    }
    if (warp >= NAUX) {
        const int wk = warp - NAUX;
        const uint32_t bar = sb + BAR_KV + wk * (NPART * 8);
        const uint32_t buf = sb + SM_KV + wk * TILE_BYTES;
        uint64_t pol;
        asm volatile("createpolicy.fractional.L2::evict_first.b64 %0, 1.0;" : "=l"(pol));
        const int nstatic = NWORK * grid;
        constexpr int POOL0 = NUNITS - NPOOL;
        int uk = wk * grid + cta;
        spin_ns(K0_DELAY_NS);
        request_tile(buf, &p.k, uk, bar, pol);
        if (wk == 0) {
            spin_ns(WO_AT_NS - K0_DELAY_NS);
#pragma unroll 1
            for (int i = 0; i < (cta < NE_CTAS ? 5 : 4); i++)
                request_box(sb + SM_A + i * 12288, &p.wo, cta < NE_CTAS ? (cta & 3) * 160 + i * 32 : (cta - NE_CTAS) * 32,
                            (cta < NE_CTAS ? cta >> 2 : 28 + i) * DH, sb + BAR_WO, i ? 0 : cta < NE_CTAS ? 61440 : 49152);
        }
        uint32_t koff[3], voff[3];
        {
            const int r = lane & 7, hf = (lane >> 3) & 1;
            const int kkey = hf ? 8 + (r ^ 1) : r;
            const int vh = lane >> 4;
            const int vkey = ((r & 1) ? 8 : 0) + (vh ? (r ^ 1) : r);
#pragma unroll
            for (int b = 0; b < 3; b++) {
                const int rk = 3 * kkey + b, rv = 3 * vkey + b;
                koff[b] = buf + rk * 128 + (((lane >> 4) ^ (rk & 7)) << 4);
                voff[b] = buf + rv * 128 + ((hf ^ (rv & 7)) << 4);
            }
        }
        uint32_t phase = 0, kbar = bar;
        uint4 qf[6];
        auto load_q = [&](int u) {
            const uint32_t* q = &g_early[u / UPB].q[j * 4];
#pragma unroll
            for (int i = 0; i < 6; i++) qf[i] = ld_relaxed_v4(q + i * 16);
        };
        load_q(uk);
        int uq[LAG];
        uint32_t sq[LAG];
#pragma unroll
        for (int i = 0; i < LAG; i++) { uq[i] = -1; sq[i] = 0; }
        uint4 mv = make_uint4(0u, 0u, 0u, 0u);
        float freed = UPB;
        while (true) {
            const int uv = uq[0];
            uint32_t sv = sq[0];
#pragma unroll
            for (int i = 0; i + 1 < LAG; i++) { uq[i] = uq[i + 1]; sq[i] = sq[i + 1]; }
            uq[LAG - 1] = uk;
            if (uk < NUNITS) {
                PH(7);
#pragma unroll 1
                for (int it = 0; it < SPIN_MAX; it++) {
                    uint32_t lo = 0xffffffffu;
#pragma unroll
                    for (int i = 0; i < 6; i++) lo = min(min(lo, min(qf[i].x, qf[i].y)), min(qf[i].z, qf[i].w));
                    if (__all_sync(0xffffffffu, lo != 0)) break;
                    __nanosleep(250);
                    load_q(uk);
                }
#pragma unroll
                for (int t = 0; t < NPART; t++) mbar_wait(kbar + t * 8, phase);
                phase ^= 1;
                PH(0); ARR();
                TSI(0, 16); TSI(1, 18);
                float acc[2][4][4] = {};
#pragma unroll
                for (int ks = 0; ks < 12; ks++) {
                    const uint4 qq = qf[ks >> 1];
                    const uint32_t b0 = (ks & 1) ? qq.z : qq.x, b1 = (ks & 1) ? qq.w : qq.y;
#pragma unroll
                    for (int mt = 0; mt < 4; mt++) {
                        uint32_t a[4];
                        ldsm4(a, (koff[ks >> 2] ^ ((ks & 3) << 5)) + mt * 6144);
                        mma16816(acc[ks & 1][mt], a, b0, b1);
                    }
                }
                PH(1);
                TSI(0, 17); TSI(1, 19);
                if (uv < NUNITS && kbar == bar) request_tile(buf, uv >= 0 ? &p.v : &p.k, uv >= 0 ? uv : uk + (wk < NSPARE ? 2 : 1) * nstatic, bar, pol);
                const float sa = sel4(j, acc[0][0][0], acc[0][1][0], acc[0][2][0], acc[0][3][0]) + sel4(j, acc[1][0][0], acc[1][1][0], acc[1][2][0], acc[1][3][0]);
                const float sc = sel4(j, acc[0][0][2], acc[0][1][2], acc[0][2][2], acc[0][3][2]) + sel4(j, acc[1][0][2], acc[1][1][2], acc[1][2][2], acc[1][3][2]);
                const uint32_t raw = pack_bf16(sa, sc);
                const float scale = -0.07216878364870322f;
                const uint32_t sk = pack_bf16(lo_f(raw) * scale, hi_f(raw) * scale);
                sq[LAG - 1] = sk;
                if (uk >= POOL0) st_relaxed(&g_st.score[uk - POOL0][lane], sk ? sk : 0x80008000u);
                int a = (int)(sk << 16), b = (int)(sk & 0xffff0000u);
                a ^= (a >> 31) & 0x7fff0000; b ^= (b >> 31) & 0x7fff0000;
                const int mx = __reduce_max_sync(0xffffffffu, max(a, b));
                if (lane == 0) st_relaxed(&g_early[uk / UPB].umax[uk % UPB], (uint32_t)mx | 1u);
            }
            if (uv < 0) {
                if (wk < NSPARE) {
                    const int d = uk < nstatic ? SM_W - SM_KV : SM_KV - SM_W;
#pragma unroll
                    for (int b = 0; b < 3; b++) koff[b] += d;
                    kbar = uk < nstatic ? bar + NWORK * NPART * 8 : bar;
                    phase = uk >= nstatic;
                }
                uk += nstatic;
                load_q(uk);
                continue;
            }
            if (uv >= NUNITS) break;
            const int bh = uv / UPB;
#pragma unroll 1
            for (int it = 0; it < SPIN_MAX; it++) {
                if (__all_sync(0xffffffffu, (mv.x & mv.y & mv.z & mv.w & 1u) && (uv < POOL0 || sv != 0) && freed == UPB)) break;
                mv = ld_relaxed_v4(&g_early[bh].umax[lane * 4]);
                if (bh >= RING && bh < RED0) freed = __uint_as_float(ld_relaxed_u32(&g_st.oacc[oidx(bh - RING, (lane & 7) * 8)].w));
                if (uv >= POOL0) sv = ld_relaxed_u32(&g_st.score[uv - POOL0][lane]);
            }
            PH(2);
            int un = NUNITS, vn = 0;
            draw(un, g_work, uk < NUNITS && lane == 0);
            uint32_t tdraw;
            asm volatile("mov.u32 %0, %%globaltimer_lo;" : "=r"(tdraw));
            draw(vn, g_work + 32, uq[0] >= POOL0 && lane == 0);
            int mx = __reduce_max_sync(0xffffffffu, max(max((int)mv.x, (int)mv.y), max((int)mv.z, (int)mv.w))) & 0xffff0000;
            mx ^= (mx >> 31) & 0x7fff0000;
            const float m = __int_as_float(mx);
            const float l2e = 1.4426950408889634f;
            const uint32_t pp = pack_bf16(exp2f((lo_f(sv) - m) * l2e), exp2f((hi_f(sv) - m) * l2e));
            uint32_t pb[8];
#pragma unroll
            for (int t = 0; t < 4; t++) {
                pb[2 * t] = __shfl_sync(0xffffffffu, pp, 8 * j + t);
                pb[2 * t + 1] = __shfl_sync(0xffffffffu, pp, 8 * j + 4 + t);
            }
            float lacc[4] = {};
            const uint32_t ones[4] = {0x3f803f80u, 0x3f803f80u, 0x3f803f80u, 0x3f803f80u};
#pragma unroll
            for (int t = 0; t < 4; t++) mma16816(lacc, ones, pb[2 * t], pb[2 * t + 1]);
            if (uv < nstatic) {
                asm volatile("bar.sync 2, %0;" :: "n"((NWORK + 2) * 32) : "memory");
                TSW(3);
            }
            const int grp = 16 * j + 4 * (g & 1) + (g >> 1);
            uint32_t mode = (bh >= RED0) + (bh >= NBH - 4);
            float tag = mode ? 1.f : (float)(bh + 1), tag2 = tag;
            void* dst = mode == 0 ? (void*)&g_ring[bh % RING][uv % UPB][grp] :
                        mode == 1 ? (void*)&g_st.oacc[oidx(bh, grp)] : (void*)&g_st.ox[uv % OREP].w[0][oidx(bh & 3, grp) * 4];
            if (mode == 2 && lane < 2) red_f2(reinterpret_cast<float*>(&g_st.lx.w[lane][(bh & 3) * 256]), lacc[0], 1.f);
            un = __shfl_sync(0xffffffffu, un, 0) + (LAG + 1) * nstatic;
            vn = __shfl_sync(0xffffffffu, vn, 0);
            if (uq[0] >= POOL0) uq[0] = POOL0 + vn;
            if (vn == FW_TICKET && lane == 0) st_relaxed(g_st.fw_time, tdraw | 1u);
            if (EARLY_LOOK && uq[0] < NUNITS && un >= NUNITS) {
                mv = ld_relaxed_v4(&g_early[uq[0] / UPB].umax[lane * 4]);
                if (uq[0] < RED0 * UPB) freed = 0.f;
                if (uq[0] >= POOL0) sq[0] = ld_relaxed_u32(&g_st.score[uq[0] - POOL0][lane]);
            }
            pin(dst); pin(mode); pin(tag); pin(tag2); pin(voff[0]); pin(voff[1]); pin(voff[2]);
            PH(3);
            float acc[12][4] = {};
#pragma unroll
            for (int t = 0; t < 4; t++) {
                if (t % (4 / NPART) == 0) mbar_wait(bar + t / (4 / NPART) * 8, phase);
                if (t == 4 - 4 / NPART) { PH(4); ARR(); CK(12, lds32(buf)); }
#pragma unroll
                for (int mt = 0; mt < 12; mt++) {
                    uint32_t a[4];
                    ldsm4t(a, (voff[mt >> 2] ^ ((mt & 3) << 5)) + t * 6144);
                    mma16816(acc[mt], a, pb[2 * t], pb[2 * t + 1]);
                }
            }
            phase ^= 1;
            PH(5);
            if (lane == 0) PROG(un);
            if (un < NUNITS || uq[0] < NUNITS) request_tile(buf, un < NUNITS ? &p.k : &p.v, un < NUNITS ? un : uq[0], bar, pol);
            if (un < NUNITS || uq[0] < NUNITS) CK(11, 0);
            float o[6];
#pragma unroll
            for (int e = 0; e < 6; e++) {
                const int q = e % 3, c = (e / 3) * 2;
                o[e] = sel4(j, acc[q][c], acc[3 + q][c], acc[6 + q][c], acc[9 + q][c]);
            }
            put_groups(dst, mode, o, tag, tag2);
            CK(13, 0);
            if (un < NUNITS) load_q(un);
            if (lane == 0) red_f2(&g_st.lsum[bh][0].x, lacc[0], 1.f);
            PH(6);
            if (uq[0] >= NUNITS && un >= NUNITS) break;
            uk = un;
            if (uq[0] < NUNITS && (!EARLY_LOOK || un < NUNITS)) {
                const int nb = uq[0] / UPB;
                mv = ld_relaxed_v4(&g_early[nb].umax[lane * 4]);
                freed = nb >= RING && nb < RED0 ? __uint_as_float(ld_relaxed_u32(&g_st.oacc[oidx(nb - RING, (lane & 7) * 8)].w)) : UPB;
                if (uq[0] >= POOL0) sq[0] = ld_relaxed_u32(&g_st.score[uq[0] - POOL0][lane]);
            }
        }
        TSW(4 + wk);
        return;
    }

    __nv_bfloat16* xs = reinterpret_cast<__nv_bfloat16*>(smem + SM_X);
    float* red = reinterpret_cast<float*>(smem + SM_RED);
    const int frow = (lane & 7) + ((lane >> 4) << 3), fcol = (lane >> 3) & 1;
    const uint32_t f32b = sb + (frow * 2 + (fcol ^ ((frow >> 2) & 1))) * 16;
    const uint32_t f64b = sb + (frow * 4 + (fcol ^ ((frow >> 1) & 3))) * 16;
    if (cta < NQ_CTAS) {
        uint2 xr[5];
        if (warp < NB) {
#pragma unroll
            for (int i = 0; i < 5; i++) xr[i] = *reinterpret_cast<const uint2*>(p.x + warp * DM + i * 128 + lane * 4);
        }
        TS(26);
        if (warp < NB) {
            float v[20];
#pragma unroll
            for (int i = 0; i < 5; i++) {
                v[4 * i] = lo_f(xr[i].x); v[4 * i + 1] = hi_f(xr[i].x); v[4 * i + 2] = lo_f(xr[i].y); v[4 * i + 3] = hi_f(xr[i].y);
            }
            layernorm20(v);
#pragma unroll
            for (int i = 0; i < 5; i++)
                *reinterpret_cast<uint2*>(xs + warp * XPITCH + i * 128 + lane * 4) =
                    make_uint2(pack_bf16(v[4 * i], v[4 * i + 1]), pack_bf16(v[4 * i + 2], v[4 * i + 3]));
        }
        TS(27);
        aux_sync();
        mbar_wait(sb + BAR_WQ, 0);
        TS(1);
        const uint32_t xfrag = sb + SM_X + ((g & 3) * XPITCH + 2 * j) * 2;
        float acc[3][4] = {};
#pragma unroll
        for (int s = 0; s < 5; s++) {
            const int ks = warp * 5 + s;
            const uint32_t b0 = lds32(xfrag + ks * 32), b1 = lds32(xfrag + ks * 32 + 16);
            const int row = ks * 16 + frow;
#pragma unroll
            for (int mt = 0; mt < 3; mt++) {
                uint32_t a[4];
                ldsm4t(a, sb + SM_W + (row * 6 + 2 * mt + fcol) * 16);
                mma16816(acc[mt], a, b0, b1);
            }
        }
        if (j < 2) {
#pragma unroll
            for (int mt = 0; mt < 3; mt++) {
                *reinterpret_cast<float2*>(red + (warp * 48 + mt * 16 + g) * 4 + 2 * j) = make_float2(acc[mt][0], acc[mt][1]);
                *reinterpret_cast<float2*>(red + (warp * 48 + mt * 16 + 8 + g) * 4 + 2 * j) = make_float2(acc[mt][2], acc[mt][3]);
            }
        }
        aux_sync();
        if (tid < 96) {
            const int b = tid & 3, cp = tid >> 2;
            float s0 = 0.f, s1 = 0.f;
#pragma unroll
            for (int w = 0; w < 8; w++) { s0 += red[(w * 48 + 2 * cp) * 4 + b]; s1 += red[(w * 48 + 2 * cp + 1) * 4 + b]; }
            const int h = cta >> 2, d = (cta & 3) * 48 + 2 * cp;
            const int ch = d >> 3, jj = (d & 7) >> 1;
            st_relaxed(&g_early[b * NH + h].q[(ch >> 2) * 16 + jj * 4 + (ch & 3)], pack_neg(s0, s1));
        }
        TS(28);
    }
    if (warp >= 4 && warp < 4 + NSPARE) {
        uint64_t pol;
        asm volatile("createpolicy.fractional.L2::evict_first.b64 %0, 1.0;" : "=l"(pol));
        spin_ns(cta < NQ_CTAS ? SPARE_NS : WO_AT_NS + SPARE_NS);
        asm volatile("fence.proxy.async.shared::cta;" ::: "memory");
        request_tile(sb + SM_W + (warp - 4) * TILE_BYTES, &p.k, (NWORK + warp - 4) * grid + cta, sb + BAR_KV + (NWORK + warp - 4) * (NPART * 8), pol);
    }
    fin_sync<3>();
    mbar_wait(sb + BAR_WO, 0);
    TS(7);
    uint32_t part = sb + SM_RED + (warp * 32 + 8 * j + g) * 4;

#pragma unroll 1
    for (int b = 0; b < NB; b++) {
        if (cta >= NE_CTAS) {
            uint32_t a[6][2][4];
#pragma unroll
            for (int s = 0; s < 6; s++) {
#pragma unroll
                for (int mt = 0; mt < 2; mt++) ldsm4t(a[s][mt], (f64b ^ (mt * 32)) + SM_A + (warp * 6 + s) * 1024);
            }
            const int bh = b * NH + 28 + (warp >> 1);
            const int side = near_side(sb) ^ 1;
            const void* osrc[OREP];
#pragma unroll
            for (int c = 0; c < OREP; c++)
                osrc[c] = b == NB - 1 ? (const void*)&g_st.ox[c].w[side][oidx(bh & 3, (warp & 1) * 32 + lane) * 4] : &g_st.oacc[oidx(bh, (warp & 1) * 32 + lane)];
            const void* lsrc = b == NB - 1 ? (const void*)&g_st.lx.w[side][(bh & 3) * 256] : g_st.lsum[bh];
            wait_row_o(bh, 1);
            const float rl = rcp_approx(wait_sum(lsrc, UPB)) * (b == NB - 1 ? 1.f : 1.f / OREP), full = b == NB - 1 ? UPB : UPB * OREP;
            float4 ov;
            float px, py, pz;
            Warm warm;
#pragma unroll 1
            for (int it = 0; it < SPIN_MAX; it++) {
                float4 oc[OREP];
#pragma unroll
                for (int c = 0; c < OREP; c++) oc[c] = ld_relaxed_f4(osrc[c]);
                if (WARM & 8) warm();
                ov = oc[0];
#pragma unroll
                for (int c = 1; c < OREP; c++) { ov.x += oc[c].x; ov.y += oc[c].y; ov.z += oc[c].z; ov.w += oc[c].w; }
                ov.x *= rl; ov.y *= rl; ov.z *= rl;
                px = __shfl_xor_sync(0xffffffffu, ov.x, 4); py = __shfl_xor_sync(0xffffffffu, ov.y, 4); pz = __shfl_xor_sync(0xffffffffu, ov.z, 4);
                if (all(ov.w == full)) break;
            }
            CK(0, __float_as_uint(ov.x));
            if (ov.x != 1.2345f && warp == 7) TSW(14);
            const uint32_t w[3] = {pack_bf16(ov.x, px), pack_bf16(ov.y, py), pack_bf16(ov.z, pz)};
            float acc[2][2][4] = {};
#pragma unroll
            for (int s = 0; s < 6; s++) {
                const uint32_t b0 = __shfl_sync(0xffffffffu, w[s % 3], (s / 3) * 16 + j);
                const uint32_t b1 = __shfl_sync(0xffffffffu, w[s % 3], (s / 3) * 16 + 8 + j);
#pragma unroll
                for (int mt = 0; mt < 2; mt++) mma16816(acc[mt][s & 1], a[s][mt], b0, b1);
            }
            sts32f(part, sel4(j, acc[0][0][0] + acc[0][1][0], acc[0][0][2] + acc[0][1][2], acc[1][0][0] + acc[1][1][0], acc[1][0][2] + acc[1][1][2]));
            CK(1, 0);
            fin_arrive<4>();
            warm.done(sb + SM_MISC);
            fin_sync<5>();
            if (cta < NE_CTAS + 4 && tid < 56) reinterpret_cast<uint4*>(&g_early[b * NH + 28 + cta - NE_CTAS])[tid] = make_uint4(0u, 0u, 0u, 0u);
        } else {
            const int bh = b * NH + (cta >> 2);
            if (warp == 0) wait_row_o(bh, UPB);
            aux_sync();
            if (warp < 5) {
                uint32_t ob[12][2];
                load_o<4>(ob, bh, 0, j);
                float acc[2][2][4] = {};
#pragma unroll
                for (int ks = 0; ks < 12; ks++) {
#pragma unroll
                    for (int mt = 0; mt < 2; mt++) {
                        uint32_t a[4];
                        ldsm4t(a, (f64b ^ (mt * 32)) + SM_A + warp * 12288 + ks * 1024);
                        mma16816(acc[mt][ks & 1], a, ob[ks][0], ob[ks][1]);
                    }
                }
                red_f2(&g_st.attn[b][(cta & 3) * 160 + warp * 32 + 8 * j + g].x,
                       sel4(j, acc[0][0][0] + acc[0][1][0], acc[0][0][2] + acc[0][1][2], acc[1][0][0] + acc[1][1][0], acc[1][0][2] + acc[1][1][2]), 1.f);
                TS(8);
            } else if (warp > 5 && (cta & 3) == 0 && tid - 192 < 56) {
                reinterpret_cast<uint4*>(&g_early[bh])[tid - 192] = make_uint4(0u, 0u, 0u, 0u);
            }
        }
        if (b < NB - 2) continue;

        if (is_f(cta)) {
            uint32_t ga[10][2][4];
            uint4 hv[5] = {};
            const uint32_t hfrag = sb + SM_X + min(g, 4) * HPITCH + ((warp >> 1) * 80 + 4 * j) * 4;
#pragma unroll
            for (int s = 0; s < 5; s++) lds128_if(hv[s], hfrag + s * 64, b == NB - 1);
            if (b == NB - 1) mbar_wait(sb + BAR_FW + warp * 8, 0);
            if (warp == 7) TSW(10);
            CK(12, lds32(sb + SM_W));
#pragma unroll
            for (int s = 0; s < 10; s++) {
#pragma unroll
                for (int mt = 0; mt < 2; mt++) ldsm4t(ga[s][mt], (f64b ^ (mt * 32)) + SM_W + (warp * 10 + s) * 1024);
            }
            const uint32_t gpart = sb + SM_RED + (warp >> 1) * 640 + j * 256 + ((g + 2 * j) & 7) * 16 + (warp & 1) * 8;
            mbar_wait(sb + BAR_H, b & 1);
#pragma unroll
            for (int s = 0; s < 5; s++) lds128_if(hv[s], hfrag + s * 64, g == b);
            CK(4, hv[0].x);
            float acc[2][2][4] = {};
#pragma unroll
            for (int s = 0; s < 10; s++) {
#pragma unroll
                for (int mt = 0; mt < 2; mt++)
                    mma16816(acc[mt][s & 1], ga[s][mt], (s & 1) ? hv[s >> 1].z : hv[s >> 1].x, (s & 1) ? hv[s >> 1].w : hv[s >> 1].y);
            }
#pragma unroll
            for (int mt = 0; mt < 2; mt++) {
                if (j < 3) sts64f(gpart + mt * 2560, acc[mt][0][0] + acc[mt][1][0], acc[mt][0][2] + acc[mt][1][2]);
                if (j < 2) sts64f(gpart + mt * 2560 + 128, acc[mt][0][1] + acc[mt][1][1], acc[mt][0][3] + acc[mt][1][3]);
            }
            CK(5, 0);
            asm volatile("bar.arrive 4, 320;" ::: "memory");
        } else if (is_g(cta)) {
            const uint32_t* asrc = &g_st.ax[0].w[(~b & 1) * 2 + near_side(sb)][ALINE ? warp * 128 + ((g >> 2) * 2 + (j >> 1)) * 32 + (g & 3) * 8 + (j & 1) * 4 : (warp * 32 + lane) * 4];
            const uint32_t ypart = sb + SM_RED2 + warp * 512 + j * 128 + ((g + 2 * j) & 7) * 16;
            uint32_t wb[12][4];
            if (b == NB - 1) mbar_wait(sb + BAR_FW + warp * 8, 0);
            if (warp == 7) TSW(11);
            CK(13, lds32(sb + SM_W));
            {
                const int jj = (lane & 7) >> 1, q = jj >> 1, hi = lane >> 4;
                const uint32_t base = sb + SM_W + warp * 6144 + q * 512 + ((hi ^ q) * 4 + (jj & 1) * 2 + (lane & 1)) * 32 + ((fcol ^ hi ^ q) << 4);
#pragma unroll
                for (int s = 0; s < 12; s++) ldsm4t(wb[s], base + (s >> 2) * 2048 + (s & 1) * 1024 + (s & 2) * 128);
            }
            mbar_wait(sb + BAR_H, b & 1);
            uint4 va[3];
            Warm warm;
#pragma unroll 1
            for (int it = 0; it < SPIN_MAX; it++) {
                uint32_t lo = 0xffffffffu;
#pragma unroll
                for (int i = 0; i < 3; i++) va[i] = ld_relaxed_v4(asrc + i * 4096);
                if (WARM & 16) warm();
#pragma unroll
                for (int i = 0; i < 3; i++) lo = min(min(lo, min(va[i].x, va[i].y)), min(va[i].z, va[i].w));
                if (all(lo != 0)) break;
            }
            CK(8, va[0].x);
            if (va[0].x != 0x12345 && warp == 7) TSW(15);
            float acc[GCH][4] = {};
#pragma unroll
            for (int s = 0; s < 12; s++) {
                const uint4 v = va[s >> 2];
                mma16816(acc[s % GCH], wb[s], (s & 2) ? v.z : v.x, (s & 2) ? v.w : v.y);
            }
            float y[4];
#pragma unroll
            for (int e = 0; e < 4; e++) {
                y[e] = j < 2 ? acc[0][e] + acc[2][e] : acc[1][e] + acc[3][e];
                if (GCH == 6) y[e] += j < 2 ? acc[GCH - 2][e] : acc[GCH - 1][e];
            }
            sts128f(ypart, y[0], y[1], y[2], y[3]);
            CK(9, 0);
            fin_arrive<6>();
            warm.done(sb + SM_MISC);
        }
    }
}

typedef CUresult (*EncodeFn)(CUtensorMap*, CUtensorMapDataType, cuuint32_t, void*, const cuuint64_t*, const cuuint64_t*,
                             const cuuint32_t*, const cuuint32_t*, CUtensorMapInterleave, CUtensorMapSwizzle,
                             CUtensorMapL2promotion, CUtensorMapFloatOOBfill);

CUtensorMap make_map(EncodeFn enc, void* ptr, uint64_t cols, uint64_t rows, uint32_t bcols, uint32_t brows,
                     CUtensorMapSwizzle sw, CUtensorMapL2promotion promo) {
    CUtensorMap m;
    const cuuint64_t dims[2] = {cols, rows};
    const cuuint64_t strides[1] = {cols * 2};
    const cuuint32_t box[2] = {bcols, brows};
    const cuuint32_t es[2] = {1, 1};
    enc(&m, CU_TENSOR_MAP_DATA_TYPE_BFLOAT16, 2, ptr, dims, strides, box, es, CU_TENSOR_MAP_INTERLEAVE_NONE, sw, promo,
        CU_TENSOR_MAP_FLOAT_OOB_FILL_NONE);
    return m;
}

}

extern "C" void kernel_launch(void* const* d_in, const int* in_sizes, int n_in, void* d_out, int out_size) {
    (void)in_sizes; (void)n_in; (void)out_size;
    static EncodeFn enc = nullptr;
    static int sms = 0;
    if (!enc) {
        cudaDriverEntryPointQueryResult qr;
        cudaGetDriverEntryPoint("cuTensorMapEncodeTiled", (void**)&enc, cudaEnableDefault, &qr);
        int dev = 0;
        cudaGetDevice(&dev);
        cudaDeviceGetAttribute(&sms, cudaDevAttrMultiProcessorCount, dev);
        cudaFuncSetAttribute(fused_decode_kernel, cudaFuncAttributeMaxDynamicSharedMemorySize, SM_TOTAL);
    }
    if (sms < NCTAS) return;
    const CUtensorMapL2promotion WPROMO = CU_TENSOR_MAP_L2_PROMOTION_L2_128B;
#define GPROMO 2
#define DPROMO 2
    Params p;
    p.k = make_map(enc, d_in[1], 64, (uint64_t)NBH * SK * 3, 64, TILE_ROWS / NPART, CU_TENSOR_MAP_SWIZZLE_128B, CU_TENSOR_MAP_L2_PROMOTION_NONE);
    p.v = make_map(enc, d_in[2], 64, (uint64_t)NBH * SK * 3, 64, TILE_ROWS / NPART, CU_TENSOR_MAP_SWIZZLE_128B, CU_TENSOR_MAP_L2_PROMOTION_NONE);
    p.wq = make_map(enc, d_in[3], NH * DH, DM, 48, 160, CU_TENSOR_MAP_SWIZZLE_NONE, WPROMO);
    p.wo = make_map(enc, d_in[4], DM, NH * DH, 32, DH, CU_TENSOR_MAP_SWIZZLE_64B, WPROMO);
    p.wg = make_map(enc, d_in[7], FF, DM, 32, 160, CU_TENSOR_MAP_SWIZZLE_64B, (CUtensorMapL2promotion)GPROMO);
    p.wu = make_map(enc, d_in[8], FF, DM, 32, 160, CU_TENSOR_MAP_SWIZZLE_64B, (CUtensorMapL2promotion)GPROMO);
    {
        const cuuint64_t dims[4] = {DM, 2, 8, FF / 16}, strides[3] = {8 * DM * 2, DM * 2, 16 * DM * 2};
        const cuuint32_t box[4] = {16, 2, 8, 12}, es[4] = {1, 1, 1, 1};
        enc(&p.wd, CU_TENSOR_MAP_DATA_TYPE_BFLOAT16, 4, d_in[9], dims, strides, box, es, CU_TENSOR_MAP_INTERLEAVE_NONE,
            CU_TENSOR_MAP_SWIZZLE_32B, (CUtensorMapL2promotion)DPROMO, CU_TENSOR_MAP_FLOAT_OOB_FILL_NONE);
    }
    p.x = (const __nv_bfloat16*)d_in[0];
    p.wr = (const __nv_bfloat16*)d_in[6];
    p.out = (__nv_bfloat16*)d_out;
    fused_decode_kernel<<<NCTAS, NTHREADS, SM_TOTAL, cudaStreamPerThread>>>(p);
}
```

```cpp
#include <cuda_runtime.h>
#include <cuda_bf16.h>
#include <cuda.h>
#include <stdint.h>

namespace {

constexpr int NB = 4, NH = 32, SK = 8192, DH = 192, DM = 640, FF = 1536;
constexpr int NBH = NB * NH;
constexpr int TILE = 64;
constexpr int UPB = SK / TILE;
constexpr int NUNITS = NBH * UPB;
constexpr int TILE_BYTES = TILE * DH * 2;
constexpr int TILE_ROWS = TILE * 3;
constexpr int NCTAS = 132;
constexpr int NQ_CTAS = 128;
constexpr int NE_CTAS = 112;
__host__ __device__ constexpr bool is_f(int cta) { return cta < NE_CTAS && cta % 14 < 11 && !(cta & 1); }
__host__ __device__ constexpr bool is_g(int cta) { return cta < NE_CTAS && cta % 14 < 11 && (cta & 1); }
__host__ __device__ constexpr int ffn_slice(int cta) { return cta / 14 * ((cta & 1) ? 5 : 6) + cta % 14 / 2; }

#define NWORK 2
#define NSPARE 1
#define LAG 2
#define NPOOL 768
#define RED0 116
#define RING 12
#define OREP 3
#define K0_DELAY_NS 1200
#define WO_AT_NS 3800
#define FW_TICKET 648
#define FW_AT_NS 3250
#define FW_GAP 280
#define FW_MID 2000
#define FW_GAP2 200
#define HGATE_NS 700
#define NPROBE 24
constexpr int NAUX = 8;
constexpr int NTHREADS = (NAUX + NWORK + 2) * 32;
constexpr int SPIN_MAX = 1 << 22;

constexpr int SM_KV = 0;
constexpr int SM_A = SM_KV + NWORK * TILE_BYTES;
constexpr int SM_W = SM_A + 61440;
constexpr int SM_X = SM_W + 81920;
constexpr int XPITCH = 648;
constexpr int HPITCH = 1344;
constexpr int SM_RED = SM_X + 5 * HPITCH + 64;
constexpr int SM_RED2 = SM_RED + 8 * 48 * 4 * 4;
constexpr int SM_MISC = SM_RED2 + 4096;
constexpr int BAR_WQ = SM_MISC + 32, BAR_WO = SM_MISC + 40, SM_SIDE = SM_MISC + 48, BAR_H = SM_MISC + 56, BAR_FW = SM_MISC + 64;
constexpr int BAR_KV = BAR_FW + 64;
constexpr int SM_TOTAL = BAR_KV + 2 * NWORK * 8;
static_assert(LAG == 2 && SM_W % 1024 == 0 && NB * XPITCH * 2 <= 4 * HPITCH && SM_RED % 128 == 0, "smem layout");

struct Params {
    CUtensorMap k, v;
    CUtensorMap wq;
    CUtensorMap wo;
    CUtensorMap wg, wu;
    CUtensorMap wd;
    const __nv_bfloat16 *x, *wr;
    __nv_bfloat16* out;
};

struct Early {
    uint32_t q[96];
    uint32_t umax[UPB];
};
struct Twin { uint32_t w[4][1024]; };
constexpr int PROBE = 1024 - 32;
#define LSTRIDE 16
struct State {
    Twin ax[3];
    Twin hx;
    Twin ox[OREP];
    Twin lx;
    float4 oacc[NBH * 64];
    float2 attn[NB][DM];
    uint32_t fw_time[32];
    float2 lsum[NBH][LSTRIDE];
    uint32_t score[NPOOL][32];
};
__host__ __device__ constexpr int oidx(int row, int grp) {
    return (row >> 2) * 256 + ((row & 1) * 2 + (grp >> 5)) * 64 + (row & 2) * 16 + (grp & 31);
}
constexpr int STATE_V4 = ((sizeof(State) / 32 + NQ_CTAS - 1) / NQ_CTAS) * 2;
static_assert(sizeof(State) % 32 == 0, "State is cleared in whole sectors");
static_assert(sizeof(Early) == 56 * 16, "an Early entry is cleared by 56 threads");
struct Scratch {
    State st;
    unsigned work[64];
    unsigned cnt_z[32];
    Early early[NBH];
    alignas(4096) float4 ring[RING][UPB][64];
};
constexpr size_t PAGE = 2u << 20;
static_assert(sizeof(Scratch) <= PAGE, "scratch must fit one page");
__device__ __align__(128) unsigned char g_raw[2 * PAGE];
__device__ __forceinline__ Scratch* scratch() {
    return reinterpret_cast<Scratch*>((reinterpret_cast<uintptr_t>(g_raw) + PAGE - 1) & ~(uintptr_t)(PAGE - 1));
}
#define g_early scratch()->early
#define g_st scratch()->st
#define g_ring scratch()->ring
#define g_cnt_z scratch()->cnt_z
#define g_work scratch()->work
#define ALL_LOADERS 0
#define TS(i)
#define TSW(i)
#define TS2(i)
#define TSI(n, i)
#define PH(i)
#define CK(i, dep)
#define ARR()
#define PROG(u)

__device__ __forceinline__ uint32_t s2u(const void* p) { return (uint32_t)__cvta_generic_to_shared(p); }
__device__ __forceinline__ void mbar_init(uint32_t bar, int cnt) {
    asm volatile("mbarrier.init.shared::cta.b64 [%0], %1;" :: "r"(bar), "r"(cnt) : "memory");
}
__device__ __forceinline__ void mbar_wait(uint32_t bar, uint32_t parity) {
    asm volatile("{\n.reg .pred p;\n.reg .u32 n;\nmov.u32 n, 0;\nWAIT_LOOP:\n"
                 "mbarrier.try_wait.parity.shared::cta.b64 p, [%0], %1;\n"
                 "@p bra WAIT_DONE;\nadd.u32 n, n, 1;\nsetp.lt.u32 p, n, %2;\n@p bra WAIT_LOOP;\nWAIT_DONE:\n}"
                 :: "r"(bar), "r"(parity), "n"(SPIN_MAX) : "memory");
}
__device__ __forceinline__ void request_tile(uint32_t dst, const CUtensorMap* tm, int unit, uint32_t bar, uint64_t pol) {
    asm volatile("{\n.reg .pred p;\nelect.sync _|p, 0xffffffff;\n"
                 "@p mbarrier.arrive.expect_tx.shared::cta.b64 _, [%2], %6;\n"
                 "@p cp.async.bulk.tensor.2d.shared::cluster.global.mbarrier::complete_tx::bytes.L2::cache_hint "
                 "[%0], [%1, {%3, %4}], [%2], %5;\n}"
                 :: "r"(dst), "l"(tm), "r"(bar), "r"(0), "r"(unit * TILE_ROWS), "l"(pol), "n"(TILE_BYTES) : "memory");
}
__device__ __forceinline__ void put_groups(void* dst, int mode, const float (&o)[6], float tag, float tag2) {
    asm volatile("{\n.reg .pred s, r, t;\n.reg .b128 u, v;\n.reg .b64 a, b;\n"
                 "setp.eq.s32 s|r, %1, 0;\nsetp.eq.s32 t, %1, 2;\n"
                 "@r red.relaxed.gpu.global.add.v4.f32 [%0], {%2,%3,%4,%8};\n"
                 "@t red.relaxed.gpu.global.add.v4.f32 [%0+4096], {%2,%3,%4,%8};\n"
                 "@r red.relaxed.gpu.global.add.v4.f32 [%0+128], {%5,%6,%7,%9};\n"
                 "@t red.relaxed.gpu.global.add.v4.f32 [%0+4224], {%5,%6,%7,%9};\n"
                 "mov.b64 a, {%2, %3};\nmov.b64 b, {%4, %8};\nmov.b128 u, {a, b};\n"
                 "mov.b64 a, {%5, %6};\nmov.b64 b, {%7, %9};\nmov.b128 v, {a, b};\n"
                 "@s st.relaxed.gpu.global.b128 [%0], u;\n@s st.relaxed.gpu.global.b128 [%0+128], v;\n}"
                 :: "l"(dst), "r"(mode), "f"(o[0]), "f"(o[1]), "f"(o[2]), "f"(o[3]), "f"(o[4]), "f"(o[5]), "f"(tag), "f"(tag2) : "memory");
}
__device__ __forceinline__ void request_box(uint32_t dst, const CUtensorMap* tm, int col, int row, uint32_t bar, uint32_t bytes) {
    asm volatile("{\n.reg .pred p, q;\nelect.sync _|p, 0xffffffff;\nsetp.ne.and.u32 q, %5, 0, p;\n"
                 "@q mbarrier.arrive.expect_tx.shared::cta.b64 _, [%2], %5;\n"
                 "@p cp.async.bulk.tensor.2d.shared::cluster.global.mbarrier::complete_tx::bytes [%0], [%1, {%3, %4}], [%2];\n}"
                 :: "r"(dst), "l"(tm), "r"(bar), "r"(col), "r"(row), "r"(bytes) : "memory");
}
__device__ __forceinline__ uint32_t lds32(uint32_t addr) {
    uint32_t v;
    asm volatile("ld.shared.u32 %0, [%1];" : "=r"(v) : "r"(addr) : "memory");
    return v;
}
__device__ __forceinline__ void ldsm4(uint32_t (&r)[4], uint32_t addr) {
    asm volatile("ldmatrix.sync.aligned.m8n8.x4.shared.b16 {%0,%1,%2,%3}, [%4];"
                 : "=r"(r[0]), "=r"(r[1]), "=r"(r[2]), "=r"(r[3]) : "r"(addr) : "memory");
}
__device__ __forceinline__ void ldsm4t(uint32_t (&r)[4], uint32_t addr) {
    asm volatile("ldmatrix.sync.aligned.m8n8.x4.trans.shared.b16 {%0,%1,%2,%3}, [%4];"
                 : "=r"(r[0]), "=r"(r[1]), "=r"(r[2]), "=r"(r[3]) : "r"(addr) : "memory");
}
__device__ __forceinline__ void mma16816(float (&c)[4], const uint32_t (&a)[4], uint32_t b0, uint32_t b1) {
    asm volatile("mma.sync.aligned.m16n8k16.row.col.f32.bf16.bf16.f32 {%0,%1,%2,%3}, {%4,%5,%6,%7}, {%8,%9}, {%0,%1,%2,%3};"
                 : "+f"(c[0]), "+f"(c[1]), "+f"(c[2]), "+f"(c[3])
                 : "r"(a[0]), "r"(a[1]), "r"(a[2]), "r"(a[3]), "r"(b0), "r"(b1));
}
struct Warm {
    float c[4] = {};
    __device__ __forceinline__ void operator()() {
        asm volatile("mma.sync.aligned.m16n8k8.row.col.f32.bf16.bf16.f32 {%0,%1,%2,%3}, {%4,%4}, {%4}, {%0,%1,%2,%3};"
                     : "+f"(c[0]), "+f"(c[1]), "+f"(c[2]), "+f"(c[3]) : "r"(0));
    }
    __device__ __forceinline__ void done(uint32_t scrap) {
        asm volatile("{\n.reg .pred p;\nsetp.gt.f32 p, %1, 0f3f800000;\n@p st.shared.f32 [%0], %1;\n}" :: "r"(scrap), "f"(c[0]) : "memory");
    }
};
__device__ __forceinline__ uint4 ld_relaxed_v4(const void* p) {
    uint4 v;
    asm volatile("ld.relaxed.gpu.global.v4.u32 {%0,%1,%2,%3}, [%4];" : "=r"(v.x), "=r"(v.y), "=r"(v.z), "=r"(v.w) : "l"(p) : "memory");
    return v;
}
__device__ __forceinline__ float4 ld_relaxed_f4(const void* p) {
    float4 v;
    asm volatile("ld.relaxed.gpu.global.v4.f32 {%0,%1,%2,%3}, [%4];" : "=f"(v.x), "=f"(v.y), "=f"(v.z), "=f"(v.w) : "l"(p) : "memory");
    return v;
}
__device__ __forceinline__ float2 ld_relaxed_f2(const void* p) {
    float2 v;
    asm volatile("ld.relaxed.gpu.global.v2.f32 {%0,%1}, [%2];" : "=f"(v.x), "=f"(v.y) : "l"(p) : "memory");
    return v;
}
__device__ __forceinline__ float4 ld_relaxed_b128(const void* p) {
    float4 v;
    asm volatile("{\n.reg .b128 t;\n.reg .b64 a, b;\nld.relaxed.gpu.global.b128 t, [%4];\nmov.b128 {a, b}, t;\n"
                 "mov.b64 {%0, %1}, a;\nmov.b64 {%2, %3}, b;\n}" : "=f"(v.x), "=f"(v.y), "=f"(v.z), "=f"(v.w) : "l"(p) : "memory");
    return v;
}
__device__ __forceinline__ void st_relaxed_b128(void* p, float x, float y, float z, float w) {
    asm volatile("{\n.reg .b128 t;\n.reg .b64 a, b;\nmov.b64 a, {%1, %2};\nmov.b64 b, {%3, %4};\nmov.b128 t, {a, b};\n"
                 "st.relaxed.gpu.global.b128 [%0], t;\n}" :: "l"(p), "f"(x), "f"(y), "f"(z), "f"(w) : "memory");
}
__device__ __forceinline__ unsigned ld_acquire(const unsigned* p) {
    unsigned v;
    asm volatile("ld.acquire.gpu.global.u32 %0, [%1];" : "=r"(v) : "l"(p) : "memory");
    return v;
}
__device__ __forceinline__ void st_relaxed(void* p, uint32_t v) {
    asm volatile("st.relaxed.gpu.global.u32 [%0], %1;" :: "l"(p), "r"(v) : "memory");
}
__device__ __forceinline__ void red_f2(float* p, float a, float b) {
    asm volatile("red.relaxed.gpu.global.add.v2.f32 [%0], {%1,%2};" :: "l"(p), "f"(a), "f"(b) : "memory");
}
__device__ __forceinline__ void draw(int& ticket, unsigned* ctr, bool pred) {
    asm volatile("{\n.reg .pred p;\nsetp.ne.u32 p, %2, 0;\n@p atom.relaxed.gpu.global.inc.u32 %0, [%1], 0x7fffffff;\n}"
                 : "+r"(ticket) : "l"(ctr), "r"((uint32_t)pred) : "memory");
}
__device__ __forceinline__ void red_release(unsigned* p) {
    asm volatile("red.release.gpu.global.add.u32 [%0], 1;" :: "l"(p) : "memory");
}
__device__ __forceinline__ uint32_t ld_relaxed_u32(const void* p) {
    uint32_t v;
    asm volatile("ld.relaxed.gpu.global.u32 %0, [%1];" : "=r"(v) : "l"(p) : "memory");
    return v;
}
__device__ __forceinline__ float rcp_approx(float v) {
    float r;
    asm("rcp.approx.ftz.f32 %0, %1;" : "=f"(r) : "f"(v));
    return r;
}
__device__ __forceinline__ float ex2_approx(float v) {
    float e;
    asm("ex2.approx.ftz.f32 %0, %1;" : "=f"(e) : "f"(v));
    return e;
}
__device__ __forceinline__ float sigmoid_approx(float v) { return rcp_approx(1.0f + ex2_approx(v * -1.4426950408889634f)); }
__device__ __forceinline__ float sqrt_approx(float v) {
    float r;
    asm("sqrt.approx.ftz.f32 %0, %1;" : "=f"(r) : "f"(v));
    return r;
}
__device__ __forceinline__ bool all(bool v) { return __all_sync(0xffffffffu, v); }
__device__ __forceinline__ void wait_count(const unsigned* p, unsigned target) {
#pragma unroll 1
    for (int it = 0; it < SPIN_MAX; it++) {
        if (all(ld_acquire(p) >= target)) break;
        __nanosleep(400);
    }
}
__device__ __forceinline__ float wait_sum(const void* p, float n, int nap = 0) {
    float2 v;
#pragma unroll 1
    for (int it = 0; it < SPIN_MAX; it++) {
        v = ld_relaxed_f2(p);
        if (all(v.y >= n)) break;
        if (all(v.y == 0.f)) __nanosleep(600);
        else if (nap) __nanosleep(nap);
    }
    return v.x;
}
__device__ __forceinline__ void wait_row(int bh, float n) { wait_sum(g_st.lsum[bh], n); }
__device__ __forceinline__ void wait_row_o(int bh, float n) {
    wait_row(bh, n);
    if (bh >= RED0) return;
#pragma unroll 1
    for (int it = 0; it < SPIN_MAX; it++) {
        if (all(__uint_as_float(ld_relaxed_u32(&g_st.oacc[oidx(bh, 0)].w)) == UPB)) break;
        __nanosleep(300);
    }
}
__device__ __forceinline__ void wait_clock(uint32_t t, Warm& warm) { while (!all((int)(clock() - t) >= 0)) { warm(); } }
__device__ __forceinline__ void spin_ns(int ns) { const uint32_t t = clock() + ns * 2; while (!all((int)(clock() - t) >= 0)) {} }
__device__ __forceinline__ uint32_t pack_bf16(float lo, float hi) {
    uint32_t r;
    asm("cvt.rn.bf16x2.f32 %0, %1, %2;" : "=r"(r) : "f"(hi), "f"(lo));
    return r;
}
__device__ __forceinline__ float bf16r(float v) { return __uint_as_float(pack_bf16(0.f, v)); }
__device__ __forceinline__ uint32_t nonzero(uint32_t w) { return w ? w : 0x80008000u; }
__device__ __forceinline__ uint32_t pack_neg(float lo, float hi) { return nonzero(pack_bf16(-lo, -hi)); }
__device__ __forceinline__ float lo_f(uint32_t v) { return __uint_as_float(v << 16); }
__device__ __forceinline__ float hi_f(uint32_t v) { return __uint_as_float(v & 0xffff0000u); }
__device__ __forceinline__ float warp_sum(float v) {
#pragma unroll
    for (int o = 16; o; o >>= 1) v += __shfl_xor_sync(0xffffffffu, v, o);
    return v;
}
__device__ __forceinline__ void layernorm20(float (&v)[20]) {
    float s = 0.f;
#pragma unroll
    for (int i = 0; i < 20; i++) s += v[i];
    const float mean = warp_sum(s) * (1.0f / DM);
    float q = 0.f;
#pragma unroll
    for (int i = 0; i < 20; i++) { const float d = v[i] - mean; q += d * d; }
    const float var = bf16r(warp_sum(q) * (1.0f / DM));
    const float m = bf16r(mean);
    const float rden = 1.0f / bf16r(sqrtf(bf16r(var + 1e-5f)));
#pragma unroll
    for (int i = 0; i < 20; i++) v[i] = bf16r(bf16r(v[i] - m) * rden);
}

__device__ __forceinline__ void moments(float m1, float m2, float& nmean, float& rden) {
    m1 *= 1.0f / DM;
    const float var = bf16r(fmaxf(fmaf(-m1, m1, m2 * (1.0f / DM)), 0.f));
    nmean = bf16r(m1);
    rden = rcp_approx(bf16r(sqrt_approx(bf16r(var + 1e-5f))));
}
__device__ __forceinline__ float sel4(int j, float a, float b, float c, float d) {
    float lo, hi, r;
    asm("{\n.reg .pred p;\nsetp.ne.s32 p, %3, 0;\nselp.f32 %0, %2, %1, p;\n}" : "=f"(lo) : "f"(a), "f"(b), "r"(j & 1));
    asm("{\n.reg .pred p;\nsetp.ne.s32 p, %3, 0;\nselp.f32 %0, %2, %1, p;\n}" : "=f"(hi) : "f"(c), "f"(d), "r"(j & 1));
    asm("{\n.reg .pred p;\nsetp.ne.s32 p, %3, 0;\nselp.f32 %0, %2, %1, p;\n}" : "=f"(r) : "f"(lo), "f"(hi), "r"(j & 2));
    return r;
}
template <typename T> __device__ __forceinline__ void pin(T*& p) { asm volatile("" : "+l"(p)); }
__device__ __forceinline__ void pin(uint32_t& v) { asm volatile("" : "+r"(v)); }
__device__ __forceinline__ void pin(float& v) { asm volatile("" : "+f"(v)); }
__device__ __forceinline__ uint32_t after(uint32_t n, float v) {
    asm volatile("{\n.reg .pred p;\nsetp.eq.u32 p, %1, 0x7fc1a5a5;\n@p add.u32 %0, %0, 32;\n}" : "+r"(n) : "r"(__float_as_uint(v)));
    return n;
}
__device__ __forceinline__ float2 lds64f(uint32_t addr) {
    float2 v;
    asm volatile("ld.shared.v2.f32 {%0,%1}, [%2];" : "=f"(v.x), "=f"(v.y) : "r"(addr) : "memory");
    return v;
}
__device__ __forceinline__ void sts32f(uint32_t addr, float v) { asm volatile("st.shared.f32 [%0], %1;" :: "r"(addr), "f"(v) : "memory"); }
template <int ID> __device__ __forceinline__ void fin_arrive() { asm volatile("bar.arrive %0, 288;" :: "n"(ID) : "memory"); }
template <int ID> __device__ __forceinline__ void fin_sync() { asm volatile("bar.sync %0, 288;" :: "n"(ID) : "memory"); }
template <int ID> __device__ __forceinline__ void fin_sync(uint32_t n) { asm volatile("bar.sync %0, %1;" :: "n"(ID), "r"(n) : "memory"); }
__device__ __forceinline__ float2 sum8(uint32_t addr) {
    float2 t[8];
#pragma unroll
    for (int w = 0; w < 8; w++) t[w] = lds64f(addr + w * 128);
    return make_float2(((t[0].x + t[1].x) + (t[2].x + t[3].x)) + ((t[4].x + t[5].x) + (t[6].x + t[7].x)),
                       ((t[0].y + t[1].y) + (t[2].y + t[3].y)) + ((t[4].y + t[5].y) + (t[6].y + t[7].y)));
}
__device__ __forceinline__ float4 sum4x4(uint32_t addr, int pitch) {
    float4 t[4];
#pragma unroll
    for (int w = 0; w < 4; w++)
        asm volatile("ld.shared.v4.f32 {%0,%1,%2,%3}, [%4];" : "=f"(t[w].x), "=f"(t[w].y), "=f"(t[w].z), "=f"(t[w].w) : "r"(addr + w * pitch) : "memory");
    return make_float4((t[0].x + t[1].x) + (t[2].x + t[3].x), (t[0].y + t[1].y) + (t[2].y + t[3].y),
                       (t[0].z + t[1].z) + (t[2].z + t[3].z), (t[0].w + t[1].w) + (t[2].w + t[3].w));
}
__device__ __forceinline__ void sts64f(uint32_t addr, float x, float y) {
    asm volatile("st.shared.v2.f32 [%0], {%1,%2};" :: "r"(addr), "f"(x), "f"(y) : "memory");
}
__device__ __forceinline__ void lds128_if(uint4& v, uint32_t addr, bool pred) {
    asm volatile("{\n.reg .pred p;\nsetp.ne.u32 p, %5, 0;\n@p ld.shared.v4.u32 {%0,%1,%2,%3}, [%4];\n}"
                 : "+r"(v.x), "+r"(v.y), "+r"(v.z), "+r"(v.w) : "r"(addr), "r"((uint32_t)pred) : "memory");
}
__device__ __forceinline__ void sts128f(uint32_t addr, float x, float y, float z, float w) {
    asm volatile("st.shared.v4.f32 [%0], {%1,%2,%3,%4};" :: "r"(addr), "f"(x), "f"(y), "f"(z), "f"(w) : "memory");
}
template <int NJ>
__device__ __forceinline__ void load_o(uint32_t (&ob)[3 * NJ][2], int bh, int J0, int j) {
    float4 v[NJ][4];
    float2 l;
#pragma unroll 1
    for (int it = 0; it < SPIN_MAX; it++) {
#pragma unroll
        for (int J = 0; J < NJ; J++) {
#pragma unroll
            for (int e = 0; e < 4; e++) v[J][e] = ld_relaxed_f4(&g_st.oacc[oidx(bh, j)] + oidx(0, (J0 + J) * 16 + e * 4));
        }
        l = ld_relaxed_f2(g_st.lsum[bh]);
        bool ok = l.y == UPB;
#pragma unroll
        for (int J = 0; J < NJ; J++) {
#pragma unroll
            for (int e = 0; e < 4; e++) ok &= v[J][e].w == UPB;
        }
        if (all(ok)) break;
    }
    const float rl = __fdividef(1.0f, l.x);
#pragma unroll
    for (int J = 0; J < NJ; J++) {
        ob[3 * J][0] = pack_bf16(v[J][0].x * rl, v[J][1].x * rl);     ob[3 * J][1] = pack_bf16(v[J][2].x * rl, v[J][3].x * rl);
        ob[3 * J + 1][0] = pack_bf16(v[J][0].y * rl, v[J][1].y * rl); ob[3 * J + 1][1] = pack_bf16(v[J][2].y * rl, v[J][3].y * rl);
        ob[3 * J + 2][0] = pack_bf16(v[J][0].z * rl, v[J][1].z * rl); ob[3 * J + 2][1] = pack_bf16(v[J][2].z * rl, v[J][3].z * rl);
    }
}
__device__ __forceinline__ int near_side(uint32_t sb) {
    uint32_t v;
    asm volatile("ld.volatile.shared.u32 %0, [%1];" : "=r"(v) : "r"(sb + SM_SIDE) : "memory");
    return v;
}
__device__ __forceinline__ void poll_row(uint4& a, uint4& b, uint2& c, const void* pa, const void* pb, const void* pc, uint32_t sa, uint32_t sc,
                                         bool arrive, bool nap, uint32_t bar, Warm& warm) {
    asm volatile("{\n.reg .pred p, q, r, s;\n.reg .b32 m, n, it;\n"
                 "setp.ne.u32 r, %19, 0;\nsetp.ne.u32 s, %20, 0;\nmov.u32 it, 0;\n"
                 "POLL:\n"
                 "ld.relaxed.gpu.global.v4.u32 {%0,%1,%2,%3}, [%14];\n"
                 "ld.relaxed.gpu.global.v4.u32 {%4,%5,%6,%7}, [%15];\n"
                 "ld.relaxed.gpu.global.v2.u32 {%8,%9}, [%16];\n"
                 "add.u32 it, it, 1;\nsetp.ge.u32 q, it, %21;\n"
                 "mov.u32 m, 0;\nmma.sync.aligned.m16n8k8.row.col.f32.bf16.bf16.f32 {%10,%11,%12,%13}, {m,m}, {m}, {%10,%11,%12,%13};\n"
                 "st.shared.v4.u32 [%17], {%0,%1,%2,%3};\n"
                 "st.shared.v4.u32 [%17+512], {%4,%5,%6,%7};\n"
                 "st.shared.v2.u32 [%18], {%8,%9};\n"
                 "min.u32 m, %0, %1;\nmin.u32 m, m, %2;\nmin.u32 n, %3, %4;\nmin.u32 n, n, %5;\nmin.u32 m, m, %6;\nmin.u32 m, m, %7;\n"
                 "min.u32 n, n, m;\nmin.u32 m, %8, %9;\nmin.u32 m, m, n;\n"
                 "setp.ne.or.u32 p, m, 0, q;\n"
                 "vote.sync.all.pred p, p, 0xffffffff;\n"
                 "and.pred q, p, r;\n"
                 "bar.warp.sync 0xffffffff;\n"
                 "@q mbarrier.arrive.shared::cta.b64 _, [%22];\n"
                 "@p bra.uni DONE;\n"
                 "@s nanosleep.u32 500;\n"
                 "bra.uni POLL;\n"
                 "DONE:\n}"
                 : "=&r"(a.x), "=&r"(a.y), "=&r"(a.z), "=&r"(a.w), "=&r"(b.x), "=&r"(b.y), "=&r"(b.z), "=&r"(b.w), "=&r"(c.x), "=&r"(c.y),
                   "+f"(warm.c[0]), "+f"(warm.c[1]), "+f"(warm.c[2]), "+f"(warm.c[3])
                 : "l"(pa), "l"(pb), "l"(pc), "r"(sa), "r"(sc), "r"((uint32_t)arrive), "r"((uint32_t)nap), "n"(SPIN_MAX), "r"(bar) : "memory");
}
__device__ __forceinline__ void aux_sync() { asm volatile("bar.sync 1, 256;" ::: "memory"); }

__global__ void __launch_bounds__(NTHREADS, 1)
fused_decode_kernel(const __grid_constant__ Params p) {
    extern __shared__ __align__(1024) unsigned char smem[];
    const uint32_t sb = s2u(smem);
    const int tid = threadIdx.x, cta = blockIdx.x;
    if (tid < 32 && cta < NQ_CTAS) {
        asm volatile("{\n.reg .pred p;\nelect.sync _|p, 0xffffffff;\n"
                     "@p mbarrier.init.shared::cta.b64 [%2], 1;\n"
                     "@p fence.mbarrier_init.release.cluster;\n"
                     "@p mbarrier.arrive.expect_tx.shared::cta.b64 _, [%2], 61440;\n"
                     "@p cp.async.bulk.tensor.2d.shared::cluster.global.mbarrier::complete_tx::bytes [%0], [%1, {%3, %4}], [%2];\n"
                     "@p cp.async.bulk.tensor.2d.shared::cluster.global.mbarrier::complete_tx::bytes [%0+15360], [%1, {%3, %5}], [%2];\n"
                     "@p cp.async.bulk.tensor.2d.shared::cluster.global.mbarrier::complete_tx::bytes [%0+30720], [%1, {%3, %6}], [%2];\n"
                     "@p cp.async.bulk.tensor.2d.shared::cluster.global.mbarrier::complete_tx::bytes [%0+46080], [%1, {%3, %7}], [%2];\n}"
                     :: "r"(sb + SM_W), "l"(&p.wq), "r"(sb + BAR_WQ), "r"(cta * 48), "r"(0), "r"(160), "r"(320), "r"(480) : "memory");
    }
    const int warp = __shfl_sync(0xffffffffu, tid >> 5, 0), lane = tid & 31;
    constexpr int grid = NCTAS;
    const int g = lane >> 2, j = lane & 3;
    TS(0);
    if (tid == 160) {
        mbar_init(sb + BAR_WO, 1);
        mbar_init(sb + BAR_H, 1);
#pragma unroll
        for (int i = 0; i < 8 + 2 * NWORK; i++) mbar_init(sb + BAR_FW + i * 8, 1);
        sts32f(sb + SM_SIDE, 0.f);
        asm volatile("fence.mbarrier_init.release.cluster;" ::: "memory");
        asm volatile("fence.proxy.async.shared::cta;" ::: "memory");
    }
    __syncthreads();
    if (warp >= NAUX + NWORK) {
        const int fw = warp - (NAUX + NWORK), fi = ffn_slice(cta);
        if (fw == 0) {
            if (cta < NQ_CTAS) {
#pragma unroll
                for (int i = lane; i < STATE_V4; i += 32)
                    if (cta * STATE_V4 + i < (int)(sizeof(State) / 16)) reinterpret_cast<uint4*>(&g_st)[cta * STATE_V4 + i] = make_uint4(0u, 0u, 0u, 0u);
                __syncwarp();
                if (lane == 0) red_release(g_cnt_z);
            }
            TSW(2); wait_count(g_cnt_z, NQ_CTAS); TSW(29);
            asm volatile("bar.arrive 2, %0;" :: "n"((NWORK + 2) * 32) : "memory");
            fin_arrive<3>();
        } else {
            asm volatile("bar.sync 2, %0;" :: "n"((NWORK + 2) * 32) : "memory");
            uint32_t best[2] = {~0u, ~0u};
#pragma unroll 1
            for (int i = 0; i < NPROBE; i++) {
#pragma unroll
                for (int c = 0; c < 2; c++) {
                    uint32_t t0 = clock(), t1 = t0;
                    int v = 0;
                    draw(v, &g_st.hx.w[c][PROBE], lane == 0);
                    asm volatile("{\n.reg .pred p;\nsetp.ne.u32 p, %1, 0xffffffff;\n@p mov.u32 %0, %%clock;\n}" : "+r"(t1) : "r"(v) : "memory");
                    best[c] = min(best[c], t1 - t0);
                }
                __nanosleep(1000);
            }
            if (lane == 0) sts32f(sb + SM_SIDE, __uint_as_float(best[1] < best[0]));
        }
        int job = cta;
        auto sum_rows = [&](int row_end) {
#pragma unroll 1
            for (; job < 8 * min(row_end, RED0); job += NCTAS) {
                const int row = job >> 3, grp = (job & 7) * 8 + (lane & 7);
                wait_row(row, UPB);
                const float4* src = &g_ring[row % RING][lane >> 3][grp];
                float sx = 0.f, sy = 0.f, sz = 0.f;
#pragma unroll 1
                for (int i = 0; i < 2; i++, src += 64 * 64) {
                    float4 v[16];
#pragma unroll 1
                    for (int it = 0; it < SPIN_MAX; it++) {
                        bool ok = true;
#pragma unroll
                        for (int k = 0; k < 16; k++) v[k] = ld_relaxed_b128(src + k * 4 * 64);
#pragma unroll
                        for (int k = 0; k < 16; k++) ok &= v[k].w == (float)(row + 1);
                        if (all(ok)) break;
                    }
#pragma unroll
                    for (int k = 0; k < 16; k++) { sx += v[k].x; sy += v[k].y; sz += v[k].z; }
                }
#pragma unroll
                for (int o = 8; o < 32; o <<= 1) {
                    sx += __shfl_xor_sync(0xffffffffu, sx, o); sy += __shfl_xor_sync(0xffffffffu, sy, o); sz += __shfl_xor_sync(0xffffffffu, sz, o);
                }
                if (lane < 8) st_relaxed_b128(&g_st.oacc[oidx(row, grp)], sx, sy, sz, UPB);
            }
        };
        const int ho0 = lane / 20 * 256 + lane % 20 * 4, ho1 = (lane + 32) / 20 * 256 + (lane + 32) % 20 * 4, ho2 = 3 * 256 + 16 + 2 * lane;
        uint32_t wr[10] = {};
        float wsum = 0.f;
        if (is_g(cta) && fw == 0) {
#pragma unroll
            for (int i = 0; i < 10; i++) {
                const int w = 4 * lane + 128 * (i >> 2) + (i & 3) - (i >= 8 ? 2 * lane : 0);
                wr[i] = *reinterpret_cast<const uint32_t*>(p.wr + (w >> 4) * 32 + (w & 3) * 8 + ((w >> 1) & 6));
                wsum += lo_f(wr[i]) + hi_f(wr[i]);
            }
            wsum = warp_sum(wsum);
        }
        const int fb = lane >> 3, fg = lane & 7;
        if (fw == 0) {
#pragma unroll
            for (int i = lane; i < DM / 2; i += 32) sts32f(sb + SM_X + 4 * HPITCH + i * 4, __uint_as_float(0x3f803f80u));
        }
        Warm warm;
        float nmean = 0.f, rden = 0.f, sig = 0.f;
#pragma unroll 1
        for (int b = 0; b < NB; b++) {
            const bool ffn = b >= NB - 2;
            if (fw == 0) {
                sum_rows((b + 1) * NH);
                if (ffn) asm volatile("bar.arrive 8, 64;" ::: "memory");
            } else if (ffn) {
                asm volatile("bar.sync 8, 64;" ::: "memory");
                if (b == NB - 1 && (is_f(cta) || is_g(cta) || ALL_LOADERS)) {
                    uint32_t t0 = 0, now;
#pragma unroll 1
                    for (int it = 0; it < SPIN_MAX; it++) {
                        t0 = ld_relaxed_u32(g_st.fw_time);
                        if (all(t0 != 0)) break;
                        __nanosleep(400);
                    }
                    asm volatile("fence.proxy.async.shared::cta;" ::: "memory");
#pragma unroll 1
                    for (int it = 0; it < SPIN_MAX; it++) {
                        asm volatile("mov.u32 %0, %%globaltimer_lo;" : "=r"(now));
                        if (all((int)(now - t0) >= FW_AT_NS)) break;
                    }
                    TSW(9);
                    uint32_t t = clock() + (is_f(cta) ? (fi & 1) * (FW_GAP / 2) : FW_MID + (fi & 3) * (FW_GAP2 / 4));
#pragma unroll 1
                    for (int i = 0; i < 8; i++) {
                        const uint32_t bar = sb + BAR_FW + i * 8;
                        if (is_f(cta)) {
                            wait_clock(t, warm);
                            request_box(sb + SM_W + i * 10240, (i & 1) ? &p.wu : &p.wg, fi * 32, (i >> 1) * 160, bar, 10240);
                            t += FW_GAP;
                        } else if (is_g(cta)) {
                            wait_clock(t, warm);
                            asm volatile("{\n.reg .pred p;\nelect.sync _|p, 0xffffffff;\n"
                                         "@p mbarrier.arrive.expect_tx.shared::cta.b64 _, [%2], 6144;\n"
                                         "@p cp.async.bulk.tensor.4d.shared::cluster.global.mbarrier::complete_tx::bytes [%0], [%1, {%3, %4, %4, %5}], [%2];\n}"
                                         :: "r"(sb + SM_W + i * 6144), "l"(&p.wd), "r"(bar), "r"(fi * 16), "r"(0), "r"(i * 12) : "memory");
                            t += FW_GAP2;
                        }
                    }
                }
                if (is_f(cta)) {
                    const uint32_t* src = &g_st.hx.w[near_side(sb)][min(fb, b) * 256 + 96];
                    float4 m;
#pragma unroll 1
                    for (int it = 0; it < SPIN_MAX; it++) {
                        m = ld_relaxed_f4(src);
                        warm();
                        if (all(m.y + m.w == 2 * (NCTAS - NE_CTAS))) break;
                        if (b < NB - 1) __nanosleep(500);
                    }
                    moments(m.x, m.z, m.x, m.z);
                    sts64f(sb + SM_RED + 5120 + fb * 8, m.x, m.z);
                }
            }
            if (fw == 0 && cta >= NE_CTAS) {
                const int lc = cta - NE_CTAS, col = lc * 32 + 2 * (lane & 15);
                const uint32_t xv = *reinterpret_cast<const uint32_t*>(p.x + b * DM + col);
                uint32_t* dst = &(ffn ? g_st.hx.w : g_st.lx.w + 2)[lane >> 4][(b & 1) * 128 + lc / 5 * 256 + lc % 5 * 16 + (col & 6) * 2 + ((col >> 3) & 3)];
                uint32_t part = sb + SM_RED + (lane & 15) * 8;
                wait_row(b * NH + 28, 1);
                float4 early;
#pragma unroll 1
                for (int it = 0; it < SPIN_MAX; it++) {
                    early = ld_relaxed_f4(&g_st.attn[b][col]);
                    if (all(early.y == NE_CTAS / 4 && early.w == NE_CTAS / 4)) break;
                }
                if (early.x != 1.2345f && lane == 0) TS2(6);
                CK(1, __float_as_uint(early.x));
                const float x0 = -(lo_f(xv) + early.x), x1 = -(hi_f(xv) + early.z);
                fin_sync<4>(after(after(288, x0), x1));
                CK(2, lds32(sb + SM_RED));
                const float2 late = sum8(part);
                const uint32_t hv = nonzero(pack_bf16(x0 - late.x, x1 - late.y));
                st_relaxed(dst, hv);
                if (ffn) st_relaxed(dst + 2048, hv);
                CK(3, 0);
                float m = lane < 16 ? lo_f(hv) + hi_f(hv) : fmaf(lo_f(hv), lo_f(hv), hi_f(hv) * hi_f(hv));
#pragma unroll
                for (int o = 1; o < 16; o <<= 1) m += __shfl_xor_sync(0xffffffffu, m, o);
                if ((lane & 14) == 0) red_f2(reinterpret_cast<float*>(&g_st.hx.w[lane & 1][b * 256 + 96 + (lane >> 4) * 2]), m, 1.f);
                fin_arrive<5>();
            }
            if (fw == 0 && (is_g(cta) || is_f(cta))) {
                const uint32_t* src = &(ffn ? g_st.hx.w : g_st.lx.w + 2)[near_side(sb) ^ (ffn && is_g(cta) ? 3 : 0)][(b & 1) * 128];
                const uint32_t hrow = sb + SM_X + b * HPITCH;
                wait_sum(b == NB - 1 ? (const void*)&g_st.lx.w[near_side(sb) ^ 1][3 * 256] : g_st.lsum[b * NH + NH - 1], UPB, 100);
                wait_clock(clock() + HGATE_NS * 2, warm);
                uint4 h0, h1;
                uint2 h2;
                poll_row(h0, h1, h2, src + ho0, src + ho1, src + ho2, hrow + lane * 16, hrow + 1024 + lane * 8, ffn && lane == 0, b < NB - 1, sb + BAR_H, warm);
                CK(4, h0.x);
                if (is_g(cta)) {
                    const uint32_t hw[10] = {h0.x, h0.y, h0.z, h0.w, h1.x, h1.y, h1.z, h1.w, h2.x, h2.y};
                    float m1 = 0.f, m2 = 0.f, rr = 0.f;
#pragma unroll
                    for (int i = 0; i < 10; i++) {
                        const float v0 = lo_f(hw[i]), v1 = hi_f(hw[i]);
                        m1 += v0 + v1;
                        m2 = fmaf(v0, v0, fmaf(v1, v1, m2));
                        rr = fmaf(v0, lo_f(wr[i]), fmaf(v1, hi_f(wr[i]), rr));
                    }
                    moments(warp_sum(m1), warp_sum(m2), m1, m2);
                    const float sg = bf16r(sigmoid_approx(bf16r((m1 * wsum - warp_sum(rr)) * m2)));
                    if (fb == b) { nmean = m1; rden = m2; sig = sg; }
                    __syncwarp();
                    if (ffn) {
                        const int yj = 2 * (fb & 1) + (fb >> 1);
                        uint32_t ypart = sb + SM_RED2 + yj * 128 + ((fg + 2 * yj) & 7) * 16;
                        __nv_bfloat16* out = p.out + fb * DM + fi * 16 + fg;
                        const float2 hw2 = lds64f(sb + SM_X + fb * HPITCH + ((fi >> 1) * 16 + (fg & 6) * 2 + (fi & 1) * 2) * 4);
                        const uint32_t w0 = __float_as_uint(hw2.x), w1 = __float_as_uint(hw2.y);
                        const float nh0 = (fg & 1) ? hi_f(w0) : lo_f(w0), nh1 = (fg & 1) ? hi_f(w1) : lo_f(w1);
                        const float ln0 = bf16r(bf16r(nmean - nh0) * rden) - nh0, ln1 = bf16r(bf16r(nmean - nh1) * rden) - nh1;
                        pin(ypart); pin(out);
                        fin_sync<6>(after(after(after(288, sig), ln0), ln1));
                        CK(10, lds32(ypart));
                        const float4 ya = sum4x4(ypart, 512), yb = sum4x4(ypart + 2048, 512);
                        const float4 y = make_float4(ya.x + yb.x, ya.y + yb.y, ya.z + yb.z, ya.w + yb.w);
                        const float y0 = -(((fb & 1) ? y.y : y.x) + __shfl_xor_sync(0xffffffffu, (fb & 1) ? y.x : y.y, 8));
                        const float y1 = -(((fb & 1) ? y.w : y.z) + __shfl_xor_sync(0xffffffffu, (fb & 1) ? y.z : y.w, 8));
                        const uint32_t ov = pack_bf16(fmaf(y0, sig, ln0), fmaf(y1, sig, ln1));
                        if (b == NB - 1) {
                            asm volatile("st.global.u16 [%0], %1;" :: "l"(out), "h"((unsigned short)(ov & 0xffffu)) : "memory");
                            asm volatile("st.global.u16 [%0], %1;" :: "l"(out + 8), "h"((unsigned short)(ov >> 16)) : "memory");
                        }
                        CK(11, 0);
                        if (lane == 0) TS2(13);
                    }
                }
            }
            if (is_f(cta) && ffn) {
                const int ks = (2 * fi + fw) % 12;
                const int far = near_side(sb) ^ 1;
                uint32_t* dst = &g_st.ax[ks >> 2].w[(~b & 1) * 2 + far][(fi / 6) * 128 + (ks & 3) * 32 + fb * 8 + (fg & 1) * 4 + ((fg >> 1) ^ (ks & 1))];
                uint32_t* dst2 = dst + (far ? -1024 : 1024);
                uint32_t part = sb + SM_RED + fw * 2560 + fb * 128 + ((fg + (fb & 2)) & 7) * 16;
                uint32_t psum = sb + SM_RED + fw * 2560 + 4 * 128 + ((fg + 4) & 7) * 16;
                pin(dst); pin(part); pin(psum);
                asm volatile("bar.sync 4, 320;" ::: "memory");
                CK(6, lds32(part));
                const float4 d = sum4x4(part, 640), cs = sum4x4(psum, 640);
                const float2 mo = lds64f(sb + SM_RED + 5120 + fb * 8);
                nmean = mo.x; rden = mo.y;
                const float g0 = fmaf(nmean, cs.x, -d.x), g1 = fmaf(nmean, cs.y, -d.y), ke = rden * -1.4426950408889634f, r2 = rden * rden;
                const float p0 = g0 * fmaf(-nmean, cs.z, d.z) * r2, p1 = g1 * fmaf(-nmean, cs.w, d.w) * r2;
                const uint32_t av = nonzero(pack_bf16(p0 * rcp_approx(1.0f + ex2_approx(g0 * ke)), p1 * rcp_approx(1.0f + ex2_approx(g1 * ke))));
                st_relaxed(dst, av);
                st_relaxed(dst2, av);
                CK(7, 0);
            }
        }
        warm.done(sb + SM_MISC);
        if (cta == 0 && tid == (NAUX + NWORK) * 32) { g_work[0] = 0; g_work[32] = 0; g_cnt_z[0] = 0; }
        return;
    }
    if (warp >= NAUX) {
        const int wk = warp - NAUX;
        const uint32_t bar = sb + BAR_KV + wk * 8;
        const uint32_t buf = sb + SM_KV + wk * TILE_BYTES;
        uint64_t pol;
        asm volatile("createpolicy.fractional.L2::evict_first.b64 %0, 1.0;" : "=l"(pol));
        const int nstatic = NWORK * grid;
        constexpr int POOL0 = NUNITS - NPOOL;
        int uk = wk * grid + cta;
        spin_ns(K0_DELAY_NS);
        request_tile(buf, &p.k, uk, bar, pol);
        if (wk == 0) {
            spin_ns(WO_AT_NS - K0_DELAY_NS);
#pragma unroll 1
            for (int i = 0; i < (cta < NE_CTAS ? 5 : 4); i++)
                request_box(sb + SM_A + i * 12288, &p.wo, cta < NE_CTAS ? (cta & 3) * 160 + i * 32 : (cta - NE_CTAS) * 32,
                            (cta < NE_CTAS ? cta >> 2 : 28 + i) * DH, sb + BAR_WO, i ? 0 : cta < NE_CTAS ? 61440 : 49152);
        }
        uint32_t koff[3], voff[3];
        {
            const int r = lane & 7, hf = (lane >> 3) & 1;
            const int kkey = hf ? 8 + (r ^ 1) : r;
            const int vh = lane >> 4;
            const int vkey = ((r & 1) ? 8 : 0) + (vh ? (r ^ 1) : r);
#pragma unroll
            for (int b = 0; b < 3; b++) {
                const int rk = 3 * kkey + b, rv = 3 * vkey + b;
                koff[b] = buf + rk * 128 + (((lane >> 4) ^ (rk & 7)) << 4);
                voff[b] = buf + rv * 128 + ((hf ^ (rv & 7)) << 4);
            }
        }
        uint32_t phase = 0, kbar = bar;
        uint4 qf[6];
        auto load_q = [&](int u) {
            const uint32_t* q = &g_early[u / UPB].q[j * 4];
#pragma unroll
            for (int i = 0; i < 6; i++) qf[i] = ld_relaxed_v4(q + i * 16);
        };
        load_q(uk);
        int uq[LAG];
        uint32_t sq[LAG];
#pragma unroll
        for (int i = 0; i < LAG; i++) { uq[i] = -1; sq[i] = 0; }
        uint4 mv = make_uint4(0u, 0u, 0u, 0u);
        float freed = UPB;
        while (true) {
            const int uv = uq[0];
            uint32_t sv = sq[0];
#pragma unroll
            for (int i = 0; i + 1 < LAG; i++) { uq[i] = uq[i + 1]; sq[i] = sq[i + 1]; }
            uq[LAG - 1] = uk;
            if (uk < NUNITS) {
                PH(7);
#pragma unroll 1
                for (int it = 0; it < SPIN_MAX; it++) {
                    uint32_t lo = 0xffffffffu;
#pragma unroll
                    for (int i = 0; i < 6; i++) lo = min(min(lo, min(qf[i].x, qf[i].y)), min(qf[i].z, qf[i].w));
                    if (all(lo != 0)) break;
                    __nanosleep(250);
                    load_q(uk);
                }
                mbar_wait(kbar, phase); phase ^= 1;
                PH(0); ARR();
                TSI(0, 16); TSI(1, 18);
                float acc[2][4][4] = {};
#pragma unroll
                for (int ks = 0; ks < 12; ks++) {
                    const uint4 qq = qf[ks >> 1];
                    const uint32_t b0 = (ks & 1) ? qq.z : qq.x, b1 = (ks & 1) ? qq.w : qq.y;
#pragma unroll
                    for (int mt = 0; mt < 4; mt++) {
                        uint32_t a[4];
                        ldsm4(a, (koff[ks >> 2] ^ ((ks & 3) << 5)) + mt * 6144);
                        mma16816(acc[ks & 1][mt], a, b0, b1);
                    }
                }
                PH(1);
                TSI(0, 17); TSI(1, 19);
                if (uv < NUNITS && kbar == bar) request_tile(buf, uv >= 0 ? &p.v : &p.k, uv >= 0 ? uv : uk + (wk < NSPARE ? 2 : 1) * nstatic, bar, pol);
                const float sa = sel4(j, acc[0][0][0], acc[0][1][0], acc[0][2][0], acc[0][3][0]) + sel4(j, acc[1][0][0], acc[1][1][0], acc[1][2][0], acc[1][3][0]);
                const float sc = sel4(j, acc[0][0][2], acc[0][1][2], acc[0][2][2], acc[0][3][2]) + sel4(j, acc[1][0][2], acc[1][1][2], acc[1][2][2], acc[1][3][2]);
                const uint32_t raw = pack_bf16(sa, sc);
                const float scale = -0.07216878364870322f;
                const uint32_t sk = pack_bf16(lo_f(raw) * scale, hi_f(raw) * scale);
                sq[LAG - 1] = sk;
                if (uk >= POOL0) st_relaxed(&g_st.score[uk - POOL0][lane], sk ? sk : 0x80008000u);
                int a = (int)(sk << 16), b = (int)(sk & 0xffff0000u);
                a ^= (a >> 31) & 0x7fff0000; b ^= (b >> 31) & 0x7fff0000;
                const int mx = __reduce_max_sync(0xffffffffu, max(a, b));
                if (lane == 0) st_relaxed(&g_early[uk / UPB].umax[uk % UPB], (uint32_t)mx | 1u);
            }
            if (uv < 0) {
                if (wk < NSPARE) {
                    const int d = uk < nstatic ? SM_W - SM_KV : SM_KV - SM_W;
#pragma unroll
                    for (int b = 0; b < 3; b++) koff[b] += d;
                    kbar = uk < nstatic ? bar + NWORK * 8 : bar;
                    phase = uk >= nstatic;
                }
                uk += nstatic;
                load_q(uk);
                continue;
            }
            if (uv >= NUNITS) break;
            const int bh = uv / UPB;
#pragma unroll 1
            for (int it = 0; it < SPIN_MAX; it++) {
                if (all((mv.x & mv.y & mv.z & mv.w & 1u) && (uv < POOL0 || sv != 0) && freed == UPB)) break;
                mv = ld_relaxed_v4(&g_early[bh].umax[lane * 4]);
                if (bh >= RING && bh < RED0) freed = __uint_as_float(ld_relaxed_u32(&g_st.oacc[oidx(bh - RING, (lane & 7) * 8)].w));
                if (uv >= POOL0) sv = ld_relaxed_u32(&g_st.score[uv - POOL0][lane]);
            }
            PH(2);
            int un = NUNITS, vn = 0;
            draw(un, g_work, uk < NUNITS && lane == 0);
            uint32_t tdraw;
            asm volatile("mov.u32 %0, %%globaltimer_lo;" : "=r"(tdraw));
            draw(vn, g_work + 32, uq[0] >= POOL0 && lane == 0);
            int mx = __reduce_max_sync(0xffffffffu, max(max((int)mv.x, (int)mv.y), max((int)mv.z, (int)mv.w))) & 0xffff0000;
            mx ^= (mx >> 31) & 0x7fff0000;
            const float m = __int_as_float(mx);
            const float l2e = 1.4426950408889634f;
            const uint32_t pp = pack_bf16(exp2f((lo_f(sv) - m) * l2e), exp2f((hi_f(sv) - m) * l2e));
            uint32_t pb[8];
#pragma unroll
            for (int t = 0; t < 4; t++) {
                pb[2 * t] = __shfl_sync(0xffffffffu, pp, 8 * j + t);
                pb[2 * t + 1] = __shfl_sync(0xffffffffu, pp, 8 * j + 4 + t);
            }
            float lacc[4] = {};
            const uint32_t ones[4] = {0x3f803f80u, 0x3f803f80u, 0x3f803f80u, 0x3f803f80u};
#pragma unroll
            for (int t = 0; t < 4; t++) mma16816(lacc, ones, pb[2 * t], pb[2 * t + 1]);
            if (uv < nstatic) {
                asm volatile("bar.sync 2, %0;" :: "n"((NWORK + 2) * 32) : "memory");
                TSW(3);
            }
            const int grp = 16 * j + 4 * (g & 1) + (g >> 1);
            uint32_t mode = (bh >= RED0) + (bh >= NBH - 4);
            float tag = mode ? 1.f : (float)(bh + 1), tag2 = tag;
            void* dst = mode == 0 ? (void*)&g_ring[bh % RING][uv % UPB][grp] :
                        mode == 1 ? (void*)&g_st.oacc[oidx(bh, grp)] : (void*)&g_st.ox[uv % OREP].w[0][oidx(bh & 3, grp) * 4];
            if (mode == 2 && lane < 2) red_f2(reinterpret_cast<float*>(&g_st.lx.w[lane][(bh & 3) * 256]), lacc[0], 1.f);
            un = __shfl_sync(0xffffffffu, un, 0) + (LAG + 1) * nstatic;
            vn = __shfl_sync(0xffffffffu, vn, 0);
            if (uq[0] >= POOL0) uq[0] = POOL0 + vn;
            if (vn == FW_TICKET && lane == 0) st_relaxed(g_st.fw_time, tdraw | 1u);
            if (uq[0] < NUNITS && un >= NUNITS) {
                mv = ld_relaxed_v4(&g_early[uq[0] / UPB].umax[lane * 4]);
                if (uq[0] < RED0 * UPB) freed = 0.f;
                if (uq[0] >= POOL0) sq[0] = ld_relaxed_u32(&g_st.score[uq[0] - POOL0][lane]);
            }
            pin(dst); pin(mode); pin(tag); pin(tag2); pin(voff[0]); pin(voff[1]); pin(voff[2]);
            PH(3);
            mbar_wait(bar, phase); phase ^= 1;
            PH(4); ARR(); CK(12, lds32(buf));
            float acc[12][4] = {};
#pragma unroll
            for (int t = 0; t < 4; t++) {
#pragma unroll
                for (int mt = 0; mt < 12; mt++) {
                    uint32_t a[4];
                    ldsm4t(a, (voff[mt >> 2] ^ ((mt & 3) << 5)) + t * 6144);
                    mma16816(acc[mt], a, pb[2 * t], pb[2 * t + 1]);
                }
            }
            PH(5);
            if (lane == 0) PROG(un);
            if (un < NUNITS || uq[0] < NUNITS) request_tile(buf, un < NUNITS ? &p.k : &p.v, un < NUNITS ? un : uq[0], bar, pol);
            if (un < NUNITS || uq[0] < NUNITS) CK(11, 0);
            float o[6];
#pragma unroll
            for (int e = 0; e < 6; e++) {
                const int q = e % 3, c = (e / 3) * 2;
                o[e] = sel4(j, acc[q][c], acc[3 + q][c], acc[6 + q][c], acc[9 + q][c]);
            }
            put_groups(dst, mode, o, tag, tag2);
            CK(13, 0);
            if (un < NUNITS) load_q(un);
            if (lane == 0) red_f2(&g_st.lsum[bh][0].x, lacc[0], 1.f);
            PH(6);
            if (uq[0] >= NUNITS && un >= NUNITS) break;
            uk = un;
            if (uq[0] < NUNITS && un < NUNITS) {
                const int nb = uq[0] / UPB;
                mv = ld_relaxed_v4(&g_early[nb].umax[lane * 4]);
                freed = nb >= RING && nb < RED0 ? __uint_as_float(ld_relaxed_u32(&g_st.oacc[oidx(nb - RING, (lane & 7) * 8)].w)) : UPB;
                if (uq[0] >= POOL0) sq[0] = ld_relaxed_u32(&g_st.score[uq[0] - POOL0][lane]);
            }
        }
        TSW(4 + wk);
        return;
    }

    __nv_bfloat16* xs = reinterpret_cast<__nv_bfloat16*>(smem + SM_X);
    float* red = reinterpret_cast<float*>(smem + SM_RED);
    const int frow = (lane & 7) + ((lane >> 4) << 3), fcol = (lane >> 3) & 1;
    const uint32_t f64b = sb + (frow * 4 + (fcol ^ ((frow >> 1) & 3))) * 16;
    if (cta < NQ_CTAS) {
        uint2 xr[5];
        if (warp < NB) {
#pragma unroll
            for (int i = 0; i < 5; i++) xr[i] = *reinterpret_cast<const uint2*>(p.x + warp * DM + i * 128 + lane * 4);
        }
        TS(26);
        if (warp < NB) {
            float v[20];
#pragma unroll
            for (int i = 0; i < 5; i++) {
                v[4 * i] = lo_f(xr[i].x); v[4 * i + 1] = hi_f(xr[i].x); v[4 * i + 2] = lo_f(xr[i].y); v[4 * i + 3] = hi_f(xr[i].y);
            }
            layernorm20(v);
#pragma unroll
            for (int i = 0; i < 5; i++)
                *reinterpret_cast<uint2*>(xs + warp * XPITCH + i * 128 + lane * 4) =
                    make_uint2(pack_bf16(v[4 * i], v[4 * i + 1]), pack_bf16(v[4 * i + 2], v[4 * i + 3]));
        }
        TS(27);
        aux_sync();
        mbar_wait(sb + BAR_WQ, 0);
        TS(1);
        const uint32_t xfrag = sb + SM_X + ((g & 3) * XPITCH + 2 * j) * 2;
        float acc[3][4] = {};
#pragma unroll
        for (int s = 0; s < 5; s++) {
            const int ks = warp * 5 + s;
            const uint32_t b0 = lds32(xfrag + ks * 32), b1 = lds32(xfrag + ks * 32 + 16);
            const int row = ks * 16 + frow;
#pragma unroll
            for (int mt = 0; mt < 3; mt++) {
                uint32_t a[4];
                ldsm4t(a, sb + SM_W + (row * 6 + 2 * mt + fcol) * 16);
                mma16816(acc[mt], a, b0, b1);
            }
        }
        if (j < 2) {
#pragma unroll
            for (int mt = 0; mt < 3; mt++) {
                *reinterpret_cast<float2*>(red + (warp * 48 + mt * 16 + g) * 4 + 2 * j) = make_float2(acc[mt][0], acc[mt][1]);
                *reinterpret_cast<float2*>(red + (warp * 48 + mt * 16 + 8 + g) * 4 + 2 * j) = make_float2(acc[mt][2], acc[mt][3]);
            }
        }
        aux_sync();
        if (tid < 96) {
            const int b = tid & 3, cp = tid >> 2;
            float s0 = 0.f, s1 = 0.f;
#pragma unroll
            for (int w = 0; w < 8; w++) { s0 += red[(w * 48 + 2 * cp) * 4 + b]; s1 += red[(w * 48 + 2 * cp + 1) * 4 + b]; }
            const int h = cta >> 2, d = (cta & 3) * 48 + 2 * cp;
            const int ch = d >> 3, jj = (d & 7) >> 1;
            st_relaxed(&g_early[b * NH + h].q[(ch >> 2) * 16 + jj * 4 + (ch & 3)], pack_neg(s0, s1));
        }
        TS(28);
    }
    if (warp >= 4 && warp < 4 + NSPARE) {
        uint64_t pol;
        asm volatile("createpolicy.fractional.L2::evict_first.b64 %0, 1.0;" : "=l"(pol));
        if (cta >= NQ_CTAS) spin_ns(WO_AT_NS);
        asm volatile("fence.proxy.async.shared::cta;" ::: "memory");
        request_tile(sb + SM_W + (warp - 4) * TILE_BYTES, &p.k, (NWORK + warp - 4) * grid + cta, sb + BAR_KV + (NWORK + warp - 4) * 8, pol);
    }
    fin_sync<3>();
    mbar_wait(sb + BAR_WO, 0);
    TS(7);
    uint32_t part = sb + SM_RED + (warp * 32 + 8 * j + g) * 4;

#pragma unroll 1
    for (int b = 0; b < NB; b++) {
        if (cta >= NE_CTAS) {
            uint32_t a[6][2][4];
#pragma unroll
            for (int s = 0; s < 6; s++) {
#pragma unroll
                for (int mt = 0; mt < 2; mt++) ldsm4t(a[s][mt], (f64b ^ (mt * 32)) + SM_A + (warp * 6 + s) * 1024);
            }
            const int bh = b * NH + 28 + (warp >> 1);
            const int side = near_side(sb) ^ 1;
            const void* osrc[OREP];
#pragma unroll
            for (int c = 0; c < OREP; c++)
                osrc[c] = b == NB - 1 ? (const void*)&g_st.ox[c].w[side][oidx(bh & 3, (warp & 1) * 32 + lane) * 4] : &g_st.oacc[oidx(bh, (warp & 1) * 32 + lane)];
            const void* lsrc = b == NB - 1 ? (const void*)&g_st.lx.w[side][(bh & 3) * 256] : g_st.lsum[bh];
            wait_row_o(bh, 1);
            const float rl = rcp_approx(wait_sum(lsrc, UPB)) * (b == NB - 1 ? 1.f : 1.f / OREP), full = b == NB - 1 ? UPB : UPB * OREP;
            float4 ov;
            float px, py, pz;
            Warm warm;
#pragma unroll 1
            for (int it = 0; it < SPIN_MAX; it++) {
                float4 oc[OREP];
#pragma unroll
                for (int c = 0; c < OREP; c++) oc[c] = ld_relaxed_f4(osrc[c]);
                warm();
                ov = oc[0];
#pragma unroll
                for (int c = 1; c < OREP; c++) { ov.x += oc[c].x; ov.y += oc[c].y; ov.z += oc[c].z; ov.w += oc[c].w; }
                ov.x *= rl; ov.y *= rl; ov.z *= rl;
                px = __shfl_xor_sync(0xffffffffu, ov.x, 4); py = __shfl_xor_sync(0xffffffffu, ov.y, 4); pz = __shfl_xor_sync(0xffffffffu, ov.z, 4);
                if (all(ov.w == full)) break;
            }
            CK(0, __float_as_uint(ov.x));
            if (ov.x != 1.2345f && warp == 7) TSW(14);
            const uint32_t w[3] = {pack_bf16(ov.x, px), pack_bf16(ov.y, py), pack_bf16(ov.z, pz)};
            float acc[2][2][4] = {};
#pragma unroll
            for (int s = 0; s < 6; s++) {
                const uint32_t b0 = __shfl_sync(0xffffffffu, w[s % 3], (s / 3) * 16 + j);
                const uint32_t b1 = __shfl_sync(0xffffffffu, w[s % 3], (s / 3) * 16 + 8 + j);
#pragma unroll
                for (int mt = 0; mt < 2; mt++) mma16816(acc[mt][s & 1], a[s][mt], b0, b1);
            }
            sts32f(part, sel4(j, acc[0][0][0] + acc[0][1][0], acc[0][0][2] + acc[0][1][2], acc[1][0][0] + acc[1][1][0], acc[1][0][2] + acc[1][1][2]));
            CK(1, 0);
            fin_arrive<4>();
            warm.done(sb + SM_MISC);
            fin_sync<5>();
            if (cta < NE_CTAS + 4 && tid < 56) reinterpret_cast<uint4*>(&g_early[b * NH + 28 + cta - NE_CTAS])[tid] = make_uint4(0u, 0u, 0u, 0u);
        } else {
            const int bh = b * NH + (cta >> 2);
            if (warp == 0) wait_row_o(bh, UPB);
            aux_sync();
            if (warp < 5) {
                uint32_t ob[12][2];
                load_o<4>(ob, bh, 0, j);
                float acc[2][2][4] = {};
#pragma unroll
                for (int ks = 0; ks < 12; ks++) {
#pragma unroll
                    for (int mt = 0; mt < 2; mt++) {
                        uint32_t a[4];
                        ldsm4t(a, (f64b ^ (mt * 32)) + SM_A + warp * 12288 + ks * 1024);
                        mma16816(acc[mt][ks & 1], a, ob[ks][0], ob[ks][1]);
                    }
                }
                red_f2(&g_st.attn[b][(cta & 3) * 160 + warp * 32 + 8 * j + g].x,
                       sel4(j, acc[0][0][0] + acc[0][1][0], acc[0][0][2] + acc[0][1][2], acc[1][0][0] + acc[1][1][0], acc[1][0][2] + acc[1][1][2]), 1.f);
                TS(8);
            } else if (warp > 5 && (cta & 3) == 0 && tid - 192 < 56) {
                reinterpret_cast<uint4*>(&g_early[bh])[tid - 192] = make_uint4(0u, 0u, 0u, 0u);
            }
        }
        if (b < NB - 2) continue;

        if (is_f(cta)) {
            uint32_t ga[10][2][4];
            uint4 hv[5] = {};
            const uint32_t hfrag = sb + SM_X + min(g, 4) * HPITCH + ((warp >> 1) * 80 + 4 * j) * 4;
#pragma unroll
            for (int s = 0; s < 5; s++) lds128_if(hv[s], hfrag + s * 64, b == NB - 1);
            if (b == NB - 1) mbar_wait(sb + BAR_FW + warp * 8, 0);
            if (warp == 7) TSW(10);
            CK(12, lds32(sb + SM_W));
#pragma unroll
            for (int s = 0; s < 10; s++) {
#pragma unroll
                for (int mt = 0; mt < 2; mt++) ldsm4t(ga[s][mt], (f64b ^ (mt * 32)) + SM_W + (warp * 10 + s) * 1024);
            }
            const uint32_t gpart = sb + SM_RED + (warp >> 1) * 640 + j * 256 + ((g + 2 * j) & 7) * 16 + (warp & 1) * 8;
            mbar_wait(sb + BAR_H, b & 1);
#pragma unroll
            for (int s = 0; s < 5; s++) lds128_if(hv[s], hfrag + s * 64, g == b);
            CK(4, hv[0].x);
            float acc[2][2][4] = {};
#pragma unroll
            for (int s = 0; s < 10; s++) {
#pragma unroll
                for (int mt = 0; mt < 2; mt++)
                    mma16816(acc[mt][s & 1], ga[s][mt], (s & 1) ? hv[s >> 1].z : hv[s >> 1].x, (s & 1) ? hv[s >> 1].w : hv[s >> 1].y);
            }
#pragma unroll
            for (int mt = 0; mt < 2; mt++) {
                if (j < 3) sts64f(gpart + mt * 2560, acc[mt][0][0] + acc[mt][1][0], acc[mt][0][2] + acc[mt][1][2]);
                if (j < 2) sts64f(gpart + mt * 2560 + 128, acc[mt][0][1] + acc[mt][1][1], acc[mt][0][3] + acc[mt][1][3]);
            }
            CK(5, 0);
            asm volatile("bar.arrive 4, 320;" ::: "memory");
        } else if (is_g(cta)) {
            const uint32_t* asrc = &g_st.ax[0].w[(~b & 1) * 2 + near_side(sb)][warp * 128 + ((g >> 2) * 2 + (j >> 1)) * 32 + (g & 3) * 8 + (j & 1) * 4];
            const uint32_t ypart = sb + SM_RED2 + warp * 512 + j * 128 + ((g + 2 * j) & 7) * 16;
            uint32_t wb[12][4];
            if (b == NB - 1) mbar_wait(sb + BAR_FW + warp * 8, 0);
            if (warp == 7) TSW(11);
            CK(13, lds32(sb + SM_W));
            {
                const int jj = (lane & 7) >> 1, q = jj >> 1, hi = lane >> 4;
                const uint32_t base = sb + SM_W + warp * 6144 + q * 512 + ((hi ^ q) * 4 + (jj & 1) * 2 + (lane & 1)) * 32 + ((fcol ^ hi ^ q) << 4);
#pragma unroll
                for (int s = 0; s < 12; s++) ldsm4t(wb[s], base + (s >> 2) * 2048 + (s & 1) * 1024 + (s & 2) * 128);
            }
            mbar_wait(sb + BAR_H, b & 1);
            uint4 va[3];
            Warm warm;
#pragma unroll 1
            for (int it = 0; it < SPIN_MAX; it++) {
                uint32_t lo = 0xffffffffu;
#pragma unroll
                for (int i = 0; i < 3; i++) va[i] = ld_relaxed_v4(asrc + i * 4096);
                warm();
#pragma unroll
                for (int i = 0; i < 3; i++) lo = min(min(lo, min(va[i].x, va[i].y)), min(va[i].z, va[i].w));
                if (all(lo != 0)) break;
            }
            CK(8, va[0].x);
            if (va[0].x != 0x12345 && warp == 7) TSW(15);
            float acc[6][4] = {};
#pragma unroll
            for (int s = 0; s < 12; s++) {
                const uint4 v = va[s >> 2];
                mma16816(acc[s % 6], wb[s], (s & 2) ? v.z : v.x, (s & 2) ? v.w : v.y);
            }
            float y[4];
#pragma unroll
            for (int e = 0; e < 4; e++) y[e] = j < 2 ? (acc[0][e] + acc[2][e]) + acc[4][e] : (acc[1][e] + acc[3][e]) + acc[5][e];
            sts128f(ypart, y[0], y[1], y[2], y[3]);
            CK(9, 0);
            fin_arrive<6>();
            warm.done(sb + SM_MISC);
        }
    }
}

typedef CUresult (*EncodeFn)(CUtensorMap*, CUtensorMapDataType, cuuint32_t, void*, const cuuint64_t*, const cuuint64_t*,
                             const cuuint32_t*, const cuuint32_t*, CUtensorMapInterleave, CUtensorMapSwizzle,
                             CUtensorMapL2promotion, CUtensorMapFloatOOBfill);

CUtensorMap make_map(EncodeFn enc, void* ptr, uint64_t cols, uint64_t rows, uint32_t bcols, uint32_t brows,
                     CUtensorMapSwizzle sw, CUtensorMapL2promotion promo) {
    CUtensorMap m;
    const cuuint64_t dims[2] = {cols, rows};
    const cuuint64_t strides[1] = {cols * 2};
    const cuuint32_t box[2] = {bcols, brows};
    const cuuint32_t es[2] = {1, 1};
    enc(&m, CU_TENSOR_MAP_DATA_TYPE_BFLOAT16, 2, ptr, dims, strides, box, es, CU_TENSOR_MAP_INTERLEAVE_NONE, sw, promo,
        CU_TENSOR_MAP_FLOAT_OOB_FILL_NONE);
    return m;
}

}

extern "C" void kernel_launch(void* const* d_in, const int* in_sizes, int n_in, void* d_out, int out_size) {
    (void)in_sizes; (void)n_in; (void)out_size;
    static EncodeFn enc = nullptr;
    static int sms = 0;
    if (!enc) {
        cudaDriverEntryPointQueryResult qr;
        cudaGetDriverEntryPoint("cuTensorMapEncodeTiled", (void**)&enc, cudaEnableDefault, &qr);
        int dev = 0;
        cudaGetDevice(&dev);
        cudaDeviceGetAttribute(&sms, cudaDevAttrMultiProcessorCount, dev);
        cudaFuncSetAttribute(fused_decode_kernel, cudaFuncAttributeMaxDynamicSharedMemorySize, SM_TOTAL);
    }
    if (sms < NCTAS) return;
    const CUtensorMapL2promotion WPROMO = CU_TENSOR_MAP_L2_PROMOTION_L2_128B;
    Params p;
    p.k = make_map(enc, d_in[1], 64, (uint64_t)NBH * SK * 3, 64, TILE_ROWS, CU_TENSOR_MAP_SWIZZLE_128B, CU_TENSOR_MAP_L2_PROMOTION_NONE);
    p.v = make_map(enc, d_in[2], 64, (uint64_t)NBH * SK * 3, 64, TILE_ROWS, CU_TENSOR_MAP_SWIZZLE_128B, CU_TENSOR_MAP_L2_PROMOTION_NONE);
    p.wq = make_map(enc, d_in[3], NH * DH, DM, 48, 160, CU_TENSOR_MAP_SWIZZLE_NONE, WPROMO);
    p.wo = make_map(enc, d_in[4], DM, NH * DH, 32, DH, CU_TENSOR_MAP_SWIZZLE_64B, WPROMO);
    p.wg = make_map(enc, d_in[7], FF, DM, 32, 160, CU_TENSOR_MAP_SWIZZLE_64B, WPROMO);
    p.wu = make_map(enc, d_in[8], FF, DM, 32, 160, CU_TENSOR_MAP_SWIZZLE_64B, WPROMO);
    {
        const cuuint64_t dims[4] = {DM, 2, 8, FF / 16}, strides[3] = {8 * DM * 2, DM * 2, 16 * DM * 2};
        const cuuint32_t box[4] = {16, 2, 8, 12}, es[4] = {1, 1, 1, 1};
        enc(&p.wd, CU_TENSOR_MAP_DATA_TYPE_BFLOAT16, 4, d_in[9], dims, strides, box, es, CU_TENSOR_MAP_INTERLEAVE_NONE,
            CU_TENSOR_MAP_SWIZZLE_32B, WPROMO, CU_TENSOR_MAP_FLOAT_OOB_FILL_NONE);
    }
    p.x = (const __nv_bfloat16*)d_in[0];
    p.wr = (const __nv_bfloat16*)d_in[6];
    p.out = (__nv_bfloat16*)d_out;
    fused_decode_kernel<<<NCTAS, NTHREADS, SM_TOTAL, cudaStreamPerThread>>>(p);
}
```

```cpp
#include <cuda_runtime.h>
#include <cuda_bf16.h>
#include <cuda.h>
#include <stdint.h>

namespace {

constexpr int NB = 4, NH = 32, SK = 8192, DH = 192, DM = 640, FF = 1536;
constexpr int NBH = NB * NH;
constexpr int TILE = 64;
constexpr int UPB = SK / TILE;
constexpr int NUNITS = NBH * UPB;
constexpr int TILE_BYTES = TILE * DH * 2;
constexpr int TILE_ROWS = TILE * 3;
constexpr int NCTAS = 132;
constexpr int NQ_CTAS = 128;
constexpr int NE_CTAS = 112;
__host__ __device__ constexpr bool is_f(int cta) { return cta < NE_CTAS && cta % 14 < 11 && !(cta & 1); }
__host__ __device__ constexpr bool is_g(int cta) { return cta < NE_CTAS && cta % 14 < 11 && (cta & 1); }
__host__ __device__ constexpr int ffn_slice(int cta) { return cta / 14 * ((cta & 1) ? 5 : 6) + cta % 14 / 2; }

#define NWORK 2
#define NSPARE 1
#define LAG 2
#define NPOOL 768
#define RED0 116
#define RING 12
#define OREP 3
#define K0_DELAY_NS 1200
#define WO_AT_NS 3800
#define FW_TICKET 648
#define FW_AT_NS 3250
#define FW_GAP 280
#define FW_MID 2000
#define FW_GAP2 200
#define HGATE_NS 700
#define SLOT_TICKS 8
#define SLOT_OPEN 3
#define PH_O 0
#define PH_H 1
#define PH_M 3
#define NPROBE 24
constexpr int NAUX = 8;
constexpr int NTHREADS = (NAUX + NWORK + 2) * 32;
constexpr int SPIN_MAX = 1 << 22;

constexpr int SM_KV = 0;
constexpr int SM_A = SM_KV + NWORK * TILE_BYTES;
constexpr int SM_W = SM_A + 61440;
constexpr int SM_X = SM_W + 81920;
constexpr int XPITCH = 648;
constexpr int HPITCH = 1344;
constexpr int SM_RED = SM_X + 5 * HPITCH + 64;
constexpr int SM_RED2 = SM_RED + 8 * 48 * 4 * 4;
constexpr int SM_MISC = SM_RED2 + 4096;
constexpr int BAR_WQ = SM_MISC + 32, BAR_WO = SM_MISC + 40, SM_SIDE = SM_MISC + 48, BAR_H = SM_MISC + 56, BAR_FW = SM_MISC + 64;
constexpr int BAR_KV = BAR_FW + 64;
constexpr int SM_TOTAL = BAR_KV + 2 * NWORK * 8;
static_assert(LAG == 2 && SM_W % 1024 == 0 && NB * XPITCH * 2 <= 4 * HPITCH && SM_RED % 128 == 0, "smem layout");

struct Params {
    CUtensorMap k, v;
    CUtensorMap wq;
    CUtensorMap wo;
    CUtensorMap wg, wu;
    CUtensorMap wd;
    const __nv_bfloat16 *x, *wr;
    __nv_bfloat16* out;
};

struct Early {
    uint32_t q[96];
    uint32_t umax[UPB];
};
struct Twin { uint32_t w[4][1024]; };
constexpr int PROBE = 1024 - 32;
#define LSTRIDE 16
struct State {
    Twin ax[3];
    Twin hx;
    Twin ox[OREP];
    Twin lx;
    float4 oacc[NBH * 64];
    float2 attn[NB][DM];
    uint32_t fw_time[32];
    float2 lsum[NBH][LSTRIDE];
    uint32_t score[NPOOL][32];
};
__host__ __device__ constexpr int oidx(int row, int grp) {
    return (row >> 2) * 256 + ((row & 1) * 2 + (grp >> 5)) * 64 + (row & 2) * 16 + (grp & 31);
}
constexpr int STATE_V4 = ((sizeof(State) / 32 + NQ_CTAS - 1) / NQ_CTAS) * 2;
static_assert(sizeof(State) % 32 == 0, "State is cleared in whole sectors");
static_assert(sizeof(Early) == 56 * 16, "an Early entry is cleared by 56 threads");
struct Scratch {
    State st;
    unsigned work[64];
    unsigned cnt_z[32];
    Early early[NBH];
    alignas(4096) float4 ring[RING][UPB][64];
};
constexpr size_t PAGE = 2u << 20;
static_assert(sizeof(Scratch) <= PAGE, "scratch must fit one page");
__device__ __align__(128) unsigned char g_raw[2 * PAGE];
__device__ __forceinline__ Scratch* scratch() {
    return reinterpret_cast<Scratch*>((reinterpret_cast<uintptr_t>(g_raw) + PAGE - 1) & ~(uintptr_t)(PAGE - 1));
}
#define g_early scratch()->early
#define g_st scratch()->st
#define g_ring scratch()->ring
#define g_cnt_z scratch()->cnt_z
#define g_work scratch()->work
#define ALL_LOADERS 0
#define TS(i)
#define TSW(i)
#define TS2(i)
#define TSI(n, i)
#define PH(i)
#define CK(i, dep)
#define ARR()
#define PROG(u)

__device__ __forceinline__ uint32_t s2u(const void* p) { return (uint32_t)__cvta_generic_to_shared(p); }
__device__ __forceinline__ void mbar_init(uint32_t bar, int cnt) {
    asm volatile("mbarrier.init.shared::cta.b64 [%0], %1;" :: "r"(bar), "r"(cnt) : "memory");
}
__device__ __forceinline__ void mbar_wait(uint32_t bar, uint32_t parity) {
    asm volatile("{\n.reg .pred p;\n.reg .u32 n;\nmov.u32 n, 0;\nWAIT_LOOP:\n"
                 "mbarrier.try_wait.parity.shared::cta.b64 p, [%0], %1;\n"
                 "@p bra WAIT_DONE;\nadd.u32 n, n, 1;\nsetp.lt.u32 p, n, %2;\n@p bra WAIT_LOOP;\nWAIT_DONE:\n}"
                 :: "r"(bar), "r"(parity), "n"(SPIN_MAX) : "memory");
}
__device__ __forceinline__ void request_tile(uint32_t dst, const CUtensorMap* tm, int unit, uint32_t bar, uint64_t pol) {
    asm volatile("{\n.reg .pred p;\nelect.sync _|p, 0xffffffff;\n"
                 "@p mbarrier.arrive.expect_tx.shared::cta.b64 _, [%2], %6;\n"
                 "@p cp.async.bulk.tensor.2d.shared::cluster.global.mbarrier::complete_tx::bytes.L2::cache_hint "
                 "[%0], [%1, {%3, %4}], [%2], %5;\n}"
                 :: "r"(dst), "l"(tm), "r"(bar), "r"(0), "r"(unit * TILE_ROWS), "l"(pol), "n"(TILE_BYTES) : "memory");
}
__device__ __forceinline__ void put_groups(void* dst, int mode, const float (&o)[6], float tag, float tag2) {
    asm volatile("{\n.reg .pred s, r, t;\n.reg .b128 u, v;\n.reg .b64 a, b;\n"
                 "setp.eq.s32 s|r, %1, 0;\nsetp.eq.s32 t, %1, 2;\n"
                 "@r red.relaxed.gpu.global.add.v4.f32 [%0], {%2,%3,%4,%8};\n"
                 "@t red.relaxed.gpu.global.add.v4.f32 [%0+4096], {%2,%3,%4,%8};\n"
                 "@r red.relaxed.gpu.global.add.v4.f32 [%0+128], {%5,%6,%7,%9};\n"
                 "@t red.relaxed.gpu.global.add.v4.f32 [%0+4224], {%5,%6,%7,%9};\n"
                 "mov.b64 a, {%2, %3};\nmov.b64 b, {%4, %8};\nmov.b128 u, {a, b};\n"
                 "mov.b64 a, {%5, %6};\nmov.b64 b, {%7, %9};\nmov.b128 v, {a, b};\n"
                 "@s st.relaxed.gpu.global.b128 [%0], u;\n@s st.relaxed.gpu.global.b128 [%0+128], v;\n}"
                 :: "l"(dst), "r"(mode), "f"(o[0]), "f"(o[1]), "f"(o[2]), "f"(o[3]), "f"(o[4]), "f"(o[5]), "f"(tag), "f"(tag2) : "memory");
}
__device__ __forceinline__ void request_box(uint32_t dst, const CUtensorMap* tm, int col, int row, uint32_t bar, uint32_t bytes) {
    asm volatile("{\n.reg .pred p, q;\nelect.sync _|p, 0xffffffff;\nsetp.ne.and.u32 q, %5, 0, p;\n"
                 "@q mbarrier.arrive.expect_tx.shared::cta.b64 _, [%2], %5;\n"
                 "@p cp.async.bulk.tensor.2d.shared::cluster.global.mbarrier::complete_tx::bytes [%0], [%1, {%3, %4}], [%2];\n}"
                 :: "r"(dst), "l"(tm), "r"(bar), "r"(col), "r"(row), "r"(bytes) : "memory");
}
__device__ __forceinline__ uint32_t lds32(uint32_t addr) {
    uint32_t v;
    asm volatile("ld.shared.u32 %0, [%1];" : "=r"(v) : "r"(addr) : "memory");
    return v;
}
__device__ __forceinline__ void ldsm4(uint32_t (&r)[4], uint32_t addr) {
    asm volatile("ldmatrix.sync.aligned.m8n8.x4.shared.b16 {%0,%1,%2,%3}, [%4];"
                 : "=r"(r[0]), "=r"(r[1]), "=r"(r[2]), "=r"(r[3]) : "r"(addr) : "memory");
}
__device__ __forceinline__ void ldsm4t(uint32_t (&r)[4], uint32_t addr) {
    asm volatile("ldmatrix.sync.aligned.m8n8.x4.trans.shared.b16 {%0,%1,%2,%3}, [%4];"
                 : "=r"(r[0]), "=r"(r[1]), "=r"(r[2]), "=r"(r[3]) : "r"(addr) : "memory");
}
__device__ __forceinline__ void mma16816(float (&c)[4], const uint32_t (&a)[4], uint32_t b0, uint32_t b1) {
    asm volatile("mma.sync.aligned.m16n8k16.row.col.f32.bf16.bf16.f32 {%0,%1,%2,%3}, {%4,%5,%6,%7}, {%8,%9}, {%0,%1,%2,%3};"
                 : "+f"(c[0]), "+f"(c[1]), "+f"(c[2]), "+f"(c[3])
                 : "r"(a[0]), "r"(a[1]), "r"(a[2]), "r"(a[3]), "r"(b0), "r"(b1));
}
struct Warm {
    float c[4] = {};
    __device__ __forceinline__ void operator()() {
        asm volatile("mma.sync.aligned.m16n8k8.row.col.f32.bf16.bf16.f32 {%0,%1,%2,%3}, {%4,%4}, {%4}, {%0,%1,%2,%3};"
                     : "+f"(c[0]), "+f"(c[1]), "+f"(c[2]), "+f"(c[3]) : "r"(0));
    }
    __device__ __forceinline__ void done(uint32_t scrap) {
        asm volatile("{\n.reg .pred p;\nsetp.gt.f32 p, %1, 0f3f800000;\n@p st.shared.f32 [%0], %1;\n}" :: "r"(scrap), "f"(c[0]) : "memory");
    }
};
__device__ __forceinline__ uint4 ld_relaxed_v4(const void* p) {
    uint4 v;
    asm volatile("ld.relaxed.gpu.global.v4.u32 {%0,%1,%2,%3}, [%4];" : "=r"(v.x), "=r"(v.y), "=r"(v.z), "=r"(v.w) : "l"(p) : "memory");
    return v;
}
__device__ __forceinline__ float4 ld_relaxed_f4(const void* p) {
    float4 v;
    asm volatile("ld.relaxed.gpu.global.v4.f32 {%0,%1,%2,%3}, [%4];" : "=f"(v.x), "=f"(v.y), "=f"(v.z), "=f"(v.w) : "l"(p) : "memory");
    return v;
}
__device__ __forceinline__ float2 ld_relaxed_f2(const void* p) {
    float2 v;
    asm volatile("ld.relaxed.gpu.global.v2.f32 {%0,%1}, [%2];" : "=f"(v.x), "=f"(v.y) : "l"(p) : "memory");
    return v;
}
__device__ __forceinline__ float4 ld_relaxed_b128(const void* p) {
    float4 v;
    asm volatile("{\n.reg .b128 t;\n.reg .b64 a, b;\nld.relaxed.gpu.global.b128 t, [%4];\nmov.b128 {a, b}, t;\n"
                 "mov.b64 {%0, %1}, a;\nmov.b64 {%2, %3}, b;\n}" : "=f"(v.x), "=f"(v.y), "=f"(v.z), "=f"(v.w) : "l"(p) : "memory");
    return v;
}
__device__ __forceinline__ void st_relaxed_b128(void* p, float x, float y, float z, float w) {
    asm volatile("{\n.reg .b128 t;\n.reg .b64 a, b;\nmov.b64 a, {%1, %2};\nmov.b64 b, {%3, %4};\nmov.b128 t, {a, b};\n"
                 "st.relaxed.gpu.global.b128 [%0], t;\n}" :: "l"(p), "f"(x), "f"(y), "f"(z), "f"(w) : "memory");
}
__device__ __forceinline__ unsigned ld_acquire(const unsigned* p) {
    unsigned v;
    asm volatile("ld.acquire.gpu.global.u32 %0, [%1];" : "=r"(v) : "l"(p) : "memory");
    return v;
}
__device__ __forceinline__ void st_relaxed(void* p, uint32_t v) {
    asm volatile("st.relaxed.gpu.global.u32 [%0], %1;" :: "l"(p), "r"(v) : "memory");
}
__device__ __forceinline__ void red_f2(float* p, float a, float b) {
    asm volatile("red.relaxed.gpu.global.add.v2.f32 [%0], {%1,%2};" :: "l"(p), "f"(a), "f"(b) : "memory");
}
__device__ __forceinline__ void draw(int& ticket, unsigned* ctr, bool pred) {
    asm volatile("{\n.reg .pred p;\nsetp.ne.u32 p, %2, 0;\n@p atom.relaxed.gpu.global.inc.u32 %0, [%1], 0x7fffffff;\n}"
                 : "+r"(ticket) : "l"(ctr), "r"((uint32_t)pred) : "memory");
}
__device__ __forceinline__ void red_release(unsigned* p) {
    asm volatile("red.release.gpu.global.add.u32 [%0], 1;" :: "l"(p) : "memory");
}
__device__ __forceinline__ uint32_t ld_relaxed_u32(const void* p) {
    uint32_t v;
    asm volatile("ld.relaxed.gpu.global.u32 %0, [%1];" : "=r"(v) : "l"(p) : "memory");
    return v;
}
__device__ __forceinline__ float rcp_approx(float v) {
    float r;
    asm("rcp.approx.ftz.f32 %0, %1;" : "=f"(r) : "f"(v));
    return r;
}
__device__ __forceinline__ float ex2_approx(float v) {
    float e;
    asm("ex2.approx.ftz.f32 %0, %1;" : "=f"(e) : "f"(v));
    return e;
}
__device__ __forceinline__ float sigmoid_approx(float v) { return rcp_approx(1.0f + ex2_approx(v * -1.4426950408889634f)); }
__device__ __forceinline__ float sqrt_approx(float v) {
    float r;
    asm("sqrt.approx.ftz.f32 %0, %1;" : "=f"(r) : "f"(v));
    return r;
}
__device__ __forceinline__ bool all(bool v) { return __all_sync(0xffffffffu, v); }
__device__ __forceinline__ void wait_count(const unsigned* p, unsigned target) {
#pragma unroll 1
    for (int it = 0; it < SPIN_MAX; it++) {
        if (all(ld_acquire(p) >= target)) break;
        __nanosleep(400);
    }
}
__device__ __forceinline__ float wait_sum(const void* p, float n, int nap = 0) {
    float2 v;
#pragma unroll 1
    for (int it = 0; it < SPIN_MAX; it++) {
        v = ld_relaxed_f2(p);
        if (all(v.y >= n)) break;
        if (all(v.y == 0.f)) __nanosleep(600);
        else if (nap) __nanosleep(nap);
    }
    return v.x;
}
__device__ __forceinline__ void wait_row(int bh, float n) { wait_sum(g_st.lsum[bh], n); }
__device__ __forceinline__ void wait_row_o(int bh, float n) {
    wait_row(bh, n);
    if (bh >= RED0) return;
#pragma unroll 1
    for (int it = 0; it < SPIN_MAX; it++) {
        if (all(__uint_as_float(ld_relaxed_u32(&g_st.oacc[oidx(bh, 0)].w)) == UPB)) break;
        __nanosleep(300);
    }
}
constexpr uint32_t SLOT_K = (uint32_t)(((1ull << 32) + SLOT_TICKS - 1) / SLOT_TICKS);
#define SLOT_ASM(t, n, p, phase, k, open) \
    "mov.u32 " n ", 0;\nSLOT:\nmov.u32 " t ", %%globaltimer_lo;\nadd.u32 " n ", " n ", 1;\nsetp.lt.u32 " p ", " n ", 24;\nshr.u32 " t ", " t ", 5;\n" \
    "mad.lo.u32 " t ", " t ", " k ", " phase ";\nsetp.ge.and.u32 " p ", " t ", " open ", " p ";\n@" p " bra.uni SLOT;\n"
template <int PHASE> __host__ __device__ constexpr uint32_t slot_phase() { return SLOT_K / 2 - PHASE * SLOT_K; }
template <int PHASE> __device__ __forceinline__ void wait_slot() {
    if (PHASE < 0) return;
    asm volatile("{\n.reg .pred p;\n.reg .b32 t, n;\n" SLOT_ASM("t", "n", "p", "%0", "%1", "%2") "}"
                 :: "n"(slot_phase<PHASE>()), "n"(SLOT_K), "n"(SLOT_OPEN * SLOT_K) : "memory");
}
__device__ __forceinline__ void wait_clock(uint32_t t, Warm& warm) { while (!all((int)(clock() - t) >= 0)) { warm(); } }
__device__ __forceinline__ void spin_ns(int ns) { const uint32_t t = clock() + ns * 2; while (!all((int)(clock() - t) >= 0)) {} }
__device__ __forceinline__ uint32_t pack_bf16(float lo, float hi) {
    uint32_t r;
    asm("cvt.rn.bf16x2.f32 %0, %1, %2;" : "=r"(r) : "f"(hi), "f"(lo));
    return r;
}
__device__ __forceinline__ float bf16r(float v) { return __uint_as_float(pack_bf16(0.f, v)); }
__device__ __forceinline__ uint32_t nonzero(uint32_t w) { return w ? w : 0x80008000u; }
__device__ __forceinline__ uint32_t pack_neg(float lo, float hi) { return nonzero(pack_bf16(-lo, -hi)); }
__device__ __forceinline__ float lo_f(uint32_t v) { return __uint_as_float(v << 16); }
__device__ __forceinline__ float hi_f(uint32_t v) { return __uint_as_float(v & 0xffff0000u); }
__device__ __forceinline__ float warp_sum(float v) {
#pragma unroll
    for (int o = 16; o; o >>= 1) v += __shfl_xor_sync(0xffffffffu, v, o);
    return v;
}
__device__ __forceinline__ void layernorm20(float (&v)[20]) {
    float s = 0.f;
#pragma unroll
    for (int i = 0; i < 20; i++) s += v[i];
    const float mean = warp_sum(s) * (1.0f / DM);
    float q = 0.f;
#pragma unroll
    for (int i = 0; i < 20; i++) { const float d = v[i] - mean; q += d * d; }
    const float var = bf16r(warp_sum(q) * (1.0f / DM));
    const float m = bf16r(mean);
    const float rden = 1.0f / bf16r(sqrtf(bf16r(var + 1e-5f)));
#pragma unroll
    for (int i = 0; i < 20; i++) v[i] = bf16r(bf16r(v[i] - m) * rden);
}

__device__ __forceinline__ void moments(float m1, float m2, float& nmean, float& rden) {
    m1 *= 1.0f / DM;
    const float var = bf16r(fmaxf(fmaf(-m1, m1, m2 * (1.0f / DM)), 0.f));
    nmean = bf16r(m1);
    rden = rcp_approx(bf16r(sqrt_approx(bf16r(var + 1e-5f))));
}
__device__ __forceinline__ float sel4(int j, float a, float b, float c, float d) {
    float lo, hi, r;
    asm("{\n.reg .pred p;\nsetp.ne.s32 p, %3, 0;\nselp.f32 %0, %2, %1, p;\n}" : "=f"(lo) : "f"(a), "f"(b), "r"(j & 1));
    asm("{\n.reg .pred p;\nsetp.ne.s32 p, %3, 0;\nselp.f32 %0, %2, %1, p;\n}" : "=f"(hi) : "f"(c), "f"(d), "r"(j & 1));
    asm("{\n.reg .pred p;\nsetp.ne.s32 p, %3, 0;\nselp.f32 %0, %2, %1, p;\n}" : "=f"(r) : "f"(lo), "f"(hi), "r"(j & 2));
    return r;
}
template <typename T> __device__ __forceinline__ void pin(T*& p) { asm volatile("" : "+l"(p)); }
__device__ __forceinline__ void pin(uint32_t& v) { asm volatile("" : "+r"(v)); }
__device__ __forceinline__ void pin(float& v) { asm volatile("" : "+f"(v)); }
__device__ __forceinline__ uint32_t after(uint32_t n, float v) {
    asm volatile("{\n.reg .pred p;\nsetp.eq.u32 p, %1, 0x7fc1a5a5;\n@p add.u32 %0, %0, 32;\n}" : "+r"(n) : "r"(__float_as_uint(v)));
    return n;
}
__device__ __forceinline__ float2 lds64f(uint32_t addr) {
    float2 v;
    asm volatile("ld.shared.v2.f32 {%0,%1}, [%2];" : "=f"(v.x), "=f"(v.y) : "r"(addr) : "memory");
    return v;
}
__device__ __forceinline__ void sts32f(uint32_t addr, float v) { asm volatile("st.shared.f32 [%0], %1;" :: "r"(addr), "f"(v) : "memory"); }
template <int ID> __device__ __forceinline__ void fin_arrive() { asm volatile("bar.arrive %0, 288;" :: "n"(ID) : "memory"); }
template <int ID> __device__ __forceinline__ void fin_sync() { asm volatile("bar.sync %0, 288;" :: "n"(ID) : "memory"); }
template <int ID> __device__ __forceinline__ void fin_sync(uint32_t n) { asm volatile("bar.sync %0, %1;" :: "n"(ID), "r"(n) : "memory"); }
__device__ __forceinline__ float2 sum8(uint32_t addr) {
    float2 t[8];
#pragma unroll
    for (int w = 0; w < 8; w++) t[w] = lds64f(addr + w * 128);
    return make_float2(((t[0].x + t[1].x) + (t[2].x + t[3].x)) + ((t[4].x + t[5].x) + (t[6].x + t[7].x)),
                       ((t[0].y + t[1].y) + (t[2].y + t[3].y)) + ((t[4].y + t[5].y) + (t[6].y + t[7].y)));
}
__device__ __forceinline__ float4 sum4x4(uint32_t addr, int pitch) {
    float4 t[4];
#pragma unroll
    for (int w = 0; w < 4; w++)
        asm volatile("ld.shared.v4.f32 {%0,%1,%2,%3}, [%4];" : "=f"(t[w].x), "=f"(t[w].y), "=f"(t[w].z), "=f"(t[w].w) : "r"(addr + w * pitch) : "memory");
    return make_float4((t[0].x + t[1].x) + (t[2].x + t[3].x), (t[0].y + t[1].y) + (t[2].y + t[3].y),
                       (t[0].z + t[1].z) + (t[2].z + t[3].z), (t[0].w + t[1].w) + (t[2].w + t[3].w));
}
__device__ __forceinline__ void sts64f(uint32_t addr, float x, float y) {
    asm volatile("st.shared.v2.f32 [%0], {%1,%2};" :: "r"(addr), "f"(x), "f"(y) : "memory");
}
__device__ __forceinline__ void lds128_if(uint4& v, uint32_t addr, bool pred) {
    asm volatile("{\n.reg .pred p;\nsetp.ne.u32 p, %5, 0;\n@p ld.shared.v4.u32 {%0,%1,%2,%3}, [%4];\n}"
                 : "+r"(v.x), "+r"(v.y), "+r"(v.z), "+r"(v.w) : "r"(addr), "r"((uint32_t)pred) : "memory");
}
__device__ __forceinline__ void sts128f(uint32_t addr, float x, float y, float z, float w) {
    asm volatile("st.shared.v4.f32 [%0], {%1,%2,%3,%4};" :: "r"(addr), "f"(x), "f"(y), "f"(z), "f"(w) : "memory");
}
template <int NJ>
__device__ __forceinline__ void load_o(uint32_t (&ob)[3 * NJ][2], int bh, int J0, int j) {
    float4 v[NJ][4];
    float2 l;
#pragma unroll 1
    for (int it = 0; it < SPIN_MAX; it++) {
#pragma unroll
        for (int J = 0; J < NJ; J++) {
#pragma unroll
            for (int e = 0; e < 4; e++) v[J][e] = ld_relaxed_f4(&g_st.oacc[oidx(bh, j)] + oidx(0, (J0 + J) * 16 + e * 4));
        }
        l = ld_relaxed_f2(g_st.lsum[bh]);
        bool ok = l.y == UPB;
#pragma unroll
        for (int J = 0; J < NJ; J++) {
#pragma unroll
            for (int e = 0; e < 4; e++) ok &= v[J][e].w == UPB;
        }
        if (all(ok)) break;
    }
    const float rl = __fdividef(1.0f, l.x);
#pragma unroll
    for (int J = 0; J < NJ; J++) {
        ob[3 * J][0] = pack_bf16(v[J][0].x * rl, v[J][1].x * rl);     ob[3 * J][1] = pack_bf16(v[J][2].x * rl, v[J][3].x * rl);
        ob[3 * J + 1][0] = pack_bf16(v[J][0].y * rl, v[J][1].y * rl); ob[3 * J + 1][1] = pack_bf16(v[J][2].y * rl, v[J][3].y * rl);
        ob[3 * J + 2][0] = pack_bf16(v[J][0].z * rl, v[J][1].z * rl); ob[3 * J + 2][1] = pack_bf16(v[J][2].z * rl, v[J][3].z * rl);
    }
}
__device__ __forceinline__ int near_side(uint32_t sb) {
    uint32_t v;
    asm volatile("ld.volatile.shared.u32 %0, [%1];" : "=r"(v) : "r"(sb + SM_SIDE) : "memory");
    return v;
}
__device__ __forceinline__ void poll_row(uint4& a, uint4& b, uint2& c, const void* pa, const void* pb, const void* pc, uint32_t sa, uint32_t sc,
                                         bool arrive, bool nap, uint32_t bar, Warm& warm) {
    asm volatile("{\n.reg .pred p, q, r, s;\n.reg .b32 m, n, it;\n"
                 "setp.ne.u32 r, %19, 0;\nsetp.ne.u32 s, %20, 0;\nmov.u32 it, 0;\n"
                 "POLL:\n"
                 SLOT_ASM("m", "n", "p", "%23", "%24", "%25")
                 "ld.relaxed.gpu.global.v4.u32 {%0,%1,%2,%3}, [%14];\n"
                 "ld.relaxed.gpu.global.v4.u32 {%4,%5,%6,%7}, [%15];\n"
                 "ld.relaxed.gpu.global.v2.u32 {%8,%9}, [%16];\n"
                 "add.u32 it, it, 1;\nsetp.ge.u32 q, it, %21;\n"
                 "mov.u32 m, 0;\nmma.sync.aligned.m16n8k8.row.col.f32.bf16.bf16.f32 {%10,%11,%12,%13}, {m,m}, {m}, {%10,%11,%12,%13};\n"
                 "st.shared.v4.u32 [%17], {%0,%1,%2,%3};\n"
                 "st.shared.v4.u32 [%17+512], {%4,%5,%6,%7};\n"
                 "st.shared.v2.u32 [%18], {%8,%9};\n"
                 "min.u32 m, %0, %1;\nmin.u32 m, m, %2;\nmin.u32 n, %3, %4;\nmin.u32 n, n, %5;\nmin.u32 m, m, %6;\nmin.u32 m, m, %7;\n"
                 "min.u32 n, n, m;\nmin.u32 m, %8, %9;\nmin.u32 m, m, n;\n"
                 "setp.ne.or.u32 p, m, 0, q;\n"
                 "vote.sync.all.pred p, p, 0xffffffff;\n"
                 "and.pred q, p, r;\n"
                 "bar.warp.sync 0xffffffff;\n"
                 "@q mbarrier.arrive.shared::cta.b64 _, [%22];\n"
                 "@p bra.uni DONE;\n"
                 "@s nanosleep.u32 500;\n"
                 "bra.uni POLL;\n"
                 "DONE:\n}"
                 : "=&r"(a.x), "=&r"(a.y), "=&r"(a.z), "=&r"(a.w), "=&r"(b.x), "=&r"(b.y), "=&r"(b.z), "=&r"(b.w), "=&r"(c.x), "=&r"(c.y),
                   "+f"(warm.c[0]), "+f"(warm.c[1]), "+f"(warm.c[2]), "+f"(warm.c[3])
                 : "l"(pa), "l"(pb), "l"(pc), "r"(sa), "r"(sc), "r"((uint32_t)arrive), "r"((uint32_t)nap), "n"(SPIN_MAX), "r"(bar),
                   "n"(slot_phase<PH_H>()), "n"(SLOT_K), "n"(SLOT_OPEN * SLOT_K) : "memory");
}
__device__ __forceinline__ void aux_sync() { asm volatile("bar.sync 1, 256;" ::: "memory"); }

__global__ void __launch_bounds__(NTHREADS, 1)
fused_decode_kernel(const __grid_constant__ Params p) {
    extern __shared__ __align__(1024) unsigned char smem[];
    const uint32_t sb = s2u(smem);
    const int tid = threadIdx.x, cta = blockIdx.x;
    if (tid < 32 && cta < NQ_CTAS) {
        asm volatile("{\n.reg .pred p;\nelect.sync _|p, 0xffffffff;\n"
                     "@p mbarrier.init.shared::cta.b64 [%2], 1;\n"
                     "@p fence.mbarrier_init.release.cluster;\n"
                     "@p mbarrier.arrive.expect_tx.shared::cta.b64 _, [%2], 61440;\n"
                     "@p cp.async.bulk.tensor.2d.shared::cluster.global.mbarrier::complete_tx::bytes [%0], [%1, {%3, %4}], [%2];\n"
                     "@p cp.async.bulk.tensor.2d.shared::cluster.global.mbarrier::complete_tx::bytes [%0+15360], [%1, {%3, %5}], [%2];\n"
                     "@p cp.async.bulk.tensor.2d.shared::cluster.global.mbarrier::complete_tx::bytes [%0+30720], [%1, {%3, %6}], [%2];\n"
                     "@p cp.async.bulk.tensor.2d.shared::cluster.global.mbarrier::complete_tx::bytes [%0+46080], [%1, {%3, %7}], [%2];\n}"
                     :: "r"(sb + SM_W), "l"(&p.wq), "r"(sb + BAR_WQ), "r"(cta * 48), "r"(0), "r"(160), "r"(320), "r"(480) : "memory");
    }
    const int warp = __shfl_sync(0xffffffffu, tid >> 5, 0), lane = tid & 31;
    constexpr int grid = NCTAS;
    const int g = lane >> 2, j = lane & 3;
    TS(0);
    if (tid == 160) {
        mbar_init(sb + BAR_WO, 1);
        mbar_init(sb + BAR_H, 1);
#pragma unroll
        for (int i = 0; i < 8 + 2 * NWORK; i++) mbar_init(sb + BAR_FW + i * 8, 1);
        sts32f(sb + SM_SIDE, 0.f);
        asm volatile("fence.mbarrier_init.release.cluster;" ::: "memory");
        asm volatile("fence.proxy.async.shared::cta;" ::: "memory");
    }
    __syncthreads();
    if (warp >= NAUX + NWORK) {
        const int fw = warp - (NAUX + NWORK), fi = ffn_slice(cta);
        if (fw == 0) {
            if (cta < NQ_CTAS) {
#pragma unroll
                for (int i = lane; i < STATE_V4; i += 32)
                    if (cta * STATE_V4 + i < (int)(sizeof(State) / 16)) reinterpret_cast<uint4*>(&g_st)[cta * STATE_V4 + i] = make_uint4(0u, 0u, 0u, 0u);
                __syncwarp();
                if (lane == 0) red_release(g_cnt_z);
            }
            TSW(2); wait_count(g_cnt_z, NQ_CTAS); TSW(29);
            asm volatile("bar.arrive 2, %0;" :: "n"((NWORK + 2) * 32) : "memory");
            fin_arrive<3>();
        } else {
            asm volatile("bar.sync 2, %0;" :: "n"((NWORK + 2) * 32) : "memory");
            uint32_t best[2] = {~0u, ~0u};
#pragma unroll 1
            for (int i = 0; i < NPROBE; i++) {
#pragma unroll
                for (int c = 0; c < 2; c++) {
                    uint32_t t0 = clock(), t1 = t0;
                    int v = 0;
                    draw(v, &g_st.hx.w[c][PROBE], lane == 0);
                    asm volatile("{\n.reg .pred p;\nsetp.ne.u32 p, %1, 0xffffffff;\n@p mov.u32 %0, %%clock;\n}" : "+r"(t1) : "r"(v) : "memory");
                    best[c] = min(best[c], t1 - t0);
                }
                __nanosleep(1000);
            }
            if (lane == 0) sts32f(sb + SM_SIDE, __uint_as_float(best[1] < best[0]));
        }
        int job = cta;
        auto sum_rows = [&](int row_end) {
#pragma unroll 1
            for (; job < 8 * min(row_end, RED0); job += NCTAS) {
                const int row = job >> 3, grp = (job & 7) * 8 + (lane & 7);
                wait_row(row, UPB);
                const float4* src = &g_ring[row % RING][lane >> 3][grp];
                float sx = 0.f, sy = 0.f, sz = 0.f;
#pragma unroll 1
                for (int i = 0; i < 2; i++, src += 64 * 64) {
                    float4 v[16];
#pragma unroll 1
                    for (int it = 0; it < SPIN_MAX; it++) {
                        bool ok = true;
#pragma unroll
                        for (int k = 0; k < 16; k++) v[k] = ld_relaxed_b128(src + k * 4 * 64);
#pragma unroll
                        for (int k = 0; k < 16; k++) ok &= v[k].w == (float)(row + 1);
                        if (all(ok)) break;
                    }
#pragma unroll
                    for (int k = 0; k < 16; k++) { sx += v[k].x; sy += v[k].y; sz += v[k].z; }
                }
#pragma unroll
                for (int o = 8; o < 32; o <<= 1) {
                    sx += __shfl_xor_sync(0xffffffffu, sx, o); sy += __shfl_xor_sync(0xffffffffu, sy, o); sz += __shfl_xor_sync(0xffffffffu, sz, o);
                }
                if (lane < 8) st_relaxed_b128(&g_st.oacc[oidx(row, grp)], sx, sy, sz, UPB);
            }
        };
        const int ho0 = lane / 20 * 256 + lane % 20 * 4, ho1 = (lane + 32) / 20 * 256 + (lane + 32) % 20 * 4, ho2 = 3 * 256 + 16 + 2 * lane;
        uint32_t wr[10] = {};
        float wsum = 0.f;
        if (is_g(cta) && fw == 0) {
#pragma unroll
            for (int i = 0; i < 10; i++) {
                const int w = 4 * lane + 128 * (i >> 2) + (i & 3) - (i >= 8 ? 2 * lane : 0);
                wr[i] = *reinterpret_cast<const uint32_t*>(p.wr + (w >> 4) * 32 + (w & 3) * 8 + ((w >> 1) & 6));
                wsum += lo_f(wr[i]) + hi_f(wr[i]);
            }
            wsum = warp_sum(wsum);
        }
        const int fb = lane >> 3, fg = lane & 7;
        if (fw == 0) {
#pragma unroll
            for (int i = lane; i < DM / 2; i += 32) sts32f(sb + SM_X + 4 * HPITCH + i * 4, __uint_as_float(0x3f803f80u));
        }
        Warm warm;
        float nmean = 0.f, rden = 0.f, sig = 0.f;
#pragma unroll 1
        for (int b = 0; b < NB; b++) {
            const bool ffn = b >= NB - 2;
            if (fw == 0) {
                sum_rows((b + 1) * NH);
                if (ffn) asm volatile("bar.arrive 8, 64;" ::: "memory");
            } else if (ffn) {
                asm volatile("bar.sync 8, 64;" ::: "memory");
                if (b == NB - 1 && (is_f(cta) || is_g(cta) || ALL_LOADERS)) {
                    uint32_t t0 = 0, now;
#pragma unroll 1
                    for (int it = 0; it < SPIN_MAX; it++) {
                        t0 = ld_relaxed_u32(g_st.fw_time);
                        if (all(t0 != 0)) break;
                        __nanosleep(400);
                    }
                    asm volatile("fence.proxy.async.shared::cta;" ::: "memory");
#pragma unroll 1
                    for (int it = 0; it < SPIN_MAX; it++) {
                        asm volatile("mov.u32 %0, %%globaltimer_lo;" : "=r"(now));
                        if (all((int)(now - t0) >= FW_AT_NS)) break;
                    }
                    TSW(9);
                    uint32_t t = clock() + (is_f(cta) ? (fi & 1) * (FW_GAP / 2) : FW_MID + (fi & 3) * (FW_GAP2 / 4));
#pragma unroll 1
                    for (int i = 0; i < 8; i++) {
                        const uint32_t bar = sb + BAR_FW + i * 8;
                        if (is_f(cta)) {
                            wait_clock(t, warm);
                            request_box(sb + SM_W + i * 10240, (i & 1) ? &p.wu : &p.wg, fi * 32, (i >> 1) * 160, bar, 10240);
                            t += FW_GAP;
                        } else if (is_g(cta)) {
                            wait_clock(t, warm);
                            asm volatile("{\n.reg .pred p;\nelect.sync _|p, 0xffffffff;\n"
                                         "@p mbarrier.arrive.expect_tx.shared::cta.b64 _, [%2], 6144;\n"
                                         "@p cp.async.bulk.tensor.4d.shared::cluster.global.mbarrier::complete_tx::bytes [%0], [%1, {%3, %4, %4, %5}], [%2];\n}"
                                         :: "r"(sb + SM_W + i * 6144), "l"(&p.wd), "r"(bar), "r"(fi * 16), "r"(0), "r"(i * 12) : "memory");
                            t += FW_GAP2;
                        }
                    }
                }
                if (is_f(cta)) {
                    const uint32_t* src = &g_st.hx.w[near_side(sb)][min(fb, b) * 256 + 96];
                    float4 m;
#pragma unroll 1
                    for (int it = 0; it < SPIN_MAX; it++) {
                        wait_slot<PH_M>();
                        m = ld_relaxed_f4(src);
                        warm();
                        if (all(m.y + m.w == 2 * (NCTAS - NE_CTAS))) break;
                        if (b < NB - 1) __nanosleep(500);
                    }
                    moments(m.x, m.z, m.x, m.z);
                    sts64f(sb + SM_RED + 5120 + fb * 8, m.x, m.z);
                }
            }
            if (fw == 0 && cta >= NE_CTAS) {
                const int lc = cta - NE_CTAS, col = lc * 32 + 2 * (lane & 15);
                const uint32_t xv = *reinterpret_cast<const uint32_t*>(p.x + b * DM + col);
                uint32_t* dst = &(ffn ? g_st.hx.w : g_st.lx.w + 2)[lane >> 4][(b & 1) * 128 + lc / 5 * 256 + lc % 5 * 16 + (col & 6) * 2 + ((col >> 3) & 3)];
                uint32_t part = sb + SM_RED + (lane & 15) * 8;
                wait_row(b * NH + 28, 1);
                float4 early;
#pragma unroll 1
                for (int it = 0; it < SPIN_MAX; it++) {
                    early = ld_relaxed_f4(&g_st.attn[b][col]);
                    if (all(early.y == NE_CTAS / 4 && early.w == NE_CTAS / 4)) break;
                }
                if (early.x != 1.2345f && lane == 0) TS2(6);
                CK(1, __float_as_uint(early.x));
                const float x0 = -(lo_f(xv) + early.x), x1 = -(hi_f(xv) + early.z);
                fin_sync<4>(after(after(288, x0), x1));
                CK(2, lds32(sb + SM_RED));
                const float2 late = sum8(part);
                const uint32_t hv = nonzero(pack_bf16(x0 - late.x, x1 - late.y));
                st_relaxed(dst, hv);
                if (ffn) st_relaxed(dst + 2048, hv);
                CK(3, 0);
                float m = lane < 16 ? lo_f(hv) + hi_f(hv) : fmaf(lo_f(hv), lo_f(hv), hi_f(hv) * hi_f(hv));
#pragma unroll
                for (int o = 1; o < 16; o <<= 1) m += __shfl_xor_sync(0xffffffffu, m, o);
                if ((lane & 14) == 0) red_f2(reinterpret_cast<float*>(&g_st.hx.w[lane & 1][b * 256 + 96 + (lane >> 4) * 2]), m, 1.f);
                fin_arrive<5>();
            }
            if (fw == 0 && (is_g(cta) || is_f(cta))) {
                const uint32_t* src = &(ffn ? g_st.hx.w : g_st.lx.w + 2)[near_side(sb) ^ (ffn && is_g(cta) ? 3 : 0)][(b & 1) * 128];
                const uint32_t hrow = sb + SM_X + b * HPITCH;
                wait_sum(b == NB - 1 ? (const void*)&g_st.lx.w[near_side(sb) ^ 1][3 * 256] : g_st.lsum[b * NH + NH - 1], UPB, 100);
                wait_clock(clock() + HGATE_NS * 2, warm);
                uint4 h0, h1;
                uint2 h2;
                poll_row(h0, h1, h2, src + ho0, src + ho1, src + ho2, hrow + lane * 16, hrow + 1024 + lane * 8, ffn && lane == 0, b < NB - 1, sb + BAR_H, warm);
                CK(4, h0.x);
                if (is_g(cta)) {
                    const uint32_t hw[10] = {h0.x, h0.y, h0.z, h0.w, h1.x, h1.y, h1.z, h1.w, h2.x, h2.y};
                    float m1 = 0.f, m2 = 0.f, rr = 0.f;
#pragma unroll
                    for (int i = 0; i < 10; i++) {
                        const float v0 = lo_f(hw[i]), v1 = hi_f(hw[i]);
                        m1 += v0 + v1;
                        m2 = fmaf(v0, v0, fmaf(v1, v1, m2));
                        rr = fmaf(v0, lo_f(wr[i]), fmaf(v1, hi_f(wr[i]), rr));
                    }
                    moments(warp_sum(m1), warp_sum(m2), m1, m2);
                    const float sg = bf16r(sigmoid_approx(bf16r((m1 * wsum - warp_sum(rr)) * m2)));
                    if (fb == b) { nmean = m1; rden = m2; sig = sg; }
                    __syncwarp();
                    if (ffn) {
                        const int yj = 2 * (fb & 1) + (fb >> 1);
                        uint32_t ypart = sb + SM_RED2 + yj * 128 + ((fg + 2 * yj) & 7) * 16;
                        __nv_bfloat16* out = p.out + fb * DM + fi * 16 + fg;
                        const float2 hw2 = lds64f(sb + SM_X + fb * HPITCH + ((fi >> 1) * 16 + (fg & 6) * 2 + (fi & 1) * 2) * 4);
                        const uint32_t w0 = __float_as_uint(hw2.x), w1 = __float_as_uint(hw2.y);
                        const float nh0 = (fg & 1) ? hi_f(w0) : lo_f(w0), nh1 = (fg & 1) ? hi_f(w1) : lo_f(w1);
                        const float ln0 = bf16r(bf16r(nmean - nh0) * rden) - nh0, ln1 = bf16r(bf16r(nmean - nh1) * rden) - nh1;
                        pin(ypart); pin(out);
                        fin_sync<6>(after(after(after(288, sig), ln0), ln1));
                        CK(10, lds32(ypart));
                        const float4 ya = sum4x4(ypart, 512), yb = sum4x4(ypart + 2048, 512);
                        const float4 y = make_float4(ya.x + yb.x, ya.y + yb.y, ya.z + yb.z, ya.w + yb.w);
                        const float y0 = -(((fb & 1) ? y.y : y.x) + __shfl_xor_sync(0xffffffffu, (fb & 1) ? y.x : y.y, 8));
                        const float y1 = -(((fb & 1) ? y.w : y.z) + __shfl_xor_sync(0xffffffffu, (fb & 1) ? y.z : y.w, 8));
                        const uint32_t ov = pack_bf16(fmaf(y0, sig, ln0), fmaf(y1, sig, ln1));
                        if (b == NB - 1) {
                            asm volatile("st.global.u16 [%0], %1;" :: "l"(out), "h"((unsigned short)(ov & 0xffffu)) : "memory");
                            asm volatile("st.global.u16 [%0], %1;" :: "l"(out + 8), "h"((unsigned short)(ov >> 16)) : "memory");
                        }
                        CK(11, 0);
                        if (lane == 0) TS2(13);
                    }
                }
            }
            if (is_f(cta) && ffn) {
                const int ks = (2 * fi + fw) % 12;
                const int far = near_side(sb) ^ 1;
                uint32_t* dst = &g_st.ax[ks >> 2].w[(~b & 1) * 2 + far][(fi / 6) * 128 + (ks & 3) * 32 + fb * 8 + (fg & 1) * 4 + ((fg >> 1) ^ (ks & 1))];
                uint32_t* dst2 = dst + (far ? -1024 : 1024);
                uint32_t part = sb + SM_RED + fw * 2560 + fb * 128 + ((fg + (fb & 2)) & 7) * 16;
                uint32_t psum = sb + SM_RED + fw * 2560 + 4 * 128 + ((fg + 4) & 7) * 16;
                pin(dst); pin(part); pin(psum);
                asm volatile("bar.sync 4, 320;" ::: "memory");
                CK(6, lds32(part));
                const float4 d = sum4x4(part, 640), cs = sum4x4(psum, 640);
                const float2 mo = lds64f(sb + SM_RED + 5120 + fb * 8);
                nmean = mo.x; rden = mo.y;
                const float g0 = fmaf(nmean, cs.x, -d.x), g1 = fmaf(nmean, cs.y, -d.y), ke = rden * -1.4426950408889634f, r2 = rden * rden;
                const float p0 = g0 * fmaf(-nmean, cs.z, d.z) * r2, p1 = g1 * fmaf(-nmean, cs.w, d.w) * r2;
                const uint32_t av = nonzero(pack_bf16(p0 * rcp_approx(1.0f + ex2_approx(g0 * ke)), p1 * rcp_approx(1.0f + ex2_approx(g1 * ke))));
                st_relaxed(dst, av);
                st_relaxed(dst2, av);
                CK(7, 0);
            }
        }
        warm.done(sb + SM_MISC);
        if (cta == 0 && tid == (NAUX + NWORK) * 32) { g_work[0] = 0; g_work[32] = 0; g_cnt_z[0] = 0; }
        return;
    }
    if (warp >= NAUX) {
        const int wk = warp - NAUX;
        const uint32_t bar = sb + BAR_KV + wk * 8;
        const uint32_t buf = sb + SM_KV + wk * TILE_BYTES;
        uint64_t pol;
        asm volatile("createpolicy.fractional.L2::evict_first.b64 %0, 1.0;" : "=l"(pol));
        const int nstatic = NWORK * grid;
        constexpr int POOL0 = NUNITS - NPOOL;
        int uk = wk * grid + cta;
        spin_ns(K0_DELAY_NS);
        request_tile(buf, &p.k, uk, bar, pol);
        if (wk == 0) {
            spin_ns(WO_AT_NS - K0_DELAY_NS);
#pragma unroll 1
            for (int i = 0; i < (cta < NE_CTAS ? 5 : 4); i++)
                request_box(sb + SM_A + i * 12288, &p.wo, cta < NE_CTAS ? (cta & 3) * 160 + i * 32 : (cta - NE_CTAS) * 32,
                            (cta < NE_CTAS ? cta >> 2 : 28 + i) * DH, sb + BAR_WO, i ? 0 : cta < NE_CTAS ? 61440 : 49152);
        }
        uint32_t koff[3], voff[3];
        {
            const int r = lane & 7, hf = (lane >> 3) & 1;
            const int kkey = hf ? 8 + (r ^ 1) : r;
            const int vh = lane >> 4;
            const int vkey = ((r & 1) ? 8 : 0) + (vh ? (r ^ 1) : r);
#pragma unroll
            for (int b = 0; b < 3; b++) {
                const int rk = 3 * kkey + b, rv = 3 * vkey + b;
                koff[b] = buf + rk * 128 + (((lane >> 4) ^ (rk & 7)) << 4);
                voff[b] = buf + rv * 128 + ((hf ^ (rv & 7)) << 4);
            }
        }
        uint32_t phase = 0, kbar = bar;
        uint4 qf[6];
        auto load_q = [&](int u) {
            const uint32_t* q = &g_early[u / UPB].q[j * 4];
#pragma unroll
            for (int i = 0; i < 6; i++) qf[i] = ld_relaxed_v4(q + i * 16);
        };
        load_q(uk);
        int uq[LAG];
        uint32_t sq[LAG];
#pragma unroll
        for (int i = 0; i < LAG; i++) { uq[i] = -1; sq[i] = 0; }
        uint4 mv = make_uint4(0u, 0u, 0u, 0u);
        float freed = UPB;
        while (true) {
            const int uv = uq[0];
            uint32_t sv = sq[0];
#pragma unroll
            for (int i = 0; i + 1 < LAG; i++) { uq[i] = uq[i + 1]; sq[i] = sq[i + 1]; }
            uq[LAG - 1] = uk;
            if (uk < NUNITS) {
                PH(7);
#pragma unroll 1
                for (int it = 0; it < SPIN_MAX; it++) {
                    uint32_t lo = 0xffffffffu;
#pragma unroll
                    for (int i = 0; i < 6; i++) lo = min(min(lo, min(qf[i].x, qf[i].y)), min(qf[i].z, qf[i].w));
                    if (all(lo != 0)) break;
                    __nanosleep(250);
                    load_q(uk);
                }
                mbar_wait(kbar, phase); phase ^= 1;
                PH(0); ARR();
                TSI(0, 16); TSI(1, 18);
                float acc[2][4][4] = {};
#pragma unroll
                for (int ks = 0; ks < 12; ks++) {
                    const uint4 qq = qf[ks >> 1];
                    const uint32_t b0 = (ks & 1) ? qq.z : qq.x, b1 = (ks & 1) ? qq.w : qq.y;
#pragma unroll
                    for (int mt = 0; mt < 4; mt++) {
                        uint32_t a[4];
                        ldsm4(a, (koff[ks >> 2] ^ ((ks & 3) << 5)) + mt * 6144);
                        mma16816(acc[ks & 1][mt], a, b0, b1);
                    }
                }
                PH(1);
                TSI(0, 17); TSI(1, 19);
                if (uv < NUNITS && kbar == bar) request_tile(buf, uv >= 0 ? &p.v : &p.k, uv >= 0 ? uv : uk + (wk < NSPARE ? 2 : 1) * nstatic, bar, pol);
                const float sa = sel4(j, acc[0][0][0], acc[0][1][0], acc[0][2][0], acc[0][3][0]) + sel4(j, acc[1][0][0], acc[1][1][0], acc[1][2][0], acc[1][3][0]);
                const float sc = sel4(j, acc[0][0][2], acc[0][1][2], acc[0][2][2], acc[0][3][2]) + sel4(j, acc[1][0][2], acc[1][1][2], acc[1][2][2], acc[1][3][2]);
                const uint32_t raw = pack_bf16(sa, sc);
                const float scale = -0.07216878364870322f;
                const uint32_t sk = pack_bf16(lo_f(raw) * scale, hi_f(raw) * scale);
                sq[LAG - 1] = sk;
                if (uk >= POOL0) st_relaxed(&g_st.score[uk - POOL0][lane], sk ? sk : 0x80008000u);
                int a = (int)(sk << 16), b = (int)(sk & 0xffff0000u);
                a ^= (a >> 31) & 0x7fff0000; b ^= (b >> 31) & 0x7fff0000;
                const int mx = __reduce_max_sync(0xffffffffu, max(a, b));
                if (lane == 0) st_relaxed(&g_early[uk / UPB].umax[uk % UPB], (uint32_t)mx | 1u);
            }
            if (uv < 0) {
                if (wk < NSPARE) {
                    const int d = uk < nstatic ? SM_W - SM_KV : SM_KV - SM_W;
#pragma unroll
                    for (int b = 0; b < 3; b++) koff[b] += d;
                    kbar = uk < nstatic ? bar + NWORK * 8 : bar;
                    phase = uk >= nstatic;
                }
                uk += nstatic;
                load_q(uk);
                continue;
            }
            if (uv >= NUNITS) break;
            const int bh = uv / UPB;
#pragma unroll 1
            for (int it = 0; it < SPIN_MAX; it++) {
                if (all((mv.x & mv.y & mv.z & mv.w & 1u) && (uv < POOL0 || sv != 0) && freed == UPB)) break;
                mv = ld_relaxed_v4(&g_early[bh].umax[lane * 4]);
                if (bh >= RING && bh < RED0) freed = __uint_as_float(ld_relaxed_u32(&g_st.oacc[oidx(bh - RING, (lane & 7) * 8)].w));
                if (uv >= POOL0) sv = ld_relaxed_u32(&g_st.score[uv - POOL0][lane]);
            }
            PH(2);
            int un = NUNITS, vn = 0;
            draw(un, g_work, uk < NUNITS && lane == 0);
            uint32_t tdraw;
            asm volatile("mov.u32 %0, %%globaltimer_lo;" : "=r"(tdraw));
            draw(vn, g_work + 32, uq[0] >= POOL0 && lane == 0);
            int mx = __reduce_max_sync(0xffffffffu, max(max((int)mv.x, (int)mv.y), max((int)mv.z, (int)mv.w))) & 0xffff0000;
            mx ^= (mx >> 31) & 0x7fff0000;
            const float m = __int_as_float(mx);
            const float l2e = 1.4426950408889634f;
            const uint32_t pp = pack_bf16(exp2f((lo_f(sv) - m) * l2e), exp2f((hi_f(sv) - m) * l2e));
            uint32_t pb[8];
#pragma unroll
            for (int t = 0; t < 4; t++) {
                pb[2 * t] = __shfl_sync(0xffffffffu, pp, 8 * j + t);
                pb[2 * t + 1] = __shfl_sync(0xffffffffu, pp, 8 * j + 4 + t);
            }
            float lacc[4] = {};
            const uint32_t ones[4] = {0x3f803f80u, 0x3f803f80u, 0x3f803f80u, 0x3f803f80u};
#pragma unroll
            for (int t = 0; t < 4; t++) mma16816(lacc, ones, pb[2 * t], pb[2 * t + 1]);
            if (uv < nstatic) {
                asm volatile("bar.sync 2, %0;" :: "n"((NWORK + 2) * 32) : "memory");
                TSW(3);
            }
            const int grp = 16 * j + 4 * (g & 1) + (g >> 1);
            uint32_t mode = (bh >= RED0) + (bh >= NBH - 4);
            float tag = mode ? 1.f : (float)(bh + 1), tag2 = tag;
            void* dst = mode == 0 ? (void*)&g_ring[bh % RING][uv % UPB][grp] :
                        mode == 1 ? (void*)&g_st.oacc[oidx(bh, grp)] : (void*)&g_st.ox[uv % OREP].w[0][oidx(bh & 3, grp) * 4];
            if (mode == 2 && lane < 2) red_f2(reinterpret_cast<float*>(&g_st.lx.w[lane][(bh & 3) * 256]), lacc[0], 1.f);
            un = __shfl_sync(0xffffffffu, un, 0) + (LAG + 1) * nstatic;
            vn = __shfl_sync(0xffffffffu, vn, 0);
            if (uq[0] >= POOL0) uq[0] = POOL0 + vn;
            if (vn == FW_TICKET && lane == 0) st_relaxed(g_st.fw_time, tdraw | 1u);
            if (uq[0] < NUNITS && un >= NUNITS) {
                mv = ld_relaxed_v4(&g_early[uq[0] / UPB].umax[lane * 4]);
                if (uq[0] < RED0 * UPB) freed = 0.f;
                if (uq[0] >= POOL0) sq[0] = ld_relaxed_u32(&g_st.score[uq[0] - POOL0][lane]);
            }
            pin(dst); pin(mode); pin(tag); pin(tag2); pin(voff[0]); pin(voff[1]); pin(voff[2]);
            PH(3);
            mbar_wait(bar, phase); phase ^= 1;
            PH(4); ARR(); CK(12, lds32(buf));
            float acc[12][4] = {};
#pragma unroll
            for (int t = 0; t < 4; t++) {
#pragma unroll
                for (int mt = 0; mt < 12; mt++) {
                    uint32_t a[4];
                    ldsm4t(a, (voff[mt >> 2] ^ ((mt & 3) << 5)) + t * 6144);
                    mma16816(acc[mt], a, pb[2 * t], pb[2 * t + 1]);
                }
            }
            PH(5);
            if (lane == 0) PROG(un);
            if (un < NUNITS || uq[0] < NUNITS) request_tile(buf, un < NUNITS ? &p.k : &p.v, un < NUNITS ? un : uq[0], bar, pol);
            if (un < NUNITS || uq[0] < NUNITS) CK(11, 0);
            float o[6];
#pragma unroll
            for (int e = 0; e < 6; e++) {
                const int q = e % 3, c = (e / 3) * 2;
                o[e] = sel4(j, acc[q][c], acc[3 + q][c], acc[6 + q][c], acc[9 + q][c]);
            }
            put_groups(dst, mode, o, tag, tag2);
            CK(13, 0);
            if (un < NUNITS) load_q(un);
            if (lane == 0) red_f2(&g_st.lsum[bh][0].x, lacc[0], 1.f);
            PH(6);
            if (uq[0] >= NUNITS && un >= NUNITS) break;
            uk = un;
            if (uq[0] < NUNITS && un < NUNITS) {
                const int nb = uq[0] / UPB;
                mv = ld_relaxed_v4(&g_early[nb].umax[lane * 4]);
                freed = nb >= RING && nb < RED0 ? __uint_as_float(ld_relaxed_u32(&g_st.oacc[oidx(nb - RING, (lane & 7) * 8)].w)) : UPB;
                if (uq[0] >= POOL0) sq[0] = ld_relaxed_u32(&g_st.score[uq[0] - POOL0][lane]);
            }
        }
        TSW(4 + wk);
        return;
    }

    __nv_bfloat16* xs = reinterpret_cast<__nv_bfloat16*>(smem + SM_X);
    float* red = reinterpret_cast<float*>(smem + SM_RED);
    const int frow = (lane & 7) + ((lane >> 4) << 3), fcol = (lane >> 3) & 1;
    const uint32_t f64b = sb + (frow * 4 + (fcol ^ ((frow >> 1) & 3))) * 16;
    if (cta < NQ_CTAS) {
        uint2 xr[5];
        if (warp < NB) {
#pragma unroll
            for (int i = 0; i < 5; i++) xr[i] = *reinterpret_cast<const uint2*>(p.x + warp * DM + i * 128 + lane * 4);
        }
        TS(26);
        if (warp < NB) {
            float v[20];
#pragma unroll
            for (int i = 0; i < 5; i++) {
                v[4 * i] = lo_f(xr[i].x); v[4 * i + 1] = hi_f(xr[i].x); v[4 * i + 2] = lo_f(xr[i].y); v[4 * i + 3] = hi_f(xr[i].y);
            }
            layernorm20(v);
#pragma unroll
            for (int i = 0; i < 5; i++)
                *reinterpret_cast<uint2*>(xs + warp * XPITCH + i * 128 + lane * 4) =
                    make_uint2(pack_bf16(v[4 * i], v[4 * i + 1]), pack_bf16(v[4 * i + 2], v[4 * i + 3]));
        }
        TS(27);
        aux_sync();
        mbar_wait(sb + BAR_WQ, 0);
        TS(1);
        const uint32_t xfrag = sb + SM_X + ((g & 3) * XPITCH + 2 * j) * 2;
        float acc[3][4] = {};
#pragma unroll
        for (int s = 0; s < 5; s++) {
            const int ks = warp * 5 + s;
            const uint32_t b0 = lds32(xfrag + ks * 32), b1 = lds32(xfrag + ks * 32 + 16);
            const int row = ks * 16 + frow;
#pragma unroll
            for (int mt = 0; mt < 3; mt++) {
                uint32_t a[4];
                ldsm4t(a, sb + SM_W + (row * 6 + 2 * mt + fcol) * 16);
                mma16816(acc[mt], a, b0, b1);
            }
        }
        if (j < 2) {
#pragma unroll
            for (int mt = 0; mt < 3; mt++) {
                *reinterpret_cast<float2*>(red + (warp * 48 + mt * 16 + g) * 4 + 2 * j) = make_float2(acc[mt][0], acc[mt][1]);
                *reinterpret_cast<float2*>(red + (warp * 48 + mt * 16 + 8 + g) * 4 + 2 * j) = make_float2(acc[mt][2], acc[mt][3]);
            }
        }
        aux_sync();
        if (tid < 96) {
            const int b = tid & 3, cp = tid >> 2;
            float s0 = 0.f, s1 = 0.f;
#pragma unroll
            for (int w = 0; w < 8; w++) { s0 += red[(w * 48 + 2 * cp) * 4 + b]; s1 += red[(w * 48 + 2 * cp + 1) * 4 + b]; }
            const int h = cta >> 2, d = (cta & 3) * 48 + 2 * cp;
            const int ch = d >> 3, jj = (d & 7) >> 1;
            st_relaxed(&g_early[b * NH + h].q[(ch >> 2) * 16 + jj * 4 + (ch & 3)], pack_neg(s0, s1));
        }
        TS(28);
    }
    if (warp >= 4 && warp < 4 + NSPARE) {
        uint64_t pol;
        asm volatile("createpolicy.fractional.L2::evict_first.b64 %0, 1.0;" : "=l"(pol));
        if (cta >= NQ_CTAS) spin_ns(WO_AT_NS);
        asm volatile("fence.proxy.async.shared::cta;" ::: "memory");
        request_tile(sb + SM_W + (warp - 4) * TILE_BYTES, &p.k, (NWORK + warp - 4) * grid + cta, sb + BAR_KV + (NWORK + warp - 4) * 8, pol);
    }
    fin_sync<3>();
    mbar_wait(sb + BAR_WO, 0);
    TS(7);
    uint32_t part = sb + SM_RED + (warp * 32 + 8 * j + g) * 4;

#pragma unroll 1
    for (int b = 0; b < NB; b++) {
        if (cta >= NE_CTAS) {
            uint32_t a[6][2][4];
#pragma unroll
            for (int s = 0; s < 6; s++) {
#pragma unroll
                for (int mt = 0; mt < 2; mt++) ldsm4t(a[s][mt], (f64b ^ (mt * 32)) + SM_A + (warp * 6 + s) * 1024);
            }
            const int bh = b * NH + 28 + (warp >> 1);
            const int side = near_side(sb) ^ 1;
            const void* osrc[OREP];
#pragma unroll
            for (int c = 0; c < OREP; c++)
                osrc[c] = b == NB - 1 ? (const void*)&g_st.ox[c].w[side][oidx(bh & 3, (warp & 1) * 32 + lane) * 4] : &g_st.oacc[oidx(bh, (warp & 1) * 32 + lane)];
            const void* lsrc = b == NB - 1 ? (const void*)&g_st.lx.w[side][(bh & 3) * 256] : g_st.lsum[bh];
            wait_row_o(bh, 1);
            const float rl = rcp_approx(wait_sum(lsrc, UPB)) * (b == NB - 1 ? 1.f : 1.f / OREP), full = b == NB - 1 ? UPB : UPB * OREP;
            float4 ov;
            float px, py, pz;
            Warm warm;
#pragma unroll 1
            for (int it = 0; it < SPIN_MAX; it++) {
                wait_slot<PH_O>();
                float4 oc[OREP];
#pragma unroll
                for (int c = 0; c < OREP; c++) oc[c] = ld_relaxed_f4(osrc[c]);
                warm();
                ov = oc[0];
#pragma unroll
                for (int c = 1; c < OREP; c++) { ov.x += oc[c].x; ov.y += oc[c].y; ov.z += oc[c].z; ov.w += oc[c].w; }
                ov.x *= rl; ov.y *= rl; ov.z *= rl;
                px = __shfl_xor_sync(0xffffffffu, ov.x, 4); py = __shfl_xor_sync(0xffffffffu, ov.y, 4); pz = __shfl_xor_sync(0xffffffffu, ov.z, 4);
                if (all(ov.w == full)) break;
            }
            CK(0, __float_as_uint(ov.x));
            if (ov.x != 1.2345f && warp == 7) TSW(14);
            const uint32_t w[3] = {pack_bf16(ov.x, px), pack_bf16(ov.y, py), pack_bf16(ov.z, pz)};
            float acc[2][2][4] = {};
#pragma unroll
            for (int s = 0; s < 6; s++) {
                const uint32_t b0 = __shfl_sync(0xffffffffu, w[s % 3], (s / 3) * 16 + j);
                const uint32_t b1 = __shfl_sync(0xffffffffu, w[s % 3], (s / 3) * 16 + 8 + j);
#pragma unroll
                for (int mt = 0; mt < 2; mt++) mma16816(acc[mt][s & 1], a[s][mt], b0, b1);
            }
            sts32f(part, sel4(j, acc[0][0][0] + acc[0][1][0], acc[0][0][2] + acc[0][1][2], acc[1][0][0] + acc[1][1][0], acc[1][0][2] + acc[1][1][2]));
            CK(1, 0);
            fin_arrive<4>();
            warm.done(sb + SM_MISC);
            fin_sync<5>();
            if (cta < NE_CTAS + 4 && tid < 56) reinterpret_cast<uint4*>(&g_early[b * NH + 28 + cta - NE_CTAS])[tid] = make_uint4(0u, 0u, 0u, 0u);
        } else {
            const int bh = b * NH + (cta >> 2);
            if (warp == 0) wait_row_o(bh, UPB);
            aux_sync();
            if (warp < 5) {
                uint32_t ob[12][2];
                load_o<4>(ob, bh, 0, j);
                float acc[2][2][4] = {};
#pragma unroll
                for (int ks = 0; ks < 12; ks++) {
#pragma unroll
                    for (int mt = 0; mt < 2; mt++) {
                        uint32_t a[4];
                        ldsm4t(a, (f64b ^ (mt * 32)) + SM_A + warp * 12288 + ks * 1024);
                        mma16816(acc[mt][ks & 1], a, ob[ks][0], ob[ks][1]);
                    }
                }
                red_f2(&g_st.attn[b][(cta & 3) * 160 + warp * 32 + 8 * j + g].x,
                       sel4(j, acc[0][0][0] + acc[0][1][0], acc[0][0][2] + acc[0][1][2], acc[1][0][0] + acc[1][1][0], acc[1][0][2] + acc[1][1][2]), 1.f);
                TS(8);
            } else if (warp > 5 && (cta & 3) == 0 && tid - 192 < 56) {
                reinterpret_cast<uint4*>(&g_early[bh])[tid - 192] = make_uint4(0u, 0u, 0u, 0u);
            }
        }
        if (b < NB - 2) continue;

        if (is_f(cta)) {
            uint32_t ga[10][2][4];
            uint4 hv[5] = {};
            const uint32_t hfrag = sb + SM_X + min(g, 4) * HPITCH + ((warp >> 1) * 80 + 4 * j) * 4;
#pragma unroll
            for (int s = 0; s < 5; s++) lds128_if(hv[s], hfrag + s * 64, b == NB - 1);
            if (b == NB - 1) mbar_wait(sb + BAR_FW + warp * 8, 0);
            if (warp == 7) TSW(10);
            CK(12, lds32(sb + SM_W));
#pragma unroll
            for (int s = 0; s < 10; s++) {
#pragma unroll
                for (int mt = 0; mt < 2; mt++) ldsm4t(ga[s][mt], (f64b ^ (mt * 32)) + SM_W + (warp * 10 + s) * 1024);
            }
            const uint32_t gpart = sb + SM_RED + (warp >> 1) * 640 + j * 256 + ((g + 2 * j) & 7) * 16 + (warp & 1) * 8;
            mbar_wait(sb + BAR_H, b & 1);
#pragma unroll
            for (int s = 0; s < 5; s++) lds128_if(hv[s], hfrag + s * 64, g == b);
            CK(4, hv[0].x);
            float acc[2][2][4] = {};
#pragma unroll
            for (int s = 0; s < 10; s++) {
#pragma unroll
                for (int mt = 0; mt < 2; mt++)
                    mma16816(acc[mt][s & 1], ga[s][mt], (s & 1) ? hv[s >> 1].z : hv[s >> 1].x, (s & 1) ? hv[s >> 1].w : hv[s >> 1].y);
            }
#pragma unroll
            for (int mt = 0; mt < 2; mt++) {
                if (j < 3) sts64f(gpart + mt * 2560, acc[mt][0][0] + acc[mt][1][0], acc[mt][0][2] + acc[mt][1][2]);
                if (j < 2) sts64f(gpart + mt * 2560 + 128, acc[mt][0][1] + acc[mt][1][1], acc[mt][0][3] + acc[mt][1][3]);
            }
            CK(5, 0);
            asm volatile("bar.arrive 4, 320;" ::: "memory");
        } else if (is_g(cta)) {
            const uint32_t* asrc = &g_st.ax[0].w[(~b & 1) * 2 + near_side(sb)][warp * 128 + ((g >> 2) * 2 + (j >> 1)) * 32 + (g & 3) * 8 + (j & 1) * 4];
            const uint32_t ypart = sb + SM_RED2 + warp * 512 + j * 128 + ((g + 2 * j) & 7) * 16;
            uint32_t wb[12][4];
            if (b == NB - 1) mbar_wait(sb + BAR_FW + warp * 8, 0);
            if (warp == 7) TSW(11);
            CK(13, lds32(sb + SM_W));
            {
                const int jj = (lane & 7) >> 1, q = jj >> 1, hi = lane >> 4;
                const uint32_t base = sb + SM_W + warp * 6144 + q * 512 + ((hi ^ q) * 4 + (jj & 1) * 2 + (lane & 1)) * 32 + ((fcol ^ hi ^ q) << 4);
#pragma unroll
                for (int s = 0; s < 12; s++) ldsm4t(wb[s], base + (s >> 2) * 2048 + (s & 1) * 1024 + (s & 2) * 128);
            }
            mbar_wait(sb + BAR_H, b & 1);
            uint4 va[3];
            Warm warm;
#pragma unroll 1
            for (int it = 0; it < SPIN_MAX; it++) {
                uint32_t lo = 0xffffffffu;
#pragma unroll
                for (int i = 0; i < 3; i++) va[i] = ld_relaxed_v4(asrc + i * 4096);
                warm();
#pragma unroll
                for (int i = 0; i < 3; i++) lo = min(min(lo, min(va[i].x, va[i].y)), min(va[i].z, va[i].w));
                if (all(lo != 0)) break;
            }
            CK(8, va[0].x);
            if (va[0].x != 0x12345 && warp == 7) TSW(15);
            float acc[6][4] = {};
#pragma unroll
            for (int s = 0; s < 12; s++) {
                const uint4 v = va[s >> 2];
                mma16816(acc[s % 6], wb[s], (s & 2) ? v.z : v.x, (s & 2) ? v.w : v.y);
            }
            float y[4];
#pragma unroll
            for (int e = 0; e < 4; e++) y[e] = j < 2 ? (acc[0][e] + acc[2][e]) + acc[4][e] : (acc[1][e] + acc[3][e]) + acc[5][e];
            sts128f(ypart, y[0], y[1], y[2], y[3]);
            CK(9, 0);
            fin_arrive<6>();
            warm.done(sb + SM_MISC);
        }
    }
}

typedef CUresult (*EncodeFn)(CUtensorMap*, CUtensorMapDataType, cuuint32_t, void*, const cuuint64_t*, const cuuint64_t*,
                             const cuuint32_t*, const cuuint32_t*, CUtensorMapInterleave, CUtensorMapSwizzle,
                             CUtensorMapL2promotion, CUtensorMapFloatOOBfill);

CUtensorMap make_map(EncodeFn enc, void* ptr, uint64_t cols, uint64_t rows, uint32_t bcols, uint32_t brows,
                     CUtensorMapSwizzle sw, CUtensorMapL2promotion promo) {
    CUtensorMap m;
    const cuuint64_t dims[2] = {cols, rows};
    const cuuint64_t strides[1] = {cols * 2};
    const cuuint32_t box[2] = {bcols, brows};
    const cuuint32_t es[2] = {1, 1};
    enc(&m, CU_TENSOR_MAP_DATA_TYPE_BFLOAT16, 2, ptr, dims, strides, box, es, CU_TENSOR_MAP_INTERLEAVE_NONE, sw, promo,
        CU_TENSOR_MAP_FLOAT_OOB_FILL_NONE);
    return m;
}

}

extern "C" void kernel_launch(void* const* d_in, const int* in_sizes, int n_in, void* d_out, int out_size) {
    (void)in_sizes; (void)n_in; (void)out_size;
    static EncodeFn enc = nullptr;
    static int sms = 0;
    if (!enc) {
        cudaDriverEntryPointQueryResult qr;
        cudaGetDriverEntryPoint("cuTensorMapEncodeTiled", (void**)&enc, cudaEnableDefault, &qr);
        int dev = 0;
        cudaGetDevice(&dev);
        cudaDeviceGetAttribute(&sms, cudaDevAttrMultiProcessorCount, dev);
        cudaFuncSetAttribute(fused_decode_kernel, cudaFuncAttributeMaxDynamicSharedMemorySize, SM_TOTAL);
    }
    if (sms < NCTAS) return;
    const CUtensorMapL2promotion WPROMO = CU_TENSOR_MAP_L2_PROMOTION_L2_128B;
    Params p;
    p.k = make_map(enc, d_in[1], 64, (uint64_t)NBH * SK * 3, 64, TILE_ROWS, CU_TENSOR_MAP_SWIZZLE_128B, CU_TENSOR_MAP_L2_PROMOTION_NONE);
    p.v = make_map(enc, d_in[2], 64, (uint64_t)NBH * SK * 3, 64, TILE_ROWS, CU_TENSOR_MAP_SWIZZLE_128B, CU_TENSOR_MAP_L2_PROMOTION_NONE);
    p.wq = make_map(enc, d_in[3], NH * DH, DM, 48, 160, CU_TENSOR_MAP_SWIZZLE_NONE, WPROMO);
    p.wo = make_map(enc, d_in[4], DM, NH * DH, 32, DH, CU_TENSOR_MAP_SWIZZLE_64B, WPROMO);
    p.wg = make_map(enc, d_in[7], FF, DM, 32, 160, CU_TENSOR_MAP_SWIZZLE_64B, WPROMO);
    p.wu = make_map(enc, d_in[8], FF, DM, 32, 160, CU_TENSOR_MAP_SWIZZLE_64B, WPROMO);
    {
        const cuuint64_t dims[4] = {DM, 2, 8, FF / 16}, strides[3] = {8 * DM * 2, DM * 2, 16 * DM * 2};
        const cuuint32_t box[4] = {16, 2, 8, 12}, es[4] = {1, 1, 1, 1};
        enc(&p.wd, CU_TENSOR_MAP_DATA_TYPE_BFLOAT16, 4, d_in[9], dims, strides, box, es, CU_TENSOR_MAP_INTERLEAVE_NONE,
            CU_TENSOR_MAP_SWIZZLE_32B, WPROMO, CU_TENSOR_MAP_FLOAT_OOB_FILL_NONE);
    }
    p.x = (const __nv_bfloat16*)d_in[0];
    p.wr = (const __nv_bfloat16*)d_in[6];
    p.out = (__nv_bfloat16*)d_out;
    fused_decode_kernel<<<NCTAS, NTHREADS, SM_TOTAL, cudaStreamPerThread>>>(p);
}
```

```cpp
#include <cuda_runtime.h>
#include <cuda_bf16.h>
#include <cuda.h>
#include <stdint.h>

namespace {

constexpr int NB = 4, NH = 32, SK = 8192, DH = 192, DM = 640, FF = 1536;
constexpr int NBH = NB * NH;
constexpr int TILE = 64;
constexpr int UPB = SK / TILE;
constexpr int NUNITS = NBH * UPB;
constexpr int TILE_BYTES = TILE * DH * 2;
constexpr int TILE_ROWS = TILE * 3;
constexpr int NCTAS = 132;
constexpr int NQ_CTAS = 128;
constexpr int NE_CTAS = 112;
__host__ __device__ constexpr bool is_f(int cta) { return cta < NE_CTAS && cta % 14 < 11 && !(cta & 1); }
__host__ __device__ constexpr bool is_g(int cta) { return cta < NE_CTAS && cta % 14 < 11 && (cta & 1); }
__host__ __device__ constexpr int ffn_slice(int cta) { return cta / 14 * ((cta & 1) ? 5 : 6) + cta % 14 / 2; }

#define NWORK 2
#define NSPARE 1
#define LAG 2
#define NPOOL 768
#define RED0 116
#define RING 12
#define OREP 3
#define K0_DELAY_NS 1200
#define WO_AT_NS 3800
#define FW_TICKET 648
#define FW_AT_NS 3250
#define FW_GAP 280
#define FW_MID 2000
#define FW_GAP2 200
#define HGATE_NS 700
#define SLOT_TICKS 8
#define SLOT_OPEN 3
#define PH_O 0
#define PH_H 1
#define PH_M 3
#define NPROBE 24
constexpr int NAUX = 8;
constexpr int NTHREADS = (NAUX + NWORK + 2) * 32;
constexpr int SPIN_MAX = 1 << 22;

constexpr int SM_KV = 0;
constexpr int SM_A = SM_KV + NWORK * TILE_BYTES;
constexpr int SM_W = SM_A + 61440;
constexpr int SM_X = SM_W + 81920;
constexpr int XPITCH = 648;
constexpr int HPITCH = 1344;
constexpr int SM_RED = SM_X + 5 * HPITCH + 64;
constexpr int SM_RED2 = SM_RED + 8 * 48 * 4 * 4;
constexpr int SM_MISC = SM_RED2 + 4096;
constexpr int BAR_WQ = SM_MISC + 32, BAR_WO = SM_MISC + 40, SM_SIDE = SM_MISC + 48, BAR_H = SM_MISC + 56, BAR_FW = SM_MISC + 64;
constexpr int BAR_KV = BAR_FW + 64;
constexpr int SM_TOTAL = BAR_KV + 2 * NWORK * 8;
static_assert(LAG == 2 && SM_W % 1024 == 0 && NB * XPITCH * 2 <= 4 * HPITCH && SM_RED % 128 == 0, "smem layout");

struct Params {
    CUtensorMap k, v;
    CUtensorMap wq;
    CUtensorMap wo;
    CUtensorMap wg, wu;
    CUtensorMap wd;
    const __nv_bfloat16 *x, *wr;
    __nv_bfloat16* out;
};

struct Early {
    uint32_t q[96];
    uint32_t umax[UPB];
};
struct Twin { uint32_t w[4][1024]; };
constexpr int PROBE = 1024 - 32;
#define LSTRIDE 16
struct State {
    Twin ax[3];
    Twin hx;
    Twin ox[OREP];
    Twin lx;
    float4 oacc[NBH * 64];
    float2 attn[NB][DM];
    uint32_t fw_time[32];
    float2 lsum[NBH][LSTRIDE];
    uint32_t score[NPOOL][32];
};
__host__ __device__ constexpr int oidx(int row, int grp) {
    return (row >> 2) * 256 + ((row & 1) * 2 + (grp >> 5)) * 64 + (row & 2) * 16 + (grp & 31);
}
constexpr int STATE_V4 = ((sizeof(State) / 32 + NQ_CTAS - 1) / NQ_CTAS) * 2;
static_assert(sizeof(State) % 32 == 0, "State is cleared in whole sectors");
static_assert(sizeof(Early) == 56 * 16, "an Early entry is cleared by 56 threads");
struct Scratch {
    State st;
    unsigned work[64];
    unsigned cnt_z[32];
    Early early[NBH];
    alignas(4096) float4 ring[RING][UPB][64];
};
constexpr size_t PAGE = 2u << 20;
static_assert(sizeof(Scratch) <= PAGE, "scratch must fit one page");
__device__ __align__(128) unsigned char g_raw[2 * PAGE];
__device__ __forceinline__ Scratch* scratch() {
    return reinterpret_cast<Scratch*>((reinterpret_cast<uintptr_t>(g_raw) + PAGE - 1) & ~(uintptr_t)(PAGE - 1));
}
#define g_early scratch()->early
#define g_st scratch()->st
#define g_ring scratch()->ring
#define g_cnt_z scratch()->cnt_z
#define g_work scratch()->work
#define ALL_LOADERS 0
#define TS(i)
#define TSW(i)
#define TS2(i)
#define TSI(n, i)
#define PH(i)
#define CK(i, dep)
#define ARR()
#define PROG(u)

__device__ __forceinline__ uint32_t s2u(const void* p) { return (uint32_t)__cvta_generic_to_shared(p); }
__device__ __forceinline__ void mbar_init(uint32_t bar, int cnt) {
    asm volatile("mbarrier.init.shared::cta.b64 [%0], %1;" :: "r"(bar), "r"(cnt) : "memory");
}
__device__ __forceinline__ void mbar_wait(uint32_t bar, uint32_t parity) {
    asm volatile("{\n.reg .pred p;\n.reg .u32 n;\nmov.u32 n, 0;\nWAIT_LOOP:\n"
                 "mbarrier.try_wait.parity.shared::cta.b64 p, [%0], %1;\n"
                 "@p bra WAIT_DONE;\nadd.u32 n, n, 1;\nsetp.lt.u32 p, n, %2;\n@p bra WAIT_LOOP;\nWAIT_DONE:\n}"
                 :: "r"(bar), "r"(parity), "n"(SPIN_MAX) : "memory");
}
__device__ __forceinline__ void request_tile(uint32_t dst, const CUtensorMap* tm, int unit, uint32_t bar, uint64_t pol) {
    asm volatile("{\n.reg .pred p;\nelect.sync _|p, 0xffffffff;\n"
                 "@p mbarrier.arrive.expect_tx.shared::cta.b64 _, [%2], %6;\n"
                 "@p cp.async.bulk.tensor.2d.shared::cluster.global.mbarrier::complete_tx::bytes.L2::cache_hint "
                 "[%0], [%1, {%3, %4}], [%2], %5;\n}"
                 :: "r"(dst), "l"(tm), "r"(bar), "r"(0), "r"(unit * TILE_ROWS), "l"(pol), "n"(TILE_BYTES) : "memory");
}
__device__ __forceinline__ void put_groups(void* dst, int mode, const float (&o)[6], float tag, float tag2) {
    asm volatile("{\n.reg .pred s, t;\n.reg .b128 u, v;\n.reg .b64 a, b;\n"
                 "setp.eq.s32 s, %1, 0;\nsetp.ne.s32 t, %1, 2;\n"
                 "@t bra.uni SINGLE;\n"
                 "red.relaxed.gpu.global.add.v4.f32 [%0+4096], {%2,%3,%4,%8};\n"
                 "red.relaxed.gpu.global.add.v4.f32 [%0+4224], {%5,%6,%7,%9};\n"
                 "SINGLE:\n"
                 "@s bra.uni STORE;\n"
                 "red.relaxed.gpu.global.add.v4.f32 [%0], {%2,%3,%4,%8};\n"
                 "red.relaxed.gpu.global.add.v4.f32 [%0+128], {%5,%6,%7,%9};\n"
                 "STORE:\n"
                 "mov.b64 a, {%2, %3};\nmov.b64 b, {%4, %8};\nmov.b128 u, {a, b};\n"
                 "mov.b64 a, {%5, %6};\nmov.b64 b, {%7, %9};\nmov.b128 v, {a, b};\n"
                 "@s st.relaxed.gpu.global.b128 [%0], u;\n@s st.relaxed.gpu.global.b128 [%0+128], v;\n}"
                 :: "l"(dst), "r"(mode), "f"(o[0]), "f"(o[1]), "f"(o[2]), "f"(o[3]), "f"(o[4]), "f"(o[5]), "f"(tag), "f"(tag2) : "memory");
}
__device__ __forceinline__ void request_box(uint32_t dst, const CUtensorMap* tm, int col, int row, uint32_t bar, uint32_t bytes) {
    asm volatile("{\n.reg .pred p, q;\nelect.sync _|p, 0xffffffff;\nsetp.ne.and.u32 q, %5, 0, p;\n"
                 "@q mbarrier.arrive.expect_tx.shared::cta.b64 _, [%2], %5;\n"
                 "@p cp.async.bulk.tensor.2d.shared::cluster.global.mbarrier::complete_tx::bytes [%0], [%1, {%3, %4}], [%2];\n}"
                 :: "r"(dst), "l"(tm), "r"(bar), "r"(col), "r"(row), "r"(bytes) : "memory");
}
__device__ __forceinline__ uint32_t lds32(uint32_t addr) {
    uint32_t v;
    asm volatile("ld.shared.u32 %0, [%1];" : "=r"(v) : "r"(addr) : "memory");
    return v;
}
__device__ __forceinline__ void ldsm4(uint32_t (&r)[4], uint32_t addr) {
    asm volatile("ldmatrix.sync.aligned.m8n8.x4.shared.b16 {%0,%1,%2,%3}, [%4];"
                 : "=r"(r[0]), "=r"(r[1]), "=r"(r[2]), "=r"(r[3]) : "r"(addr) : "memory");
}
__device__ __forceinline__ void ldsm4t(uint32_t (&r)[4], uint32_t addr) {
    asm volatile("ldmatrix.sync.aligned.m8n8.x4.trans.shared.b16 {%0,%1,%2,%3}, [%4];"
                 : "=r"(r[0]), "=r"(r[1]), "=r"(r[2]), "=r"(r[3]) : "r"(addr) : "memory");
}
__device__ __forceinline__ void mma16816(float (&c)[4], const uint32_t (&a)[4], uint32_t b0, uint32_t b1) {
    asm volatile("mma.sync.aligned.m16n8k16.row.col.f32.bf16.bf16.f32 {%0,%1,%2,%3}, {%4,%5,%6,%7}, {%8,%9}, {%0,%1,%2,%3};"
                 : "+f"(c[0]), "+f"(c[1]), "+f"(c[2]), "+f"(c[3])
                 : "r"(a[0]), "r"(a[1]), "r"(a[2]), "r"(a[3]), "r"(b0), "r"(b1));
}
struct Warm {
    float c[4] = {};
    __device__ __forceinline__ void operator()() {
        asm volatile("mma.sync.aligned.m16n8k8.row.col.f32.bf16.bf16.f32 {%0,%1,%2,%3}, {%4,%4}, {%4}, {%0,%1,%2,%3};"
                     : "+f"(c[0]), "+f"(c[1]), "+f"(c[2]), "+f"(c[3]) : "r"(0));
    }
    __device__ __forceinline__ void done(uint32_t scrap) {
        asm volatile("{\n.reg .pred p;\nsetp.gt.f32 p, %1, 0f3f800000;\n@p st.shared.f32 [%0], %1;\n}" :: "r"(scrap), "f"(c[0]) : "memory");
    }
};
__device__ __forceinline__ uint4 ld_relaxed_v4(const void* p) {
    uint4 v;
    asm volatile("ld.relaxed.gpu.global.v4.u32 {%0,%1,%2,%3}, [%4];" : "=r"(v.x), "=r"(v.y), "=r"(v.z), "=r"(v.w) : "l"(p) : "memory");
    return v;
}
__device__ __forceinline__ float4 ld_relaxed_f4(const void* p) {
    float4 v;
    asm volatile("ld.relaxed.gpu.global.v4.f32 {%0,%1,%2,%3}, [%4];" : "=f"(v.x), "=f"(v.y), "=f"(v.z), "=f"(v.w) : "l"(p) : "memory");
    return v;
}
__device__ __forceinline__ float2 ld_relaxed_f2(const void* p) {
    float2 v;
    asm volatile("ld.relaxed.gpu.global.v2.f32 {%0,%1}, [%2];" : "=f"(v.x), "=f"(v.y) : "l"(p) : "memory");
    return v;
}
__device__ __forceinline__ float4 ld_relaxed_b128(const void* p) {
    float4 v;
    asm volatile("{\n.reg .b128 t;\n.reg .b64 a, b;\nld.relaxed.gpu.global.b128 t, [%4];\nmov.b128 {a, b}, t;\n"
                 "mov.b64 {%0, %1}, a;\nmov.b64 {%2, %3}, b;\n}" : "=f"(v.x), "=f"(v.y), "=f"(v.z), "=f"(v.w) : "l"(p) : "memory");
    return v;
}
__device__ __forceinline__ void st_relaxed_b128(void* p, float x, float y, float z, float w) {
    asm volatile("{\n.reg .b128 t;\n.reg .b64 a, b;\nmov.b64 a, {%1, %2};\nmov.b64 b, {%3, %4};\nmov.b128 t, {a, b};\n"
                 "st.relaxed.gpu.global.b128 [%0], t;\n}" :: "l"(p), "f"(x), "f"(y), "f"(z), "f"(w) : "memory");
}
__device__ __forceinline__ unsigned ld_acquire(const unsigned* p) {
    unsigned v;
    asm volatile("ld.acquire.gpu.global.u32 %0, [%1];" : "=r"(v) : "l"(p) : "memory");
    return v;
}
__device__ __forceinline__ void st_relaxed(void* p, uint32_t v) {
    asm volatile("st.relaxed.gpu.global.u32 [%0], %1;" :: "l"(p), "r"(v) : "memory");
}
__device__ __forceinline__ void red_f2(float* p, float a, float b) {
    asm volatile("red.relaxed.gpu.global.add.v2.f32 [%0], {%1,%2};" :: "l"(p), "f"(a), "f"(b) : "memory");
}
__device__ __forceinline__ void draw(int& ticket, unsigned* ctr, bool pred) {
    asm volatile("{\n.reg .pred p;\nsetp.ne.u32 p, %2, 0;\n@p atom.relaxed.gpu.global.inc.u32 %0, [%1], 0x7fffffff;\n}"
                 : "+r"(ticket) : "l"(ctr), "r"((uint32_t)pred) : "memory");
}
__device__ __forceinline__ void red_release(unsigned* p) {
    asm volatile("red.release.gpu.global.add.u32 [%0], 1;" :: "l"(p) : "memory");
}
__device__ __forceinline__ uint32_t ld_relaxed_u32(const void* p) {
    uint32_t v;
    asm volatile("ld.relaxed.gpu.global.u32 %0, [%1];" : "=r"(v) : "l"(p) : "memory");
    return v;
}
__device__ __forceinline__ float rcp_approx(float v) {
    float r;
    asm("rcp.approx.ftz.f32 %0, %1;" : "=f"(r) : "f"(v));
    return r;
}
__device__ __forceinline__ float ex2_approx(float v) {
    float e;
    asm("ex2.approx.ftz.f32 %0, %1;" : "=f"(e) : "f"(v));
    return e;
}
__device__ __forceinline__ float sigmoid_approx(float v) { return rcp_approx(1.0f + ex2_approx(v * -1.4426950408889634f)); }
__device__ __forceinline__ float sqrt_approx(float v) {
    float r;
    asm("sqrt.approx.ftz.f32 %0, %1;" : "=f"(r) : "f"(v));
    return r;
}
__device__ __forceinline__ bool all(bool v) { return __all_sync(0xffffffffu, v); }
__device__ __forceinline__ void wait_count(const unsigned* p, unsigned target) {
#pragma unroll 1
    for (int it = 0; it < SPIN_MAX; it++) {
        if (all(ld_acquire(p) >= target)) break;
        __nanosleep(400);
    }
}
__device__ __forceinline__ float wait_sum(const void* p, float n, int nap = 0) {
    float2 v;
#pragma unroll 1
    for (int it = 0; it < SPIN_MAX; it++) {
        v = ld_relaxed_f2(p);
        if (all(v.y >= n)) break;
        if (all(v.y == 0.f)) __nanosleep(600);
        else if (nap) __nanosleep(nap);
    }
    return v.x;
}
__device__ __forceinline__ void wait_row(int bh, float n) { wait_sum(g_st.lsum[bh], n); }
__device__ __forceinline__ void wait_row_o(int bh, float n) {
    wait_row(bh, n);
    if (bh >= RED0) return;
#pragma unroll 1
    for (int it = 0; it < SPIN_MAX; it++) {
        if (all(__uint_as_float(ld_relaxed_u32(&g_st.oacc[oidx(bh, 0)].w)) == UPB)) break;
        __nanosleep(300);
    }
}
constexpr uint32_t SLOT_K = (uint32_t)(((1ull << 32) + SLOT_TICKS - 1) / SLOT_TICKS);
#define SLOT_ASM(t, n, p, phase, k, open) \
    "mov.u32 " n ", 0;\nSLOT:\nmov.u32 " t ", %%globaltimer_lo;\nadd.u32 " n ", " n ", 1;\nsetp.lt.u32 " p ", " n ", 24;\nshr.u32 " t ", " t ", 5;\n" \
    "mad.lo.u32 " t ", " t ", " k ", " phase ";\nsetp.ge.and.u32 " p ", " t ", " open ", " p ";\n@" p " bra.uni SLOT;\n"
template <int PHASE> __host__ __device__ constexpr uint32_t slot_phase() { return SLOT_K / 2 - PHASE * SLOT_K; }
template <int PHASE> __device__ __forceinline__ void wait_slot() {
    if (PHASE < 0) return;
    asm volatile("{\n.reg .pred p;\n.reg .b32 t, n;\n" SLOT_ASM("t", "n", "p", "%0", "%1", "%2") "}"
                 :: "n"(slot_phase<PHASE>()), "n"(SLOT_K), "n"(SLOT_OPEN * SLOT_K) : "memory");
}
__device__ __forceinline__ void wait_clock(uint32_t t, Warm& warm) { while (!all((int)(clock() - t) >= 0)) { warm(); } }
__device__ __forceinline__ void spin_ns(int ns) { const uint32_t t = clock() + ns * 2; while (!all((int)(clock() - t) >= 0)) {} }
__device__ __forceinline__ uint32_t pack_bf16(float lo, float hi) {
    uint32_t r;
    asm("cvt.rn.bf16x2.f32 %0, %1, %2;" : "=r"(r) : "f"(hi), "f"(lo));
    return r;
}
__device__ __forceinline__ float bf16r(float v) { return __uint_as_float(pack_bf16(0.f, v)); }
__device__ __forceinline__ uint32_t nonzero(uint32_t w) { return w ? w : 0x80008000u; }
__device__ __forceinline__ uint32_t pack_neg(float lo, float hi) { return nonzero(pack_bf16(-lo, -hi)); }
__device__ __forceinline__ float lo_f(uint32_t v) { return __uint_as_float(v << 16); }
__device__ __forceinline__ float hi_f(uint32_t v) { return __uint_as_float(v & 0xffff0000u); }
__device__ __forceinline__ float warp_sum(float v) {
#pragma unroll
    for (int o = 16; o; o >>= 1) v += __shfl_xor_sync(0xffffffffu, v, o);
    return v;
}
__device__ __forceinline__ void layernorm20(float (&v)[20]) {
    float s = 0.f;
#pragma unroll
    for (int i = 0; i < 20; i++) s += v[i];
    const float mean = warp_sum(s) * (1.0f / DM);
    float q = 0.f;
#pragma unroll
    for (int i = 0; i < 20; i++) { const float d = v[i] - mean; q += d * d; }
    const float var = bf16r(warp_sum(q) * (1.0f / DM));
    const float m = bf16r(mean);
    const float rden = 1.0f / bf16r(sqrtf(bf16r(var + 1e-5f)));
#pragma unroll
    for (int i = 0; i < 20; i++) v[i] = bf16r(bf16r(v[i] - m) * rden);
}

__device__ __forceinline__ void moments(float m1, float m2, float& nmean, float& rden) {
    m1 *= 1.0f / DM;
    const float var = bf16r(fmaxf(fmaf(-m1, m1, m2 * (1.0f / DM)), 0.f));
    nmean = bf16r(m1);
    rden = rcp_approx(bf16r(sqrt_approx(bf16r(var + 1e-5f))));
}
__device__ __forceinline__ float sel4(int j, float a, float b, float c, float d) {
    float lo, hi, r;
    asm("{\n.reg .pred p;\nsetp.ne.s32 p, %3, 0;\nselp.f32 %0, %2, %1, p;\n}" : "=f"(lo) : "f"(a), "f"(b), "r"(j & 1));
    asm("{\n.reg .pred p;\nsetp.ne.s32 p, %3, 0;\nselp.f32 %0, %2, %1, p;\n}" : "=f"(hi) : "f"(c), "f"(d), "r"(j & 1));
    asm("{\n.reg .pred p;\nsetp.ne.s32 p, %3, 0;\nselp.f32 %0, %2, %1, p;\n}" : "=f"(r) : "f"(lo), "f"(hi), "r"(j & 2));
    return r;
}
template <typename T> __device__ __forceinline__ void pin(T*& p) { asm volatile("" : "+l"(p)); }
__device__ __forceinline__ void pin(uint32_t& v) { asm volatile("" : "+r"(v)); }
__device__ __forceinline__ void pin(float& v) { asm volatile("" : "+f"(v)); }
__device__ __forceinline__ uint32_t after(uint32_t n, float v) {
    asm volatile("{\n.reg .pred p;\nsetp.eq.u32 p, %1, 0x7fc1a5a5;\n@p add.u32 %0, %0, 32;\n}" : "+r"(n) : "r"(__float_as_uint(v)));
    return n;
}
__device__ __forceinline__ float2 lds64f(uint32_t addr) {
    float2 v;
    asm volatile("ld.shared.v2.f32 {%0,%1}, [%2];" : "=f"(v.x), "=f"(v.y) : "r"(addr) : "memory");
    return v;
}
__device__ __forceinline__ void sts32f(uint32_t addr, float v) { asm volatile("st.shared.f32 [%0], %1;" :: "r"(addr), "f"(v) : "memory"); }
template <int ID> __device__ __forceinline__ void fin_arrive() { asm volatile("bar.arrive %0, 288;" :: "n"(ID) : "memory"); }
template <int ID> __device__ __forceinline__ void fin_sync() { asm volatile("bar.sync %0, 288;" :: "n"(ID) : "memory"); }
template <int ID> __device__ __forceinline__ void fin_sync(uint32_t n) { asm volatile("bar.sync %0, %1;" :: "n"(ID), "r"(n) : "memory"); }
__device__ __forceinline__ float2 sum8(uint32_t addr) {
    float2 t[8];
#pragma unroll
    for (int w = 0; w < 8; w++) t[w] = lds64f(addr + w * 128);
    return make_float2(((t[0].x + t[1].x) + (t[2].x + t[3].x)) + ((t[4].x + t[5].x) + (t[6].x + t[7].x)),
                       ((t[0].y + t[1].y) + (t[2].y + t[3].y)) + ((t[4].y + t[5].y) + (t[6].y + t[7].y)));
}
__device__ __forceinline__ float4 sum4x4(uint32_t addr, int pitch) {
    float4 t[4];
#pragma unroll
    for (int w = 0; w < 4; w++)
        asm volatile("ld.shared.v4.f32 {%0,%1,%2,%3}, [%4];" : "=f"(t[w].x), "=f"(t[w].y), "=f"(t[w].z), "=f"(t[w].w) : "r"(addr + w * pitch) : "memory");
    return make_float4((t[0].x + t[1].x) + (t[2].x + t[3].x), (t[0].y + t[1].y) + (t[2].y + t[3].y),
                       (t[0].z + t[1].z) + (t[2].z + t[3].z), (t[0].w + t[1].w) + (t[2].w + t[3].w));
}
__device__ __forceinline__ void sts64f(uint32_t addr, float x, float y) {
    asm volatile("st.shared.v2.f32 [%0], {%1,%2};" :: "r"(addr), "f"(x), "f"(y) : "memory");
}
__device__ __forceinline__ void lds128_if(uint4& v, uint32_t addr, bool pred) {
    asm volatile("{\n.reg .pred p;\nsetp.ne.u32 p, %5, 0;\n@p ld.shared.v4.u32 {%0,%1,%2,%3}, [%4];\n}"
                 : "+r"(v.x), "+r"(v.y), "+r"(v.z), "+r"(v.w) : "r"(addr), "r"((uint32_t)pred) : "memory");
}
__device__ __forceinline__ void sts128f(uint32_t addr, float x, float y, float z, float w) {
    asm volatile("st.shared.v4.f32 [%0], {%1,%2,%3,%4};" :: "r"(addr), "f"(x), "f"(y), "f"(z), "f"(w) : "memory");
}
template <int NJ>
__device__ __forceinline__ void load_o(uint32_t (&ob)[3 * NJ][2], int bh, int J0, int j) {
    float4 v[NJ][4];
    float2 l;
#pragma unroll 1
    for (int it = 0; it < SPIN_MAX; it++) {
#pragma unroll
        for (int J = 0; J < NJ; J++) {
#pragma unroll
            for (int e = 0; e < 4; e++) v[J][e] = ld_relaxed_f4(&g_st.oacc[oidx(bh, j)] + oidx(0, (J0 + J) * 16 + e * 4));
        }
        l = ld_relaxed_f2(g_st.lsum[bh]);
        bool ok = l.y == UPB;
#pragma unroll
        for (int J = 0; J < NJ; J++) {
#pragma unroll
            for (int e = 0; e < 4; e++) ok &= v[J][e].w == UPB;
        }
        if (all(ok)) break;
    }
    const float rl = __fdividef(1.0f, l.x);
#pragma unroll
    for (int J = 0; J < NJ; J++) {
        ob[3 * J][0] = pack_bf16(v[J][0].x * rl, v[J][1].x * rl);     ob[3 * J][1] = pack_bf16(v[J][2].x * rl, v[J][3].x * rl);
        ob[3 * J + 1][0] = pack_bf16(v[J][0].y * rl, v[J][1].y * rl); ob[3 * J + 1][1] = pack_bf16(v[J][2].y * rl, v[J][3].y * rl);
        ob[3 * J + 2][0] = pack_bf16(v[J][0].z * rl, v[J][1].z * rl); ob[3 * J + 2][1] = pack_bf16(v[J][2].z * rl, v[J][3].z * rl);
    }
}
__device__ __forceinline__ int near_side(uint32_t sb) {
    uint32_t v;
    asm volatile("ld.volatile.shared.u32 %0, [%1];" : "=r"(v) : "r"(sb + SM_SIDE) : "memory");
    return v;
}
__device__ __forceinline__ void poll_row(uint4& a, uint4& b, uint2& c, const void* pa, const void* pb, const void* pc, uint32_t sa, uint32_t sc,
                                         bool arrive, bool nap, uint32_t bar, Warm& warm) {
    asm volatile("{\n.reg .pred p, q, r, s;\n.reg .b32 m, n, it;\n"
                 "setp.ne.u32 r, %19, 0;\nsetp.ne.u32 s, %20, 0;\nmov.u32 it, 0;\n"
                 "POLL:\n"
                 SLOT_ASM("m", "n", "p", "%23", "%24", "%25")
                 "ld.relaxed.gpu.global.v4.u32 {%0,%1,%2,%3}, [%14];\n"
                 "ld.relaxed.gpu.global.v4.u32 {%4,%5,%6,%7}, [%15];\n"
                 "ld.relaxed.gpu.global.v2.u32 {%8,%9}, [%16];\n"
                 "add.u32 it, it, 1;\nsetp.ge.u32 q, it, %21;\n"
                 "mov.u32 m, 0;\nmma.sync.aligned.m16n8k8.row.col.f32.bf16.bf16.f32 {%10,%11,%12,%13}, {m,m}, {m}, {%10,%11,%12,%13};\n"
                 "st.shared.v4.u32 [%17], {%0,%1,%2,%3};\n"
                 "st.shared.v4.u32 [%17+512], {%4,%5,%6,%7};\n"
                 "st.shared.v2.u32 [%18], {%8,%9};\n"
                 "min.u32 m, %0, %1;\nmin.u32 m, m, %2;\nmin.u32 n, %3, %4;\nmin.u32 n, n, %5;\nmin.u32 m, m, %6;\nmin.u32 m, m, %7;\n"
                 "min.u32 n, n, m;\nmin.u32 m, %8, %9;\nmin.u32 m, m, n;\n"
                 "setp.ne.or.u32 p, m, 0, q;\n"
                 "vote.sync.all.pred p, p, 0xffffffff;\n"
                 "and.pred q, p, r;\n"
                 "bar.warp.sync 0xffffffff;\n"
                 "@q mbarrier.arrive.shared::cta.b64 _, [%22];\n"
                 "@p bra.uni DONE;\n"
                 "@s nanosleep.u32 500;\n"
                 "bra.uni POLL;\n"
                 "DONE:\n}"
                 : "=&r"(a.x), "=&r"(a.y), "=&r"(a.z), "=&r"(a.w), "=&r"(b.x), "=&r"(b.y), "=&r"(b.z), "=&r"(b.w), "=&r"(c.x), "=&r"(c.y),
                   "+f"(warm.c[0]), "+f"(warm.c[1]), "+f"(warm.c[2]), "+f"(warm.c[3])
                 : "l"(pa), "l"(pb), "l"(pc), "r"(sa), "r"(sc), "r"((uint32_t)arrive), "r"((uint32_t)nap), "n"(SPIN_MAX), "r"(bar),
                   "n"(slot_phase<PH_H>()), "n"(SLOT_K), "n"(SLOT_OPEN * SLOT_K) : "memory");
}
__device__ __forceinline__ void aux_sync() { asm volatile("bar.sync 1, 256;" ::: "memory"); }

__global__ void __launch_bounds__(NTHREADS, 1)
fused_decode_kernel(const __grid_constant__ Params p) {
    extern __shared__ __align__(1024) unsigned char smem[];
    const uint32_t sb = s2u(smem);
    const int tid = threadIdx.x, cta = blockIdx.x;
    if (tid < 32 && cta < NQ_CTAS) {
        asm volatile("{\n.reg .pred p;\nelect.sync _|p, 0xffffffff;\n"
                     "@p mbarrier.init.shared::cta.b64 [%2], 1;\n"
                     "@p fence.mbarrier_init.release.cluster;\n"
                     "@p mbarrier.arrive.expect_tx.shared::cta.b64 _, [%2], 61440;\n"
                     "@p cp.async.bulk.tensor.2d.shared::cluster.global.mbarrier::complete_tx::bytes [%0], [%1, {%3, %4}], [%2];\n"
                     "@p cp.async.bulk.tensor.2d.shared::cluster.global.mbarrier::complete_tx::bytes [%0+15360], [%1, {%3, %5}], [%2];\n"
                     "@p cp.async.bulk.tensor.2d.shared::cluster.global.mbarrier::complete_tx::bytes [%0+30720], [%1, {%3, %6}], [%2];\n"
                     "@p cp.async.bulk.tensor.2d.shared::cluster.global.mbarrier::complete_tx::bytes [%0+46080], [%1, {%3, %7}], [%2];\n}"
                     :: "r"(sb + SM_W), "l"(&p.wq), "r"(sb + BAR_WQ), "r"(cta * 48), "r"(0), "r"(160), "r"(320), "r"(480) : "memory");
    }
    const int warp = __shfl_sync(0xffffffffu, tid >> 5, 0), lane = tid & 31;
    constexpr int grid = NCTAS;
    const int g = lane >> 2, j = lane & 3;
    TS(0);
    if (tid == 160) {
        mbar_init(sb + BAR_WO, 1);
        mbar_init(sb + BAR_H, 1);
#pragma unroll
        for (int i = 0; i < 8 + 2 * NWORK; i++) mbar_init(sb + BAR_FW + i * 8, 1);
        sts32f(sb + SM_SIDE, 0.f);
        asm volatile("fence.mbarrier_init.release.cluster;" ::: "memory");
        asm volatile("fence.proxy.async.shared::cta;" ::: "memory");
    }
    __syncthreads();
    if (warp >= NAUX + NWORK) {
        const int fw = warp - (NAUX + NWORK), fi = ffn_slice(cta);
        if (fw == 0) {
            if (cta < NQ_CTAS) {
#pragma unroll
                for (int i = lane; i < STATE_V4; i += 32)
                    if (cta * STATE_V4 + i < (int)(sizeof(State) / 16)) reinterpret_cast<uint4*>(&g_st)[cta * STATE_V4 + i] = make_uint4(0u, 0u, 0u, 0u);
                __syncwarp();
                if (lane == 0) red_release(g_cnt_z);
            }
            TSW(2); wait_count(g_cnt_z, NQ_CTAS); TSW(29);
            asm volatile("bar.arrive 2, %0;" :: "n"((NWORK + 2) * 32) : "memory");
            fin_arrive<3>();
        } else {
            asm volatile("bar.sync 2, %0;" :: "n"((NWORK + 2) * 32) : "memory");
            uint32_t best[2] = {~0u, ~0u};
#pragma unroll 1
            for (int i = 0; i < NPROBE; i++) {
#pragma unroll
                for (int c = 0; c < 2; c++) {
                    uint32_t t0 = clock(), t1 = t0;
                    int v = 0;
                    draw(v, &g_st.hx.w[c][PROBE], lane == 0);
                    asm volatile("{\n.reg .pred p;\nsetp.ne.u32 p, %1, 0xffffffff;\n@p mov.u32 %0, %%clock;\n}" : "+r"(t1) : "r"(v) : "memory");
                    best[c] = min(best[c], t1 - t0);
                }
                __nanosleep(1000);
            }
            if (lane == 0) sts32f(sb + SM_SIDE, __uint_as_float(best[1] < best[0]));
        }
        int job = cta;
        auto sum_rows = [&](int row_end) {
#pragma unroll 1
            for (; job < 8 * min(row_end, RED0); job += NCTAS) {
                const int row = job >> 3, grp = (job & 7) * 8 + (lane & 7);
                wait_row(row, UPB);
                const float4* src = &g_ring[row % RING][lane >> 3][grp];
                float sx = 0.f, sy = 0.f, sz = 0.f;
#pragma unroll 1
                for (int i = 0; i < 2; i++, src += 64 * 64) {
                    float4 v[16];
#pragma unroll 1
                    for (int it = 0; it < SPIN_MAX; it++) {
                        bool ok = true;
#pragma unroll
                        for (int k = 0; k < 16; k++) v[k] = ld_relaxed_b128(src + k * 4 * 64);
#pragma unroll
                        for (int k = 0; k < 16; k++) ok &= v[k].w == (float)(row + 1);
                        if (all(ok)) break;
                    }
#pragma unroll
                    for (int k = 0; k < 16; k++) { sx += v[k].x; sy += v[k].y; sz += v[k].z; }
                }
#pragma unroll
                for (int o = 8; o < 32; o <<= 1) {
                    sx += __shfl_xor_sync(0xffffffffu, sx, o); sy += __shfl_xor_sync(0xffffffffu, sy, o); sz += __shfl_xor_sync(0xffffffffu, sz, o);
                }
                if (lane < 8) st_relaxed_b128(&g_st.oacc[oidx(row, grp)], sx, sy, sz, UPB);
            }
        };
        const int ho0 = lane / 20 * 256 + lane % 20 * 4, ho1 = (lane + 32) / 20 * 256 + (lane + 32) % 20 * 4, ho2 = 3 * 256 + 16 + 2 * lane;
        uint32_t wr[10] = {};
        float wsum = 0.f;
        if (is_g(cta) && fw == 0) {
#pragma unroll
            for (int i = 0; i < 10; i++) {
                const int w = 4 * lane + 128 * (i >> 2) + (i & 3) - (i >= 8 ? 2 * lane : 0);
                wr[i] = *reinterpret_cast<const uint32_t*>(p.wr + (w >> 4) * 32 + (w & 3) * 8 + ((w >> 1) & 6));
                wsum += lo_f(wr[i]) + hi_f(wr[i]);
            }
            wsum = warp_sum(wsum);
        }
        const int fb = lane >> 3, fg = lane & 7;
        if (fw == 0) {
#pragma unroll
            for (int i = lane; i < DM / 2; i += 32) sts32f(sb + SM_X + 4 * HPITCH + i * 4, __uint_as_float(0x3f803f80u));
        }
        Warm warm;
        float nmean = 0.f, rden = 0.f, sig = 0.f;
#pragma unroll 1
        for (int b = 0; b < NB; b++) {
            const bool ffn = b >= NB - 2;
            if (fw == 0) {
                sum_rows((b + 1) * NH);
                if (ffn) asm volatile("bar.arrive 8, 64;" ::: "memory");
            } else if (ffn) {
                asm volatile("bar.sync 8, 64;" ::: "memory");
                if (b == NB - 1 && (is_f(cta) || is_g(cta) || ALL_LOADERS)) {
                    uint32_t t0 = 0, now;
#pragma unroll 1
                    for (int it = 0; it < SPIN_MAX; it++) {
                        t0 = ld_relaxed_u32(g_st.fw_time);
                        if (all(t0 != 0)) break;
                        __nanosleep(400);
                    }
                    asm volatile("fence.proxy.async.shared::cta;" ::: "memory");
#pragma unroll 1
                    for (int it = 0; it < SPIN_MAX; it++) {
                        asm volatile("mov.u32 %0, %%globaltimer_lo;" : "=r"(now));
                        if (all((int)(now - t0) >= FW_AT_NS)) break;
                    }
                    TSW(9);
                    uint32_t t = clock() + (is_f(cta) ? (fi & 1) * (FW_GAP / 2) : FW_MID + (fi & 3) * (FW_GAP2 / 4));
#pragma unroll 1
                    for (int i = 0; i < 8; i++) {
                        const uint32_t bar = sb + BAR_FW + i * 8;
                        if (is_f(cta)) {
                            wait_clock(t, warm);
                            request_box(sb + SM_W + i * 10240, (i & 1) ? &p.wu : &p.wg, fi * 32, (i >> 1) * 160, bar, 10240);
                            t += FW_GAP;
                        } else if (is_g(cta)) {
                            wait_clock(t, warm);
                            asm volatile("{\n.reg .pred p;\nelect.sync _|p, 0xffffffff;\n"
                                         "@p mbarrier.arrive.expect_tx.shared::cta.b64 _, [%2], 6144;\n"
                                         "@p cp.async.bulk.tensor.4d.shared::cluster.global.mbarrier::complete_tx::bytes [%0], [%1, {%3, %4, %4, %5}], [%2];\n}"
                                         :: "r"(sb + SM_W + i * 6144), "l"(&p.wd), "r"(bar), "r"(fi * 16), "r"(0), "r"(i * 12) : "memory");
                            t += FW_GAP2;
                        }
                    }
                }
                if (is_f(cta)) {
                    const uint32_t* src = &g_st.hx.w[near_side(sb)][min(fb, b) * 256 + 96];
                    float4 m;
#pragma unroll 1
                    for (int it = 0; it < SPIN_MAX; it++) {
                        wait_slot<PH_M>();
                        m = ld_relaxed_f4(src);
                        warm();
                        if (all(m.y + m.w == 2 * (NCTAS - NE_CTAS))) break;
                        if (b < NB - 1) __nanosleep(500);
                    }
                    moments(m.x, m.z, m.x, m.z);
                    sts64f(sb + SM_RED + 5120 + fb * 8, m.x, m.z);
                }
            }
            if (fw == 0 && cta >= NE_CTAS) {
                const int lc = cta - NE_CTAS, col = lc * 32 + 2 * (lane & 15);
                const uint32_t xv = *reinterpret_cast<const uint32_t*>(p.x + b * DM + col);
                uint32_t* dst = &(ffn ? g_st.hx.w : g_st.lx.w + 2)[lane >> 4][(b & 1) * 128 + lc / 5 * 256 + lc % 5 * 16 + (col & 6) * 2 + ((col >> 3) & 3)];
                uint32_t part = sb + SM_RED + (lane & 15) * 8;
                wait_row(b * NH + 28, 1);
                float4 early;
#pragma unroll 1
                for (int it = 0; it < SPIN_MAX; it++) {
                    early = ld_relaxed_f4(&g_st.attn[b][col]);
                    if (all(early.y == NE_CTAS / 4 && early.w == NE_CTAS / 4)) break;
                }
                if (early.x != 1.2345f && lane == 0) TS2(6);
                CK(1, __float_as_uint(early.x));
                const float x0 = -(lo_f(xv) + early.x), x1 = -(hi_f(xv) + early.z);
                fin_sync<4>(after(after(288, x0), x1));
                CK(2, lds32(sb + SM_RED));
                const float2 late = sum8(part);
                const uint32_t hv = nonzero(pack_bf16(x0 - late.x, x1 - late.y));
                st_relaxed(dst, hv);
                if (ffn) st_relaxed(dst + 2048, hv);
                CK(3, 0);
                float m = lane < 16 ? lo_f(hv) + hi_f(hv) : fmaf(lo_f(hv), lo_f(hv), hi_f(hv) * hi_f(hv));
#pragma unroll
                for (int o = 1; o < 16; o <<= 1) m += __shfl_xor_sync(0xffffffffu, m, o);
                if ((lane & 14) == 0) red_f2(reinterpret_cast<float*>(&g_st.hx.w[lane & 1][b * 256 + 96 + (lane >> 4) * 2]), m, 1.f);
                fin_arrive<5>();
            }
            if (fw == 0 && (is_g(cta) || is_f(cta))) {
                const uint32_t* src = &(ffn ? g_st.hx.w : g_st.lx.w + 2)[near_side(sb) ^ (ffn && is_g(cta) ? 3 : 0)][(b & 1) * 128];
                const uint32_t hrow = sb + SM_X + b * HPITCH;
                wait_sum(b == NB - 1 ? (const void*)&g_st.lx.w[near_side(sb) ^ 1][3 * 256] : g_st.lsum[b * NH + NH - 1], UPB, 100);
                wait_clock(clock() + HGATE_NS * 2, warm);
                uint4 h0, h1;
                uint2 h2;
                poll_row(h0, h1, h2, src + ho0, src + ho1, src + ho2, hrow + lane * 16, hrow + 1024 + lane * 8, ffn && lane == 0, b < NB - 1, sb + BAR_H, warm);
                CK(4, h0.x);
                if (is_g(cta)) {
                    const uint32_t hw[10] = {h0.x, h0.y, h0.z, h0.w, h1.x, h1.y, h1.z, h1.w, h2.x, h2.y};
                    float m1 = 0.f, m2 = 0.f, rr = 0.f;
#pragma unroll
                    for (int i = 0; i < 10; i++) {
                        const float v0 = lo_f(hw[i]), v1 = hi_f(hw[i]);
                        m1 += v0 + v1;
                        m2 = fmaf(v0, v0, fmaf(v1, v1, m2));
                        rr = fmaf(v0, lo_f(wr[i]), fmaf(v1, hi_f(wr[i]), rr));
                    }
                    moments(warp_sum(m1), warp_sum(m2), m1, m2);
                    const float sg = bf16r(sigmoid_approx(bf16r((m1 * wsum - warp_sum(rr)) * m2)));
                    if (fb == b) { nmean = m1; rden = m2; sig = sg; }
                    __syncwarp();
                    if (ffn) {
                        const int yj = 2 * (fb & 1) + (fb >> 1);
                        uint32_t ypart = sb + SM_RED2 + yj * 128 + ((fg + 2 * yj) & 7) * 16;
                        __nv_bfloat16* out = p.out + fb * DM + fi * 16 + fg;
                        const float2 hw2 = lds64f(sb + SM_X + fb * HPITCH + ((fi >> 1) * 16 + (fg & 6) * 2 + (fi & 1) * 2) * 4);
                        const uint32_t w0 = __float_as_uint(hw2.x), w1 = __float_as_uint(hw2.y);
                        const float nh0 = (fg & 1) ? hi_f(w0) : lo_f(w0), nh1 = (fg & 1) ? hi_f(w1) : lo_f(w1);
                        const float ln0 = bf16r(bf16r(nmean - nh0) * rden) - nh0, ln1 = bf16r(bf16r(nmean - nh1) * rden) - nh1;
                        pin(ypart); pin(out);
                        fin_sync<6>(after(after(after(288, sig), ln0), ln1));
                        CK(10, lds32(ypart));
                        const float4 ya = sum4x4(ypart, 512), yb = sum4x4(ypart + 2048, 512);
                        const float4 y = make_float4(ya.x + yb.x, ya.y + yb.y, ya.z + yb.z, ya.w + yb.w);
                        const float y0 = -(((fb & 1) ? y.y : y.x) + __shfl_xor_sync(0xffffffffu, (fb & 1) ? y.x : y.y, 8));
                        const float y1 = -(((fb & 1) ? y.w : y.z) + __shfl_xor_sync(0xffffffffu, (fb & 1) ? y.z : y.w, 8));
                        const uint32_t ov = pack_bf16(fmaf(y0, sig, ln0), fmaf(y1, sig, ln1));
                        if (b == NB - 1) {
                            asm volatile("st.global.u16 [%0], %1;" :: "l"(out), "h"((unsigned short)(ov & 0xffffu)) : "memory");
                            asm volatile("st.global.u16 [%0], %1;" :: "l"(out + 8), "h"((unsigned short)(ov >> 16)) : "memory");
                        }
                        CK(11, 0);
                        if (lane == 0) TS2(13);
                    }
                }
            }
            if (is_f(cta) && ffn) {
                const int ks = (2 * fi + fw) % 12;
                const int far = near_side(sb) ^ 1;
                uint32_t* dst = &g_st.ax[ks >> 2].w[(~b & 1) * 2 + far][(fi / 6) * 128 + (ks & 3) * 32 + fb * 8 + (fg & 1) * 4 + ((fg >> 1) ^ (ks & 1))];
                uint32_t* dst2 = dst + (far ? -1024 : 1024);
                uint32_t part = sb + SM_RED + fw * 2560 + fb * 128 + ((fg + (fb & 2)) & 7) * 16;
                uint32_t psum = sb + SM_RED + fw * 2560 + 4 * 128 + ((fg + 4) & 7) * 16;
                pin(dst); pin(part); pin(psum);
                asm volatile("bar.sync 4, 320;" ::: "memory");
                CK(6, lds32(part));
                const float4 d = sum4x4(part, 640), cs = sum4x4(psum, 640);
                const float2 mo = lds64f(sb + SM_RED + 5120 + fb * 8);
                nmean = mo.x; rden = mo.y;
                const float g0 = fmaf(nmean, cs.x, -d.x), g1 = fmaf(nmean, cs.y, -d.y), ke = rden * -1.4426950408889634f, r2 = rden * rden;
                const float p0 = g0 * fmaf(-nmean, cs.z, d.z) * r2, p1 = g1 * fmaf(-nmean, cs.w, d.w) * r2;
                const uint32_t av = nonzero(pack_bf16(p0 * rcp_approx(1.0f + ex2_approx(g0 * ke)), p1 * rcp_approx(1.0f + ex2_approx(g1 * ke))));
                st_relaxed(dst, av);
                st_relaxed(dst2, av);
                CK(7, 0);
            }
        }
        warm.done(sb + SM_MISC);
        if (cta == 0 && tid == (NAUX + NWORK) * 32) { g_work[0] = 0; g_work[32] = 0; g_cnt_z[0] = 0; }
        return;
    }
    if (warp >= NAUX) {
        const int wk = warp - NAUX;
        const uint32_t bar = sb + BAR_KV + wk * 8;
        const uint32_t buf = sb + SM_KV + wk * TILE_BYTES;
        uint64_t pol;
        asm volatile("createpolicy.fractional.L2::evict_first.b64 %0, 1.0;" : "=l"(pol));
        const int nstatic = NWORK * grid;
        constexpr int POOL0 = NUNITS - NPOOL;
        int uk = wk * grid + cta;
        spin_ns(K0_DELAY_NS);
        request_tile(buf, &p.k, uk, bar, pol);
        if (wk == 0) {
            spin_ns(WO_AT_NS - K0_DELAY_NS);
#pragma unroll 1
            for (int i = 0; i < (cta < NE_CTAS ? 5 : 4); i++)
                request_box(sb + SM_A + i * 12288, &p.wo, cta < NE_CTAS ? (cta & 3) * 160 + i * 32 : (cta - NE_CTAS) * 32,
                            (cta < NE_CTAS ? cta >> 2 : 28 + i) * DH, sb + BAR_WO, i ? 0 : cta < NE_CTAS ? 61440 : 49152);
        }
        uint32_t koff[3], voff[3];
        {
            const int r = lane & 7, hf = (lane >> 3) & 1;
            const int kkey = hf ? 8 + (r ^ 1) : r;
            const int vh = lane >> 4;
            const int vkey = ((r & 1) ? 8 : 0) + (vh ? (r ^ 1) : r);
#pragma unroll
            for (int b = 0; b < 3; b++) {
                const int rk = 3 * kkey + b, rv = 3 * vkey + b;
                koff[b] = buf + rk * 128 + (((lane >> 4) ^ (rk & 7)) << 4);
                voff[b] = buf + rv * 128 + ((hf ^ (rv & 7)) << 4);
            }
        }
        uint32_t phase = 0, kbar = bar;
        uint4 qf[6];
        auto load_q = [&](int u) {
            const uint32_t* q = &g_early[u / UPB].q[j * 4];
#pragma unroll
            for (int i = 0; i < 6; i++) qf[i] = ld_relaxed_v4(q + i * 16);
        };
        load_q(uk);
        int uq[LAG];
        uint32_t sq[LAG];
#pragma unroll
        for (int i = 0; i < LAG; i++) { uq[i] = -1; sq[i] = 0; }
        uint4 mv = make_uint4(0u, 0u, 0u, 0u);
        float freed = UPB;
        while (true) {
            const int uv = uq[0];
            uint32_t sv = sq[0];
#pragma unroll
            for (int i = 0; i + 1 < LAG; i++) { uq[i] = uq[i + 1]; sq[i] = sq[i + 1]; }
            uq[LAG - 1] = uk;
            if (uk < NUNITS) {
                PH(7);
#pragma unroll 1
                for (int it = 0; it < SPIN_MAX; it++) {
                    uint32_t lo = 0xffffffffu;
#pragma unroll
                    for (int i = 0; i < 6; i++) lo = min(min(lo, min(qf[i].x, qf[i].y)), min(qf[i].z, qf[i].w));
                    if (all(lo != 0)) break;
                    __nanosleep(250);
                    load_q(uk);
                }
                mbar_wait(kbar, phase); phase ^= 1;
                PH(0); ARR();
                TSI(0, 16); TSI(1, 18);
                float acc[2][4][4] = {};
#pragma unroll
                for (int ks = 0; ks < 12; ks++) {
                    const uint4 qq = qf[ks >> 1];
                    const uint32_t b0 = (ks & 1) ? qq.z : qq.x, b1 = (ks & 1) ? qq.w : qq.y;
#pragma unroll
                    for (int mt = 0; mt < 4; mt++) {
                        uint32_t a[4];
                        ldsm4(a, (koff[ks >> 2] ^ ((ks & 3) << 5)) + mt * 6144);
                        mma16816(acc[ks & 1][mt], a, b0, b1);
                    }
                }
                PH(1);
                TSI(0, 17); TSI(1, 19);
                if (uv < NUNITS && kbar == bar) request_tile(buf, uv >= 0 ? &p.v : &p.k, uv >= 0 ? uv : uk + (wk < NSPARE ? 2 : 1) * nstatic, bar, pol);
                const float sa = sel4(j, acc[0][0][0], acc[0][1][0], acc[0][2][0], acc[0][3][0]) + sel4(j, acc[1][0][0], acc[1][1][0], acc[1][2][0], acc[1][3][0]);
                const float sc = sel4(j, acc[0][0][2], acc[0][1][2], acc[0][2][2], acc[0][3][2]) + sel4(j, acc[1][0][2], acc[1][1][2], acc[1][2][2], acc[1][3][2]);
                const uint32_t raw = pack_bf16(sa, sc);
                const float scale = -0.07216878364870322f;
                const uint32_t sk = pack_bf16(lo_f(raw) * scale, hi_f(raw) * scale);
                sq[LAG - 1] = sk;
                if (uk >= POOL0) st_relaxed(&g_st.score[uk - POOL0][lane], sk ? sk : 0x80008000u);
                int a = (int)(sk << 16), b = (int)(sk & 0xffff0000u);
                a ^= (a >> 31) & 0x7fff0000; b ^= (b >> 31) & 0x7fff0000;
                const int mx = __reduce_max_sync(0xffffffffu, max(a, b));
                if (lane == 0) st_relaxed(&g_early[uk / UPB].umax[uk % UPB], (uint32_t)mx | 1u);
            }
            if (uv < 0) {
                if (wk < NSPARE) {
                    const int d = uk < nstatic ? SM_W - SM_KV : SM_KV - SM_W;
#pragma unroll
                    for (int b = 0; b < 3; b++) koff[b] += d;
                    kbar = uk < nstatic ? bar + NWORK * 8 : bar;
                    phase = uk >= nstatic;
                }
                uk += nstatic;
                load_q(uk);
                continue;
            }
            if (uv >= NUNITS) break;
            const int bh = uv / UPB;
#pragma unroll 1
            for (int it = 0; it < SPIN_MAX; it++) {
                if (all((mv.x & mv.y & mv.z & mv.w & 1u) && (uv < POOL0 || sv != 0) && freed == UPB)) break;
                mv = ld_relaxed_v4(&g_early[bh].umax[lane * 4]);
                if (bh >= RING && bh < RED0) freed = __uint_as_float(ld_relaxed_u32(&g_st.oacc[oidx(bh - RING, (lane & 7) * 8)].w));
                if (uv >= POOL0) sv = ld_relaxed_u32(&g_st.score[uv - POOL0][lane]);
            }
            PH(2);
            int un = NUNITS, vn = 0;
            draw(un, g_work, uk < NUNITS && lane == 0);
            uint32_t tdraw;
            asm volatile("mov.u32 %0, %%globaltimer_lo;" : "=r"(tdraw));
            draw(vn, g_work + 32, uq[0] >= POOL0 && lane == 0);
            int mx = __reduce_max_sync(0xffffffffu, max(max((int)mv.x, (int)mv.y), max((int)mv.z, (int)mv.w))) & 0xffff0000;
            mx ^= (mx >> 31) & 0x7fff0000;
            const float m = __int_as_float(mx);
            const float l2e = 1.4426950408889634f;
            const uint32_t pp = pack_bf16(exp2f((lo_f(sv) - m) * l2e), exp2f((hi_f(sv) - m) * l2e));
            uint32_t pb[8];
#pragma unroll
            for (int t = 0; t < 4; t++) {
                pb[2 * t] = __shfl_sync(0xffffffffu, pp, 8 * j + t);
                pb[2 * t + 1] = __shfl_sync(0xffffffffu, pp, 8 * j + 4 + t);
            }
            float lacc[4] = {};
            const uint32_t ones[4] = {0x3f803f80u, 0x3f803f80u, 0x3f803f80u, 0x3f803f80u};
#pragma unroll
            for (int t = 0; t < 4; t++) mma16816(lacc, ones, pb[2 * t], pb[2 * t + 1]);
            if (uv < nstatic) {
                asm volatile("bar.sync 2, %0;" :: "n"((NWORK + 2) * 32) : "memory");
                TSW(3);
            }
            const int grp = 16 * j + 4 * (g & 1) + (g >> 1);
            uint32_t mode = (bh >= RED0) + (bh >= NBH - 4);
            float tag = mode ? 1.f : (float)(bh + 1), tag2 = fmaf(__uint_as_float(voff[0]), 0.f, tag);
            void* dst = mode == 0 ? (void*)&g_ring[bh % RING][uv % UPB][grp] :
                        mode == 1 ? (void*)&g_st.oacc[oidx(bh, grp)] : (void*)&g_st.ox[uv % OREP].w[0][oidx(bh & 3, grp) * 4];
            if (mode == 2 && lane < 2) red_f2(reinterpret_cast<float*>(&g_st.lx.w[lane][(bh & 3) * 256]), lacc[0], 1.f);
            un = __shfl_sync(0xffffffffu, un, 0) + (LAG + 1) * nstatic;
            vn = __shfl_sync(0xffffffffu, vn, 0);
            if (uq[0] >= POOL0) uq[0] = POOL0 + vn;
            if (vn == FW_TICKET && lane == 0) st_relaxed(g_st.fw_time, tdraw | 1u);
            if (uq[0] < NUNITS && un >= NUNITS) {
                mv = ld_relaxed_v4(&g_early[uq[0] / UPB].umax[lane * 4]);
                if (uq[0] < RED0 * UPB) freed = 0.f;
                if (uq[0] >= POOL0) sq[0] = ld_relaxed_u32(&g_st.score[uq[0] - POOL0][lane]);
            }
            pin(dst); pin(mode); pin(tag); pin(tag2); pin(voff[0]); pin(voff[1]); pin(voff[2]);
            PH(3);
            mbar_wait(bar, phase); phase ^= 1;
            PH(4); ARR(); CK(12, lds32(buf));
            float acc[12][4] = {};
#pragma unroll
            for (int t = 0; t < 4; t++) {
#pragma unroll
                for (int mt = 0; mt < 12; mt++) {
                    uint32_t a[4];
                    ldsm4t(a, (voff[mt >> 2] ^ ((mt & 3) << 5)) + t * 6144);
                    mma16816(acc[mt], a, pb[2 * t], pb[2 * t + 1]);
                }
            }
            PH(5);
            if (lane == 0) PROG(un);
            if (un < NUNITS || uq[0] < NUNITS) request_tile(buf, un < NUNITS ? &p.k : &p.v, un < NUNITS ? un : uq[0], bar, pol);
            if (un < NUNITS || uq[0] < NUNITS) CK(11, 0);
            float o[6];
#pragma unroll
            for (int e = 0; e < 6; e++) {
                const int q = e % 3, c = (e / 3) * 2;
                o[e] = sel4(j, acc[q][c], acc[3 + q][c], acc[6 + q][c], acc[9 + q][c]);
            }
            put_groups(dst, mode, o, tag, tag2);
            CK(13, 0);
            if (un < NUNITS) load_q(un);
            if (lane == 0) red_f2(&g_st.lsum[bh][0].x, lacc[0], 1.f);
            PH(6);
            if (uq[0] >= NUNITS && un >= NUNITS) break;
            uk = un;
            if (uq[0] < NUNITS && un < NUNITS) {
                const int nb = uq[0] / UPB;
                mv = ld_relaxed_v4(&g_early[nb].umax[lane * 4]);
                freed = nb >= RING && nb < RED0 ? __uint_as_float(ld_relaxed_u32(&g_st.oacc[oidx(nb - RING, (lane & 7) * 8)].w)) : UPB;
                if (uq[0] >= POOL0) sq[0] = ld_relaxed_u32(&g_st.score[uq[0] - POOL0][lane]);
            }
        }
        TSW(4 + wk);
        return;
    }

    __nv_bfloat16* xs = reinterpret_cast<__nv_bfloat16*>(smem + SM_X);
    float* red = reinterpret_cast<float*>(smem + SM_RED);
    const int frow = (lane & 7) + ((lane >> 4) << 3), fcol = (lane >> 3) & 1;
    const uint32_t f64b = sb + (frow * 4 + (fcol ^ ((frow >> 1) & 3))) * 16;
    if (cta < NQ_CTAS) {
        uint2 xr[5];
        if (warp < NB) {
#pragma unroll
            for (int i = 0; i < 5; i++) xr[i] = *reinterpret_cast<const uint2*>(p.x + warp * DM + i * 128 + lane * 4);
        }
        TS(26);
        if (warp < NB) {
            float v[20];
#pragma unroll
            for (int i = 0; i < 5; i++) {
                v[4 * i] = lo_f(xr[i].x); v[4 * i + 1] = hi_f(xr[i].x); v[4 * i + 2] = lo_f(xr[i].y); v[4 * i + 3] = hi_f(xr[i].y);
            }
            layernorm20(v);
#pragma unroll
            for (int i = 0; i < 5; i++)
                *reinterpret_cast<uint2*>(xs + warp * XPITCH + i * 128 + lane * 4) =
                    make_uint2(pack_bf16(v[4 * i], v[4 * i + 1]), pack_bf16(v[4 * i + 2], v[4 * i + 3]));
        }
        TS(27);
        aux_sync();
        mbar_wait(sb + BAR_WQ, 0);
        TS(1);
        const uint32_t xfrag = sb + SM_X + ((g & 3) * XPITCH + 2 * j) * 2;
        float acc[3][4] = {};
#pragma unroll
        for (int s = 0; s < 5; s++) {
            const int ks = warp * 5 + s;
            const uint32_t b0 = lds32(xfrag + ks * 32), b1 = lds32(xfrag + ks * 32 + 16);
            const int row = ks * 16 + frow;
#pragma unroll
            for (int mt = 0; mt < 3; mt++) {
                uint32_t a[4];
                ldsm4t(a, sb + SM_W + (row * 6 + 2 * mt + fcol) * 16);
                mma16816(acc[mt], a, b0, b1);
            }
        }
        if (j < 2) {
#pragma unroll
            for (int mt = 0; mt < 3; mt++) {
                *reinterpret_cast<float2*>(red + (warp * 48 + mt * 16 + g) * 4 + 2 * j) = make_float2(acc[mt][0], acc[mt][1]);
                *reinterpret_cast<float2*>(red + (warp * 48 + mt * 16 + 8 + g) * 4 + 2 * j) = make_float2(acc[mt][2], acc[mt][3]);
            }
        }
        aux_sync();
        if (tid < 96) {
            const int b = tid & 3, cp = tid >> 2;
            float s0 = 0.f, s1 = 0.f;
#pragma unroll
            for (int w = 0; w < 8; w++) { s0 += red[(w * 48 + 2 * cp) * 4 + b]; s1 += red[(w * 48 + 2 * cp + 1) * 4 + b]; }
            const int h = cta >> 2, d = (cta & 3) * 48 + 2 * cp;
            const int ch = d >> 3, jj = (d & 7) >> 1;
            st_relaxed(&g_early[b * NH + h].q[(ch >> 2) * 16 + jj * 4 + (ch & 3)], pack_neg(s0, s1));
        }
        TS(28);
    }
    if (warp >= 4 && warp < 4 + NSPARE) {
        uint64_t pol;
        asm volatile("createpolicy.fractional.L2::evict_first.b64 %0, 1.0;" : "=l"(pol));
        if (cta >= NQ_CTAS) spin_ns(WO_AT_NS);
        asm volatile("fence.proxy.async.shared::cta;" ::: "memory");
        request_tile(sb + SM_W + (warp - 4) * TILE_BYTES, &p.k, (NWORK + warp - 4) * grid + cta, sb + BAR_KV + (NWORK + warp - 4) * 8, pol);
    }
    fin_sync<3>();
    mbar_wait(sb + BAR_WO, 0);
    TS(7);
    uint32_t part = sb + SM_RED + (warp * 32 + 8 * j + g) * 4;

#pragma unroll 1
    for (int b = 0; b < NB; b++) {
        if (cta >= NE_CTAS) {
            uint32_t a[6][2][4];
#pragma unroll
            for (int s = 0; s < 6; s++) {
#pragma unroll
                for (int mt = 0; mt < 2; mt++) ldsm4t(a[s][mt], (f64b ^ (mt * 32)) + SM_A + (warp * 6 + s) * 1024);
            }
            const int bh = b * NH + 28 + (warp >> 1);
            const int side = near_side(sb) ^ 1;
            const void* osrc[OREP];
#pragma unroll
            for (int c = 0; c < OREP; c++)
                osrc[c] = b == NB - 1 ? (const void*)&g_st.ox[c].w[side][oidx(bh & 3, (warp & 1) * 32 + lane) * 4] : &g_st.oacc[oidx(bh, (warp & 1) * 32 + lane)];
            const void* lsrc = b == NB - 1 ? (const void*)&g_st.lx.w[side][(bh & 3) * 256] : g_st.lsum[bh];
            wait_row_o(bh, 1);
            const float rl = rcp_approx(wait_sum(lsrc, UPB)) * (b == NB - 1 ? 1.f : 1.f / OREP), full = b == NB - 1 ? UPB : UPB * OREP;
            float4 ov;
            float px, py, pz;
            Warm warm;
#pragma unroll 1
            for (int it = 0; it < SPIN_MAX; it++) {
                wait_slot<PH_O>();
                float4 oc[OREP];
#pragma unroll
                for (int c = 0; c < OREP; c++) oc[c] = ld_relaxed_f4(osrc[c]);
                warm();
                ov = oc[0];
#pragma unroll
                for (int c = 1; c < OREP; c++) { ov.x += oc[c].x; ov.y += oc[c].y; ov.z += oc[c].z; ov.w += oc[c].w; }
                ov.x *= rl; ov.y *= rl; ov.z *= rl;
                px = __shfl_xor_sync(0xffffffffu, ov.x, 4); py = __shfl_xor_sync(0xffffffffu, ov.y, 4); pz = __shfl_xor_sync(0xffffffffu, ov.z, 4);
                if (all(ov.w == full)) break;
            }
            CK(0, __float_as_uint(ov.x));
            if (ov.x != 1.2345f && warp == 7) TSW(14);
            const uint32_t w[3] = {pack_bf16(ov.x, px), pack_bf16(ov.y, py), pack_bf16(ov.z, pz)};
            float acc[2][2][4] = {};
#pragma unroll
            for (int s = 0; s < 6; s++) {
                const uint32_t b0 = __shfl_sync(0xffffffffu, w[s % 3], (s / 3) * 16 + j);
                const uint32_t b1 = __shfl_sync(0xffffffffu, w[s % 3], (s / 3) * 16 + 8 + j);
#pragma unroll
                for (int mt = 0; mt < 2; mt++) mma16816(acc[mt][s & 1], a[s][mt], b0, b1);
            }
            sts32f(part, sel4(j, acc[0][0][0] + acc[0][1][0], acc[0][0][2] + acc[0][1][2], acc[1][0][0] + acc[1][1][0], acc[1][0][2] + acc[1][1][2]));
            CK(1, 0);
            fin_arrive<4>();
            warm.done(sb + SM_MISC);
            fin_sync<5>();
            if (cta < NE_CTAS + 4 && tid < 56) reinterpret_cast<uint4*>(&g_early[b * NH + 28 + cta - NE_CTAS])[tid] = make_uint4(0u, 0u, 0u, 0u);
        } else {
            const int bh = b * NH + (cta >> 2);
            if (warp == 0) wait_row_o(bh, UPB);
            aux_sync();
            if (warp < 5) {
                uint32_t ob[12][2];
                load_o<4>(ob, bh, 0, j);
                float acc[2][2][4] = {};
#pragma unroll
                for (int ks = 0; ks < 12; ks++) {
#pragma unroll
                    for (int mt = 0; mt < 2; mt++) {
                        uint32_t a[4];
                        ldsm4t(a, (f64b ^ (mt * 32)) + SM_A + warp * 12288 + ks * 1024);
                        mma16816(acc[mt][ks & 1], a, ob[ks][0], ob[ks][1]);
                    }
                }
                red_f2(&g_st.attn[b][(cta & 3) * 160 + warp * 32 + 8 * j + g].x,
                       sel4(j, acc[0][0][0] + acc[0][1][0], acc[0][0][2] + acc[0][1][2], acc[1][0][0] + acc[1][1][0], acc[1][0][2] + acc[1][1][2]), 1.f);
                TS(8);
            } else if (warp > 5 && (cta & 3) == 0 && tid - 192 < 56) {
                reinterpret_cast<uint4*>(&g_early[bh])[tid - 192] = make_uint4(0u, 0u, 0u, 0u);
            }
        }
        if (b < NB - 2) continue;

        if (is_f(cta)) {
            uint32_t ga[10][2][4];
            uint4 hv[5] = {};
            const uint32_t hfrag = sb + SM_X + min(g, 4) * HPITCH + ((warp >> 1) * 80 + 4 * j) * 4;
#pragma unroll
            for (int s = 0; s < 5; s++) lds128_if(hv[s], hfrag + s * 64, b == NB - 1);
            if (b == NB - 1) mbar_wait(sb + BAR_FW + warp * 8, 0);
            if (warp == 7) TSW(10);
            CK(12, lds32(sb + SM_W));
#pragma unroll
            for (int s = 0; s < 10; s++) {
#pragma unroll
                for (int mt = 0; mt < 2; mt++) ldsm4t(ga[s][mt], (f64b ^ (mt * 32)) + SM_W + (warp * 10 + s) * 1024);
            }
            const uint32_t gpart = sb + SM_RED + (warp >> 1) * 640 + j * 256 + ((g + 2 * j) & 7) * 16 + (warp & 1) * 8;
            mbar_wait(sb + BAR_H, b & 1);
#pragma unroll
            for (int s = 0; s < 5; s++) lds128_if(hv[s], hfrag + s * 64, g == b);
            CK(4, hv[0].x);
            float acc[2][2][4] = {};
#pragma unroll
            for (int s = 0; s < 10; s++) {
#pragma unroll
                for (int mt = 0; mt < 2; mt++)
                    mma16816(acc[mt][s & 1], ga[s][mt], (s & 1) ? hv[s >> 1].z : hv[s >> 1].x, (s & 1) ? hv[s >> 1].w : hv[s >> 1].y);
            }
#pragma unroll
            for (int mt = 0; mt < 2; mt++) {
                if (j < 3) sts64f(gpart + mt * 2560, acc[mt][0][0] + acc[mt][1][0], acc[mt][0][2] + acc[mt][1][2]);
                if (j < 2) sts64f(gpart + mt * 2560 + 128, acc[mt][0][1] + acc[mt][1][1], acc[mt][0][3] + acc[mt][1][3]);
            }
            CK(5, 0);
            asm volatile("bar.arrive 4, 320;" ::: "memory");
        } else if (is_g(cta)) {
            const uint32_t* asrc = &g_st.ax[0].w[(~b & 1) * 2 + near_side(sb)][warp * 128 + ((g >> 2) * 2 + (j >> 1)) * 32 + (g & 3) * 8 + (j & 1) * 4];
            const uint32_t ypart = sb + SM_RED2 + warp * 512 + j * 128 + ((g + 2 * j) & 7) * 16;
            uint32_t wb[12][4];
            if (b == NB - 1) mbar_wait(sb + BAR_FW + warp * 8, 0);
            if (warp == 7) TSW(11);
            CK(13, lds32(sb + SM_W));
            {
                const int jj = (lane & 7) >> 1, q = jj >> 1, hi = lane >> 4;
                const uint32_t base = sb + SM_W + warp * 6144 + q * 512 + ((hi ^ q) * 4 + (jj & 1) * 2 + (lane & 1)) * 32 + ((fcol ^ hi ^ q) << 4);
#pragma unroll
                for (int s = 0; s < 12; s++) ldsm4t(wb[s], base + (s >> 2) * 2048 + (s & 1) * 1024 + (s & 2) * 128);
            }
            mbar_wait(sb + BAR_H, b & 1);
            uint4 va[3];
            Warm warm;
#pragma unroll 1
            for (int it = 0; it < SPIN_MAX; it++) {
                uint32_t lo = 0xffffffffu;
#pragma unroll
                for (int i = 0; i < 3; i++) va[i] = ld_relaxed_v4(asrc + i * 4096);
                warm();
#pragma unroll
                for (int i = 0; i < 3; i++) lo = min(min(lo, min(va[i].x, va[i].y)), min(va[i].z, va[i].w));
                if (all(lo != 0)) break;
            }
            CK(8, va[0].x);
            if (va[0].x != 0x12345 && warp == 7) TSW(15);
            float acc[6][4] = {};
#pragma unroll
            for (int s = 0; s < 12; s++) {
                const uint4 v = va[s >> 2];
                mma16816(acc[s % 6], wb[s], (s & 2) ? v.z : v.x, (s & 2) ? v.w : v.y);
            }
            float y[4];
#pragma unroll
            for (int e = 0; e < 4; e++) y[e] = j < 2 ? (acc[0][e] + acc[2][e]) + acc[4][e] : (acc[1][e] + acc[3][e]) + acc[5][e];
            sts128f(ypart, y[0], y[1], y[2], y[3]);
            CK(9, 0);
            fin_arrive<6>();
            warm.done(sb + SM_MISC);
        }
    }
}

typedef CUresult (*EncodeFn)(CUtensorMap*, CUtensorMapDataType, cuuint32_t, void*, const cuuint64_t*, const cuuint64_t*,
                             const cuuint32_t*, const cuuint32_t*, CUtensorMapInterleave, CUtensorMapSwizzle,
                             CUtensorMapL2promotion, CUtensorMapFloatOOBfill);

CUtensorMap make_map(EncodeFn enc, void* ptr, uint64_t cols, uint64_t rows, uint32_t bcols, uint32_t brows,
                     CUtensorMapSwizzle sw, CUtensorMapL2promotion promo) {
    CUtensorMap m;
    const cuuint64_t dims[2] = {cols, rows};
    const cuuint64_t strides[1] = {cols * 2};
    const cuuint32_t box[2] = {bcols, brows};
    const cuuint32_t es[2] = {1, 1};
    enc(&m, CU_TENSOR_MAP_DATA_TYPE_BFLOAT16, 2, ptr, dims, strides, box, es, CU_TENSOR_MAP_INTERLEAVE_NONE, sw, promo,
        CU_TENSOR_MAP_FLOAT_OOB_FILL_NONE);
    return m;
}

}

extern "C" void kernel_launch(void* const* d_in, const int* in_sizes, int n_in, void* d_out, int out_size) {
    (void)in_sizes; (void)n_in; (void)out_size;
    static EncodeFn enc = nullptr;
    static int sms = 0;
    if (!enc) {
        cudaDriverEntryPointQueryResult qr;
        cudaGetDriverEntryPoint("cuTensorMapEncodeTiled", (void**)&enc, cudaEnableDefault, &qr);
        int dev = 0;
        cudaGetDevice(&dev);
        cudaDeviceGetAttribute(&sms, cudaDevAttrMultiProcessorCount, dev);
        cudaFuncSetAttribute(fused_decode_kernel, cudaFuncAttributeMaxDynamicSharedMemorySize, SM_TOTAL);
    }
    if (sms < NCTAS) return;
    const CUtensorMapL2promotion WPROMO = CU_TENSOR_MAP_L2_PROMOTION_L2_128B;
    Params p;
    p.k = make_map(enc, d_in[1], 64, (uint64_t)NBH * SK * 3, 64, TILE_ROWS, CU_TENSOR_MAP_SWIZZLE_128B, CU_TENSOR_MAP_L2_PROMOTION_NONE);
    p.v = make_map(enc, d_in[2], 64, (uint64_t)NBH * SK * 3, 64, TILE_ROWS, CU_TENSOR_MAP_SWIZZLE_128B, CU_TENSOR_MAP_L2_PROMOTION_NONE);
    p.wq = make_map(enc, d_in[3], NH * DH, DM, 48, 160, CU_TENSOR_MAP_SWIZZLE_NONE, WPROMO);
    p.wo = make_map(enc, d_in[4], DM, NH * DH, 32, DH, CU_TENSOR_MAP_SWIZZLE_64B, WPROMO);
    p.wg = make_map(enc, d_in[7], FF, DM, 32, 160, CU_TENSOR_MAP_SWIZZLE_64B, WPROMO);
    p.wu = make_map(enc, d_in[8], FF, DM, 32, 160, CU_TENSOR_MAP_SWIZZLE_64B, WPROMO);
    {
        const cuuint64_t dims[4] = {DM, 2, 8, FF / 16}, strides[3] = {8 * DM * 2, DM * 2, 16 * DM * 2};
        const cuuint32_t box[4] = {16, 2, 8, 12}, es[4] = {1, 1, 1, 1};
        enc(&p.wd, CU_TENSOR_MAP_DATA_TYPE_BFLOAT16, 4, d_in[9], dims, strides, box, es, CU_TENSOR_MAP_INTERLEAVE_NONE,
            CU_TENSOR_MAP_SWIZZLE_32B, WPROMO, CU_TENSOR_MAP_FLOAT_OOB_FILL_NONE);
    }
    p.x = (const __nv_bfloat16*)d_in[0];
    p.wr = (const __nv_bfloat16*)d_in[6];
    p.out = (__nv_bfloat16*)d_out;
    fused_decode_kernel<<<NCTAS, NTHREADS, SM_TOTAL, cudaStreamPerThread>>>(p);
}
```

```cpp
#include <cuda_runtime.h>
#include <cuda_bf16.h>
#include <cuda.h>
#include <stdint.h>

namespace {

constexpr int NB = 4, NH = 32, SK = 8192, DH = 192, DM = 640, FF = 1536;
constexpr int NBH = NB * NH;
constexpr int TILE = 64;
constexpr int UPB = SK / TILE;
constexpr int NUNITS = NBH * UPB;
constexpr int TILE_BYTES = TILE * DH * 2;
constexpr int TILE_ROWS = TILE * 3;
constexpr int NCTAS = 132;
constexpr int NQ_CTAS = 128;
constexpr int NE_CTAS = 112;
__host__ __device__ constexpr bool is_f(int cta) { return cta < NE_CTAS && cta % 14 < 11 && !(cta & 1); }
__host__ __device__ constexpr bool is_g(int cta) { return cta < NE_CTAS && cta % 14 < 11 && (cta & 1); }
__host__ __device__ constexpr int ffn_slice(int cta) { return cta / 14 * ((cta & 1) ? 5 : 6) + cta % 14 / 2; }

#define NWORK 2
#define LAG 2
#define NPOOL 768
#define RED0 116
#define RING 11
#define OREP 3
#define K0_AT_NS 1150
#define WO_AT_NS (K0_AT_NS + 2000)
#define K1_AT_NS (K0_AT_NS + 4400)
constexpr int KSWEEP_NS = 2000, WO_STEP_NS = 75;
#define FW_TICKET (NPOOL + 32)
#define FW_AT_NS 2090
#define FW_GAP 280
#define FW_MID 2000
#define FW_GAP2 200
#define HGATE_NS 700
#define SLOT_TICKS 8
#define SLOT_OPEN 3
#define PH_O 0
#define PH_H 1
#define PH_M 4
#define NPROBE 24
constexpr int NAUX = 8;
constexpr int NTHREADS = (NAUX + NWORK + 2) * 32;
constexpr int SPIN_MAX = 1 << 22;

constexpr int SM_KV = 0;
constexpr int SM_A = SM_KV + NWORK * TILE_BYTES;
constexpr int SM_W = SM_A + 61440;
constexpr int SM_X = SM_W + 81920;
constexpr int XPITCH = 648;
constexpr int HPITCH = 1344;
constexpr int SM_RED = SM_X + 5 * HPITCH + 64;
constexpr int SM_RED2 = SM_RED + 8 * 48 * 4 * 4;
constexpr int SM_MISC = SM_RED2 + 4096;
constexpr int BAR_WQ = SM_MISC, SM_SCRAP = SM_MISC + 32, BAR_WO = SM_MISC + 40, SM_SIDE = SM_MISC + 48, BAR_H = SM_MISC + 56, BAR_FW = SM_MISC + 64;
constexpr int BAR_KV = BAR_FW + 64;
constexpr int SM_TOTAL = BAR_KV + NWORK * 8;
static_assert(SM_W % 1024 == 0 && NB * XPITCH * 2 <= 4 * HPITCH && SM_RED % 128 == 0, "smem layout");

struct Params {
    CUtensorMap k, v;
    CUtensorMap wq;
    CUtensorMap wo;
    CUtensorMap wg, wu;
    CUtensorMap wd;
    const __nv_bfloat16 *x, *wr;
    __nv_bfloat16* out;
};

struct Early {
    uint32_t q[4][4][8];
    uint32_t umax[UPB];
};
struct Twin { uint32_t w[4][1024]; };
constexpr int PROBE = 1024 - 32;
#define LSTRIDE 16
struct State {
    Twin ax[3];
    Twin hx;
    Twin ox[(OREP + 1) / 2];
    Twin lx;
    float4 oacc[NBH * 64];
    float2 attn[NB][DM];
    uint32_t fw_time[32];
    float2 lsum[NBH][LSTRIDE];
    uint32_t score[NPOOL][32];
};
__host__ __device__ constexpr int oidx(int row, int grp) {
    return (row >> 2) * 256 + ((row & 1) * 2 + (grp >> 5)) * 64 + (row & 2) * 16 + (grp & 31);
}
constexpr int STATE_V4 = ((sizeof(State) / 32 + NQ_CTAS - 1) / NQ_CTAS) * 2;
static_assert(sizeof(State) % 32 == 0, "State is cleared in whole sectors");
static_assert(sizeof(Early) == 64 * 16, "an Early entry is cleared by 64 threads");
struct Scratch {
    State st;
    unsigned work[64];
    unsigned cnt_z[32];
    Early early[NBH];
    alignas(4096) float4 ring[RING][UPB][64];
};
constexpr size_t PAGE = 2u << 20;
static_assert(sizeof(Scratch) <= PAGE, "scratch must fit one page");
__device__ __align__(128) unsigned char g_raw[2 * PAGE];
__device__ __forceinline__ Scratch* scratch() {
    return reinterpret_cast<Scratch*>((reinterpret_cast<uintptr_t>(g_raw) + PAGE - 1) & ~(uintptr_t)(PAGE - 1));
}
#define g_early scratch()->early
#define g_st scratch()->st
#define g_ring scratch()->ring
#define g_cnt_z scratch()->cnt_z
#define g_work scratch()->work
#define ALL_LOADERS 0
#define TS(i)
#define TSW(i)
#define TS2(i)
#define TSI(n, i)
#define PH(i)
#define CK(i, dep)
#define ARR()
#define PROG(u)

__device__ __forceinline__ uint32_t s2u(const void* p) { return (uint32_t)__cvta_generic_to_shared(p); }
__device__ __forceinline__ void mbar_init(uint32_t bar, int cnt) {
    asm volatile("mbarrier.init.shared::cta.b64 [%0], %1;" :: "r"(bar), "r"(cnt) : "memory");
}
__device__ __forceinline__ void mbar_wait(uint32_t bar, uint32_t parity) {
    asm volatile("{\n.reg .pred p;\n.reg .u32 n;\nmov.u32 n, 0;\nWAIT_LOOP:\n"
                 "mbarrier.try_wait.parity.shared::cta.b64 p, [%0], %1;\n"
                 "@p bra WAIT_DONE;\nadd.u32 n, n, 1;\nsetp.lt.u32 p, n, %2;\n@p bra WAIT_LOOP;\nWAIT_DONE:\n}"
                 :: "r"(bar), "r"(parity), "n"(SPIN_MAX) : "memory");
}
__device__ __forceinline__ void request_tile(uint32_t dst, const CUtensorMap* tm, int unit, uint32_t bar, uint64_t pol) {
    asm volatile("{\n.reg .pred p;\nelect.sync _|p, 0xffffffff;\n"
                 "@p mbarrier.arrive.expect_tx.shared::cta.b64 _, [%2], %6;\n"
                 "@p cp.async.bulk.tensor.2d.shared::cluster.global.mbarrier::complete_tx::bytes.L2::cache_hint "
                 "[%0], [%1, {%3, %4}], [%2], %5;\n}"
                 :: "r"(dst), "l"(tm), "r"(bar), "r"(0), "r"(unit * TILE_ROWS), "l"(pol), "n"(TILE_BYTES) : "memory");
}
__device__ __forceinline__ void put_groups(void* dst, int mode, const float (&o)[6], float tag, float tag2) {
    asm volatile("{\n.reg .pred s, t;\n.reg .b128 u, v;\n.reg .b64 a, b;\n"
                 "setp.eq.s32 s, %1, 0;\nsetp.ne.s32 t, %1, 2;\n"
                 "@t bra.uni SINGLE;\n"
                 "red.relaxed.gpu.global.add.v4.f32 [%0+4096], {%2,%3,%4,%8};\n"
                 "red.relaxed.gpu.global.add.v4.f32 [%0+4224], {%5,%6,%7,%9};\n"
                 "SINGLE:\n"
                 "@s bra.uni STORE;\n"
                 "red.relaxed.gpu.global.add.v4.f32 [%0], {%2,%3,%4,%8};\n"
                 "red.relaxed.gpu.global.add.v4.f32 [%0+128], {%5,%6,%7,%9};\n"
                 "STORE:\n"
                 "mov.b64 a, {%2, %3};\nmov.b64 b, {%4, %8};\nmov.b128 u, {a, b};\n"
                 "mov.b64 a, {%5, %6};\nmov.b64 b, {%7, %9};\nmov.b128 v, {a, b};\n"
                 "@s st.relaxed.gpu.global.b128 [%0], u;\n@s st.relaxed.gpu.global.b128 [%0+128], v;\n}"
                 :: "l"(dst), "r"(mode), "f"(o[0]), "f"(o[1]), "f"(o[2]), "f"(o[3]), "f"(o[4]), "f"(o[5]), "f"(tag), "f"(tag2) : "memory");
}
__device__ __forceinline__ void request_box(uint32_t dst, const CUtensorMap* tm, int col, int row, uint32_t bar, uint32_t bytes) {
    asm volatile("{\n.reg .pred p, q;\nelect.sync _|p, 0xffffffff;\nsetp.ne.and.u32 q, %5, 0, p;\n"
                 "@q mbarrier.arrive.expect_tx.shared::cta.b64 _, [%2], %5;\n"
                 "@p cp.async.bulk.tensor.2d.shared::cluster.global.mbarrier::complete_tx::bytes [%0], [%1, {%3, %4}], [%2];\n}"
                 :: "r"(dst), "l"(tm), "r"(bar), "r"(col), "r"(row), "r"(bytes) : "memory");
}
__device__ __forceinline__ uint32_t lds32(uint32_t addr) {
    uint32_t v;
    asm volatile("ld.shared.u32 %0, [%1];" : "=r"(v) : "r"(addr) : "memory");
    return v;
}
__device__ __forceinline__ void ldsm4(uint32_t (&r)[4], uint32_t addr) {
    asm volatile("ldmatrix.sync.aligned.m8n8.x4.shared.b16 {%0,%1,%2,%3}, [%4];"
                 : "=r"(r[0]), "=r"(r[1]), "=r"(r[2]), "=r"(r[3]) : "r"(addr) : "memory");
}
__device__ __forceinline__ void ldsm4t(uint32_t (&r)[4], uint32_t addr) {
    asm volatile("ldmatrix.sync.aligned.m8n8.x4.trans.shared.b16 {%0,%1,%2,%3}, [%4];"
                 : "=r"(r[0]), "=r"(r[1]), "=r"(r[2]), "=r"(r[3]) : "r"(addr) : "memory");
}
__device__ __forceinline__ void mma16816(float (&c)[4], const uint32_t (&a)[4], uint32_t b0, uint32_t b1) {
    asm volatile("mma.sync.aligned.m16n8k16.row.col.f32.bf16.bf16.f32 {%0,%1,%2,%3}, {%4,%5,%6,%7}, {%8,%9}, {%0,%1,%2,%3};"
                 : "+f"(c[0]), "+f"(c[1]), "+f"(c[2]), "+f"(c[3])
                 : "r"(a[0]), "r"(a[1]), "r"(a[2]), "r"(a[3]), "r"(b0), "r"(b1));
}
struct Warm {
    float c[4] = {};
    __device__ __forceinline__ void operator()() {
        asm volatile("mma.sync.aligned.m16n8k8.row.col.f32.bf16.bf16.f32 {%0,%1,%2,%3}, {%4,%4}, {%4}, {%0,%1,%2,%3};"
                     : "+f"(c[0]), "+f"(c[1]), "+f"(c[2]), "+f"(c[3]) : "r"(0));
    }
    __device__ __forceinline__ void done(uint32_t scrap) {
        asm volatile("{\n.reg .pred p;\nsetp.gt.f32 p, %1, 0f3f800000;\n@p st.shared.f32 [%0], %1;\n}" :: "r"(scrap), "f"(c[0]) : "memory");
    }
};
__device__ __forceinline__ uint4 ld_relaxed_v4(const void* p) {
    uint4 v;
    asm volatile("ld.relaxed.gpu.global.v4.u32 {%0,%1,%2,%3}, [%4];" : "=r"(v.x), "=r"(v.y), "=r"(v.z), "=r"(v.w) : "l"(p) : "memory");
    return v;
}
__device__ __forceinline__ float4 ld_relaxed_f4(const void* p) {
    float4 v;
    asm volatile("ld.relaxed.gpu.global.v4.f32 {%0,%1,%2,%3}, [%4];" : "=f"(v.x), "=f"(v.y), "=f"(v.z), "=f"(v.w) : "l"(p) : "memory");
    return v;
}
__device__ __forceinline__ float2 ld_relaxed_f2(const void* p) {
    float2 v;
    asm volatile("ld.relaxed.gpu.global.v2.f32 {%0,%1}, [%2];" : "=f"(v.x), "=f"(v.y) : "l"(p) : "memory");
    return v;
}
__device__ __forceinline__ float4 ld_relaxed_b128(const void* p) {
    float4 v;
    asm volatile("{\n.reg .b128 t;\n.reg .b64 a, b;\nld.relaxed.gpu.global.b128 t, [%4];\nmov.b128 {a, b}, t;\n"
                 "mov.b64 {%0, %1}, a;\nmov.b64 {%2, %3}, b;\n}" : "=f"(v.x), "=f"(v.y), "=f"(v.z), "=f"(v.w) : "l"(p) : "memory");
    return v;
}
__device__ __forceinline__ void st_relaxed_b128(void* p, float x, float y, float z, float w) {
    asm volatile("{\n.reg .b128 t;\n.reg .b64 a, b;\nmov.b64 a, {%1, %2};\nmov.b64 b, {%3, %4};\nmov.b128 t, {a, b};\n"
                 "st.relaxed.gpu.global.b128 [%0], t;\n}" :: "l"(p), "f"(x), "f"(y), "f"(z), "f"(w) : "memory");
}
__device__ __forceinline__ unsigned ld_acquire(const unsigned* p) {
    unsigned v;
    asm volatile("ld.acquire.gpu.global.u32 %0, [%1];" : "=r"(v) : "l"(p) : "memory");
    return v;
}
__device__ __forceinline__ void st_relaxed(void* p, uint32_t v) {
    asm volatile("st.relaxed.gpu.global.u32 [%0], %1;" :: "l"(p), "r"(v) : "memory");
}
__device__ __forceinline__ void red_f2(float* p, float a, float b) {
    asm volatile("red.relaxed.gpu.global.add.v2.f32 [%0], {%1,%2};" :: "l"(p), "f"(a), "f"(b) : "memory");
}
__device__ __forceinline__ void draw(int& ticket, unsigned* ctr, bool pred) {
    asm volatile("{\n.reg .pred p;\nsetp.ne.u32 p, %2, 0;\n@p atom.relaxed.gpu.global.inc.u32 %0, [%1], 0x7fffffff;\n}"
                 : "+r"(ticket) : "l"(ctr), "r"((uint32_t)pred) : "memory");
}
__device__ __forceinline__ void red_release(unsigned* p) {
    asm volatile("red.release.gpu.global.add.u32 [%0], 1;" :: "l"(p) : "memory");
}
__device__ __forceinline__ uint32_t ld_relaxed_u32(const void* p) {
    uint32_t v;
    asm volatile("ld.relaxed.gpu.global.u32 %0, [%1];" : "=r"(v) : "l"(p) : "memory");
    return v;
}
__device__ __forceinline__ float rcp_approx(float v) {
    float r;
    asm("rcp.approx.ftz.f32 %0, %1;" : "=f"(r) : "f"(v));
    return r;
}
__device__ __forceinline__ float ex2_approx(float v) {
    float e;
    asm("ex2.approx.ftz.f32 %0, %1;" : "=f"(e) : "f"(v));
    return e;
}
__device__ __forceinline__ float sigmoid_approx(float v) { return rcp_approx(1.0f + ex2_approx(v * -1.4426950408889634f)); }
__device__ __forceinline__ float sqrt_approx(float v) {
    float r;
    asm("sqrt.approx.ftz.f32 %0, %1;" : "=f"(r) : "f"(v));
    return r;
}
__device__ __forceinline__ bool all(bool v) { return __all_sync(0xffffffffu, v); }
__device__ __forceinline__ void wait_count(const unsigned* p, unsigned target) {
#pragma unroll 1
    for (int it = 0; it < SPIN_MAX; it++) {
        if (all(ld_acquire(p) >= target)) break;
        __nanosleep(400);
    }
}
__device__ __forceinline__ float wait_sum(const void* p, float n, int nap = 0) {
    float2 v;
#pragma unroll 1
    for (int it = 0; it < SPIN_MAX; it++) {
        v = ld_relaxed_f2(p);
        if (all(v.y >= n)) break;
        if (all(v.y == 0.f)) __nanosleep(600);
        else if (nap) __nanosleep(nap);
    }
    return v.x;
}
__device__ __forceinline__ void wait_row(int bh, float n) { wait_sum(g_st.lsum[bh], n); }
__device__ __forceinline__ void wait_row_o(int bh, float n) {
    wait_row(bh, n);
    if (bh >= RED0) return;
#pragma unroll 1
    for (int it = 0; it < SPIN_MAX; it++) {
        if (all(__uint_as_float(ld_relaxed_u32(&g_st.oacc[oidx(bh, 0)].w)) == UPB)) break;
        __nanosleep(300);
    }
}
constexpr uint32_t SLOT_K = (uint32_t)(((1ull << 32) + SLOT_TICKS - 1) / SLOT_TICKS);
#define SLOT_ASM(t, n, p, phase, k, open) \
    "mov.u32 " n ", 0;\nSLOT:\nmov.u32 " t ", %%globaltimer_lo;\nadd.u32 " n ", " n ", 1;\nsetp.lt.u32 " p ", " n ", 24;\nshr.u32 " t ", " t ", 5;\n" \
    "mad.lo.u32 " t ", " t ", " k ", " phase ";\nsetp.ge.and.u32 " p ", " t ", " open ", " p ";\n@" p " bra.uni SLOT;\n"
template <int PHASE> __host__ __device__ constexpr uint32_t slot_phase() { return SLOT_K / 2 - PHASE * SLOT_K; }
template <int PHASE> __device__ __forceinline__ void wait_slot() {
    if (PHASE < 0) return;
    asm volatile("{\n.reg .pred p;\n.reg .b32 t, n;\n" SLOT_ASM("t", "n", "p", "%0", "%1", "%2") "}"
                 :: "n"(slot_phase<PHASE>()), "n"(SLOT_K), "n"(SLOT_OPEN * SLOT_K) : "memory");
}
__device__ __forceinline__ void wait_time(uint32_t t) {
#pragma unroll 1
    for (int it = 0; it < SPIN_MAX; it++) {
        uint32_t now;
        asm volatile("mov.u32 %0, %%globaltimer_lo;" : "=r"(now));
        if (all((int)(now - t) >= 0)) break;
    }
}
__device__ __forceinline__ void wait_clock(uint32_t t, Warm& warm) { while (!all((int)(clock() - t) >= 0)) { warm(); } }
__device__ __forceinline__ uint32_t pack_bf16(float lo, float hi) {
    uint32_t r;
    asm("cvt.rn.bf16x2.f32 %0, %1, %2;" : "=r"(r) : "f"(hi), "f"(lo));
    return r;
}
__device__ __forceinline__ float bf16r(float v) { return __uint_as_float(pack_bf16(0.f, v)); }
__device__ __forceinline__ uint32_t nonzero(uint32_t w) { return w ? w : 0x80008000u; }
__device__ __forceinline__ uint32_t pack_neg(float lo, float hi) { return nonzero(pack_bf16(-lo, -hi)); }
__device__ __forceinline__ float lo_f(uint32_t v) { return __uint_as_float(v << 16); }
__device__ __forceinline__ float hi_f(uint32_t v) { return __uint_as_float(v & 0xffff0000u); }
__device__ __forceinline__ float warp_sum(float v) {
#pragma unroll
    for (int o = 16; o; o >>= 1) v += __shfl_xor_sync(0xffffffffu, v, o);
    return v;
}
__device__ __forceinline__ void layernorm20(float (&v)[20]) {
    float s = 0.f;
#pragma unroll
    for (int i = 0; i < 20; i++) s += v[i];
    const float mean = warp_sum(s) * (1.0f / DM);
    float q = 0.f;
#pragma unroll
    for (int i = 0; i < 20; i++) { const float d = v[i] - mean; q += d * d; }
    const float var = bf16r(warp_sum(q) * (1.0f / DM));
    const float m = bf16r(mean);
    const float rden = 1.0f / bf16r(sqrtf(bf16r(var + 1e-5f)));
#pragma unroll
    for (int i = 0; i < 20; i++) v[i] = bf16r(bf16r(v[i] - m) * rden);
}

__device__ __forceinline__ void moments(float m1, float m2, float& nmean, float& rden) {
    m1 *= 1.0f / DM;
    const float var = bf16r(fmaxf(fmaf(-m1, m1, m2 * (1.0f / DM)), 0.f));
    nmean = bf16r(m1);
    rden = rcp_approx(bf16r(sqrt_approx(bf16r(var + 1e-5f))));
}
__device__ __forceinline__ float sel4(int j, float a, float b, float c, float d) {
    float lo, hi, r;
    asm("{\n.reg .pred p;\nsetp.ne.s32 p, %3, 0;\nselp.f32 %0, %2, %1, p;\n}" : "=f"(lo) : "f"(a), "f"(b), "r"(j & 1));
    asm("{\n.reg .pred p;\nsetp.ne.s32 p, %3, 0;\nselp.f32 %0, %2, %1, p;\n}" : "=f"(hi) : "f"(c), "f"(d), "r"(j & 1));
    asm("{\n.reg .pred p;\nsetp.ne.s32 p, %3, 0;\nselp.f32 %0, %2, %1, p;\n}" : "=f"(r) : "f"(lo), "f"(hi), "r"(j & 2));
    return r;
}
template <typename T> __device__ __forceinline__ void pin(T*& p) { asm volatile("" : "+l"(p)); }
__device__ __forceinline__ void pin(uint32_t& v) { asm volatile("" : "+r"(v)); }
__device__ __forceinline__ void pin(float& v) { asm volatile("" : "+f"(v)); }
__device__ __forceinline__ uint32_t after(uint32_t n, float v) {
    asm volatile("{\n.reg .pred p;\nsetp.eq.u32 p, %1, 0x7fc1a5a5;\n@p add.u32 %0, %0, 32;\n}" : "+r"(n) : "r"(__float_as_uint(v)));
    return n;
}
__device__ __forceinline__ float2 lds64f(uint32_t addr) {
    float2 v;
    asm volatile("ld.shared.v2.f32 {%0,%1}, [%2];" : "=f"(v.x), "=f"(v.y) : "r"(addr) : "memory");
    return v;
}
__device__ __forceinline__ void sts32f(uint32_t addr, float v) { asm volatile("st.shared.f32 [%0], %1;" :: "r"(addr), "f"(v) : "memory"); }
template <int ID> __device__ __forceinline__ void fin_arrive() { asm volatile("bar.arrive %0, 288;" :: "n"(ID) : "memory"); }
template <int ID> __device__ __forceinline__ void fin_sync() { asm volatile("bar.sync %0, 288;" :: "n"(ID) : "memory"); }
template <int ID> __device__ __forceinline__ void fin_sync(uint32_t n) { asm volatile("bar.sync %0, %1;" :: "n"(ID), "r"(n) : "memory"); }
__device__ __forceinline__ float2 sum8(uint32_t addr) {
    float2 t[8];
#pragma unroll
    for (int w = 0; w < 8; w++) t[w] = lds64f(addr + w * 128);
    return make_float2(((t[0].x + t[1].x) + (t[2].x + t[3].x)) + ((t[4].x + t[5].x) + (t[6].x + t[7].x)),
                       ((t[0].y + t[1].y) + (t[2].y + t[3].y)) + ((t[4].y + t[5].y) + (t[6].y + t[7].y)));
}
__device__ __forceinline__ float4 sum4x4(uint32_t addr, int pitch) {
    float4 t[4];
#pragma unroll
    for (int w = 0; w < 4; w++)
        asm volatile("ld.shared.v4.f32 {%0,%1,%2,%3}, [%4];" : "=f"(t[w].x), "=f"(t[w].y), "=f"(t[w].z), "=f"(t[w].w) : "r"(addr + w * pitch) : "memory");
    return make_float4((t[0].x + t[1].x) + (t[2].x + t[3].x), (t[0].y + t[1].y) + (t[2].y + t[3].y),
                       (t[0].z + t[1].z) + (t[2].z + t[3].z), (t[0].w + t[1].w) + (t[2].w + t[3].w));
}
__device__ __forceinline__ void sts64f(uint32_t addr, float x, float y) {
    asm volatile("st.shared.v2.f32 [%0], {%1,%2};" :: "r"(addr), "f"(x), "f"(y) : "memory");
}
__device__ __forceinline__ void lds128_if(uint4& v, uint32_t addr, bool pred) {
    asm volatile("{\n.reg .pred p;\nsetp.ne.u32 p, %5, 0;\n@p ld.shared.v4.u32 {%0,%1,%2,%3}, [%4];\n}"
                 : "+r"(v.x), "+r"(v.y), "+r"(v.z), "+r"(v.w) : "r"(addr), "r"((uint32_t)pred) : "memory");
}
__device__ __forceinline__ void sts128f(uint32_t addr, float x, float y, float z, float w) {
    asm volatile("st.shared.v4.f32 [%0], {%1,%2,%3,%4};" :: "r"(addr), "f"(x), "f"(y), "f"(z), "f"(w) : "memory");
}
template <int NJ>
__device__ __forceinline__ void load_o(uint32_t (&ob)[3 * NJ][2], int bh, int J0, int j) {
    float4 v[NJ][4];
    float2 l;
#pragma unroll 1
    for (int it = 0; it < SPIN_MAX; it++) {
#pragma unroll
        for (int J = 0; J < NJ; J++) {
#pragma unroll
            for (int e = 0; e < 4; e++) v[J][e] = ld_relaxed_f4(&g_st.oacc[oidx(bh, j)] + oidx(0, (J0 + J) * 16 + e * 4));
        }
        l = ld_relaxed_f2(g_st.lsum[bh]);
        bool ok = l.y == UPB;
#pragma unroll
        for (int J = 0; J < NJ; J++) {
#pragma unroll
            for (int e = 0; e < 4; e++) ok &= v[J][e].w == UPB;
        }
        if (all(ok)) break;
    }
    const float rl = __fdividef(1.0f, l.x);
#pragma unroll
    for (int J = 0; J < NJ; J++) {
        ob[3 * J][0] = pack_bf16(v[J][0].x * rl, v[J][1].x * rl);     ob[3 * J][1] = pack_bf16(v[J][2].x * rl, v[J][3].x * rl);
        ob[3 * J + 1][0] = pack_bf16(v[J][0].y * rl, v[J][1].y * rl); ob[3 * J + 1][1] = pack_bf16(v[J][2].y * rl, v[J][3].y * rl);
        ob[3 * J + 2][0] = pack_bf16(v[J][0].z * rl, v[J][1].z * rl); ob[3 * J + 2][1] = pack_bf16(v[J][2].z * rl, v[J][3].z * rl);
    }
}
__device__ __forceinline__ int near_side(uint32_t sb) {
    uint32_t v;
    asm volatile("ld.volatile.shared.u32 %0, [%1];" : "=r"(v) : "r"(sb + SM_SIDE) : "memory");
    return v;
}
__device__ __forceinline__ void poll_row(uint4& a, uint4& b, uint2& c, const void* pa, const void* pb, const void* pc, uint32_t sa, uint32_t sc,
                                         bool arrive, bool nap, uint32_t bar, Warm& warm) {
    asm volatile("{\n.reg .pred p, q, r, s;\n.reg .b32 m, n, it;\n"
                 "setp.ne.u32 r, %19, 0;\nsetp.ne.u32 s, %20, 0;\nmov.u32 it, 0;\n"
                 "POLL:\n"
                 SLOT_ASM("m", "n", "p", "%23", "%24", "%25")
                 "ld.relaxed.gpu.global.v4.u32 {%0,%1,%2,%3}, [%14];\n"
                 "ld.relaxed.gpu.global.v4.u32 {%4,%5,%6,%7}, [%15];\n"
                 "ld.relaxed.gpu.global.v2.u32 {%8,%9}, [%16];\n"
                 "add.u32 it, it, 1;\nsetp.ge.u32 q, it, %21;\n"
                 "mov.u32 m, 0;\nmma.sync.aligned.m16n8k8.row.col.f32.bf16.bf16.f32 {%10,%11,%12,%13}, {m,m}, {m}, {%10,%11,%12,%13};\n"
                 "st.shared.v4.u32 [%17], {%0,%1,%2,%3};\n"
                 "st.shared.v4.u32 [%17+512], {%4,%5,%6,%7};\n"
                 "st.shared.v2.u32 [%18], {%8,%9};\n"
                 "min.u32 m, %0, %1;\nmin.u32 m, m, %2;\nmin.u32 n, %3, %4;\nmin.u32 n, n, %5;\nmin.u32 m, m, %6;\nmin.u32 m, m, %7;\n"
                 "min.u32 n, n, m;\nmin.u32 m, %8, %9;\nmin.u32 m, m, n;\n"
                 "setp.ne.or.u32 p, m, 0, q;\n"
                 "vote.sync.all.pred p, p, 0xffffffff;\n"
                 "and.pred q, p, r;\n"
                 "bar.warp.sync 0xffffffff;\n"
                 "@q mbarrier.arrive.shared::cta.b64 _, [%22];\n"
                 "@p bra.uni DONE;\n"
                 "@s nanosleep.u32 500;\n"
                 "bra.uni POLL;\n"
                 "DONE:\n}"
                 : "=&r"(a.x), "=&r"(a.y), "=&r"(a.z), "=&r"(a.w), "=&r"(b.x), "=&r"(b.y), "=&r"(b.z), "=&r"(b.w), "=&r"(c.x), "=&r"(c.y),
                   "+f"(warm.c[0]), "+f"(warm.c[1]), "+f"(warm.c[2]), "+f"(warm.c[3])
                 : "l"(pa), "l"(pb), "l"(pc), "r"(sa), "r"(sc), "r"((uint32_t)arrive), "r"((uint32_t)nap), "n"(SPIN_MAX), "r"(bar),
                   "n"(slot_phase<PH_H>()), "n"(SLOT_K), "n"(SLOT_OPEN * SLOT_K) : "memory");
}
__device__ __forceinline__ void aux_sync() { asm volatile("bar.sync 1, 256;" ::: "memory"); }

__global__ void __launch_bounds__(NTHREADS, 1)
fused_decode_kernel(const __grid_constant__ Params p) {
    extern __shared__ __align__(1024) unsigned char smem[];
    const uint32_t sb = s2u(smem);
    const int tid = threadIdx.x, cta = blockIdx.x;
    if (tid < 32 && cta < NQ_CTAS) {
        asm volatile("{\n.reg .pred p;\nelect.sync _|p, 0xffffffff;\n"
                     "@p mbarrier.init.shared::cta.b64 [%2], 1;\n"
                     "@p fence.mbarrier_init.release.cluster;\n"
                     "@p mbarrier.arrive.expect_tx.shared::cta.b64 _, [%2], 15360;\n"
                     "@p cp.async.bulk.tensor.2d.shared::cluster.global.mbarrier::complete_tx::bytes [%0], [%1, {%3, %4}], [%2];\n"
                     "@p mbarrier.init.shared::cta.b64 [%2+8], 1;\n@p mbarrier.init.shared::cta.b64 [%2+16], 1;\n"
                     "@p mbarrier.init.shared::cta.b64 [%2+24], 1;\n"
                     "@p fence.mbarrier_init.release.cluster;\n"
                     "@p mbarrier.arrive.expect_tx.shared::cta.b64 _, [%2+8], 15360;\n"
                     "@p cp.async.bulk.tensor.2d.shared::cluster.global.mbarrier::complete_tx::bytes [%0+15360], [%1, {%3, %5}], [%2+8];\n"
                     "@p mbarrier.arrive.expect_tx.shared::cta.b64 _, [%2+16], 15360;\n"
                     "@p cp.async.bulk.tensor.2d.shared::cluster.global.mbarrier::complete_tx::bytes [%0+30720], [%1, {%3, %6}], [%2+16];\n"
                     "@p mbarrier.arrive.expect_tx.shared::cta.b64 _, [%2+24], 15360;\n"
                     "@p cp.async.bulk.tensor.2d.shared::cluster.global.mbarrier::complete_tx::bytes [%0+46080], [%1, {%3, %7}], [%2+24];\n}"
                     :: "r"(sb + SM_W), "l"(&p.wq), "r"(sb + BAR_WQ), "r"(cta * 48), "r"(0), "r"(160), "r"(320), "r"(480) : "memory");
    }
    const int warp = __shfl_sync(0xffffffffu, tid >> 5, 0), lane = tid & 31;
    constexpr int grid = NCTAS;
    const int g = lane >> 2, j = lane & 3;
    uint32_t t_start;
    asm volatile("mov.u32 %0, %%globaltimer_lo;" : "=r"(t_start));
    TS(0);
    if (tid == 32) {
        mbar_init(sb + BAR_WO, 1);
        mbar_init(sb + BAR_H, 1);
#pragma unroll
        for (int i = 0; i < 8 + NWORK; i++) mbar_init(sb + BAR_FW + i * 8, 1);
        sts32f(sb + SM_SIDE, 0.f);
        asm volatile("fence.mbarrier_init.release.cluster;" ::: "memory");
        asm volatile("fence.proxy.async.shared::cta;" ::: "memory");
    }
    __syncthreads();
    if (warp >= NAUX + NWORK) {
        const int fw = warp - (NAUX + NWORK), fi = ffn_slice(cta);
        if (fw == 0) {
            if (cta < NQ_CTAS) {
#pragma unroll
                for (int i = lane; i < STATE_V4; i += 32)
                    if (cta * STATE_V4 + i < (int)(sizeof(State) / 16)) reinterpret_cast<uint4*>(&g_st)[cta * STATE_V4 + i] = make_uint4(0u, 0u, 0u, 0u);
                __syncwarp();
                if (lane == 0) red_release(g_cnt_z);
            }
            TSW(2); wait_count(g_cnt_z, NQ_CTAS); TSW(29);
            asm volatile("bar.arrive 2, %0;" :: "n"((NWORK + 2) * 32) : "memory");
            fin_arrive<3>();
        } else {
#pragma unroll 1
            for (int n = cta < NE_CTAS ? 5 : 4, i = n - 1; i >= 0; i--) {
                const int head = cta < NE_CTAS ? cta >> 2 : 28 + i;
                wait_time(t_start + WO_AT_NS + (NH - 1 - head) * WO_STEP_NS);
                request_box(sb + SM_A + i * 12288, &p.wo, cta < NE_CTAS ? (cta & 3) * 160 + i * 32 : (cta - NE_CTAS) * 32,
                            head * DH, sb + BAR_WO, i == n - 1 ? n * 12288 : 0);
            }
            asm volatile("bar.sync 2, %0;" :: "n"((NWORK + 2) * 32) : "memory");
            uint32_t best[2] = {~0u, ~0u};
#pragma unroll 1
            for (int i = 0; i < NPROBE; i++) {
#pragma unroll
                for (int c = 0; c < 2; c++) {
                    uint32_t t0 = clock(), t1 = t0;
                    int v = 0;
                    draw(v, &g_st.hx.w[c][PROBE], lane == 0);
                    asm volatile("{\n.reg .pred p;\nsetp.ne.u32 p, %1, 0xffffffff;\n@p mov.u32 %0, %%clock;\n}" : "+r"(t1) : "r"(v) : "memory");
                    best[c] = min(best[c], t1 - t0);
                }
                __nanosleep(1000);
            }
            if (lane == 0) sts32f(sb + SM_SIDE, __uint_as_float(best[1] < best[0]));
        }
        int job = cta;
        auto sum_rows = [&](int row_end) {
#pragma unroll 1
            for (; job < 8 * min(row_end, RED0); job += NCTAS) {
                const int row = job >> 3, grp = (job & 7) * 8 + (lane & 7);
                wait_row(row, UPB);
                const float4* src = &g_ring[row % RING][lane >> 3][grp];
                float sx = 0.f, sy = 0.f, sz = 0.f;
#pragma unroll 1
                for (int i = 0; i < 2; i++, src += 64 * 64) {
                    float4 v[16];
#pragma unroll 1
                    for (int it = 0; it < SPIN_MAX; it++) {
                        bool ok = true;
#pragma unroll
                        for (int k = 0; k < 16; k++) v[k] = ld_relaxed_b128(src + k * 4 * 64);
#pragma unroll
                        for (int k = 0; k < 16; k++) ok &= v[k].w == (float)(row + 1);
                        if (all(ok)) break;
                    }
#pragma unroll
                    for (int k = 0; k < 16; k++) { sx += v[k].x; sy += v[k].y; sz += v[k].z; }
                }
#pragma unroll
                for (int o = 8; o < 32; o <<= 1) {
                    sx += __shfl_xor_sync(0xffffffffu, sx, o); sy += __shfl_xor_sync(0xffffffffu, sy, o); sz += __shfl_xor_sync(0xffffffffu, sz, o);
                }
                if (lane < 8) st_relaxed_b128(&g_st.oacc[oidx(row, grp)], sx, sy, sz, UPB);
            }
        };
        const int ho0 = lane / 20 * 256 + lane % 20 * 4, ho1 = (lane + 32) / 20 * 256 + (lane + 32) % 20 * 4, ho2 = 3 * 256 + 16 + 2 * lane;
        uint32_t wr[10] = {};
        float wsum = 0.f;
        if (is_g(cta) && fw == 0) {
#pragma unroll
            for (int i = 0; i < 10; i++) {
                const int w = 4 * lane + 128 * (i >> 2) + (i & 3) - (i >= 8 ? 2 * lane : 0);
                wr[i] = *reinterpret_cast<const uint32_t*>(p.wr + (w >> 4) * 32 + (w & 3) * 8 + ((w >> 1) & 6));
                wsum += lo_f(wr[i]) + hi_f(wr[i]);
            }
            wsum = warp_sum(wsum);
        }
        const int fb = lane >> 3, fg = lane & 7;
        if (fw == 0) {
#pragma unroll
            for (int i = lane; i < DM / 2; i += 32) sts32f(sb + SM_X + 4 * HPITCH + i * 4, __uint_as_float(0x3f803f80u));
        }
        Warm warm;
        float nmean = 0.f, rden = 0.f, sig = 0.f;
#pragma unroll 1
        for (int b = 0; b < NB; b++) {
            const bool ffn = b >= NB - 2;
            if (fw == 0) {
                sum_rows((b + 1) * NH);
                if (ffn) asm volatile("bar.arrive 8, 64;" ::: "memory");
            } else if (ffn) {
                asm volatile("bar.sync 8, 64;" ::: "memory");
                if (b == NB - 1 && (is_f(cta) || is_g(cta) || ALL_LOADERS)) {
                    uint32_t t0 = 0;
#pragma unroll 1
                    for (int it = 0; it < SPIN_MAX; it++) {
                        t0 = ld_relaxed_u32(g_st.fw_time);
                        if (all(t0 != 0)) break;
                        __nanosleep(150);
                    }
                    asm volatile("fence.proxy.async.shared::cta;" ::: "memory");
                    wait_time(t0 + FW_AT_NS);
                    TSW(9);
                    uint32_t t = clock() + (is_f(cta) ? ((fi & 1) * 24 + (fi >> 1)) * FW_GAP / 48 : FW_MID + ((fi & 3) * 10 + (fi >> 2)) * FW_GAP2 / 40);
#pragma unroll 1
                    for (int i = 0; i < 8; i++) {
                        const uint32_t bar = sb + BAR_FW + i * 8;
                        if (is_f(cta)) {
                            wait_clock(t, warm);
                            request_box(sb + SM_W + i * 10240, (i & 1) ? &p.wu : &p.wg, fi * 32, (i >> 1) * 160, bar, 10240);
                            t += FW_GAP;
                        } else if (is_g(cta)) {
                            wait_clock(t, warm);
                            asm volatile("{\n.reg .pred p;\nelect.sync _|p, 0xffffffff;\n"
                                         "@p mbarrier.arrive.expect_tx.shared::cta.b64 _, [%2], 6144;\n"
                                         "@p cp.async.bulk.tensor.4d.shared::cluster.global.mbarrier::complete_tx::bytes [%0], [%1, {%3, %4, %4, %5}], [%2];\n}"
                                         :: "r"(sb + SM_W + i * 6144), "l"(&p.wd), "r"(bar), "r"(fi * 16), "r"(0), "r"(i * 12) : "memory");
                            t += FW_GAP2;
                        }
                    }
                }
                if (is_f(cta)) {
                    const uint32_t* src = &g_st.hx.w[near_side(sb)][min(fb, b) * 256 + 96];
                    float4 m;
#pragma unroll 1
                    for (int it = 0; it < SPIN_MAX; it++) {
                        wait_slot<PH_M>();
                        m = ld_relaxed_f4(src);
                        warm();
                        if (all(m.y + m.w == 2 * (NCTAS - NE_CTAS))) break;
                        if (b < NB - 1) __nanosleep(500);
                    }
                    moments(m.x, m.z, m.x, m.z);
                    sts64f(sb + SM_RED + 5120 + fb * 8, m.x, m.z);
                }
            }
            if (fw == 0 && cta >= NE_CTAS) {
                const int lc = cta - NE_CTAS, col = lc * 32 + 2 * (lane & 15);
                const uint32_t xv = *reinterpret_cast<const uint32_t*>(p.x + b * DM + col);
                uint32_t* dst = &(ffn ? g_st.hx.w : g_st.lx.w + 2)[lane >> 4][(b & 1) * 128 + lc / 5 * 256 + lc % 5 * 16 + (col & 6) * 2 + ((col >> 3) & 3)];
                uint32_t part = sb + SM_RED + (lane & 15) * 8;
                wait_row(b * NH + 28, 1);
                float4 early;
#pragma unroll 1
                for (int it = 0; it < SPIN_MAX; it++) {
                    early = ld_relaxed_f4(&g_st.attn[b][col]);
                    if (all(early.y == NE_CTAS / 4 && early.w == NE_CTAS / 4)) break;
                }
                if (early.x != 1.2345f && lane == 0) TS2(6);
                CK(1, __float_as_uint(early.x));
                const float x0 = -(lo_f(xv) + early.x), x1 = -(hi_f(xv) + early.z);
                fin_sync<4>(after(after(288, x0), x1));
                CK(2, lds32(sb + SM_RED));
                const float2 late = sum8(part);
                const uint32_t hv = nonzero(pack_bf16(x0 - late.x, x1 - late.y));
                st_relaxed(dst, hv);
                if (ffn) st_relaxed(dst + 2048, hv);
                CK(3, 0);
                float m = lane < 16 ? lo_f(hv) + hi_f(hv) : fmaf(lo_f(hv), lo_f(hv), hi_f(hv) * hi_f(hv));
#pragma unroll
                for (int o = 1; o < 16; o <<= 1) m += __shfl_xor_sync(0xffffffffu, m, o);
                if ((lane & 14) == 0) red_f2(reinterpret_cast<float*>(&g_st.hx.w[lane & 1][b * 256 + 96 + (lane >> 4) * 2]), m, 1.f);
                fin_arrive<5>();
            }
            if (fw == 0 && (is_g(cta) || is_f(cta))) {
                const uint32_t* src = &(ffn ? g_st.hx.w : g_st.lx.w + 2)[near_side(sb) ^ (ffn && is_g(cta) ? 3 : 0)][(b & 1) * 128];
                const uint32_t hrow = sb + SM_X + b * HPITCH;
                wait_sum(b == NB - 1 ? (const void*)&g_st.lx.w[near_side(sb) ^ 1][3 * 256] : g_st.lsum[b * NH + NH - 1], UPB, 100);
                wait_clock(clock() + HGATE_NS * 2, warm);
                uint4 h0, h1;
                uint2 h2;
                poll_row(h0, h1, h2, src + ho0, src + ho1, src + ho2, hrow + lane * 16, hrow + 1024 + lane * 8, ffn && lane == 0, b < NB - 1, sb + BAR_H, warm);
                CK(4, h0.x);
                if (is_g(cta)) {
                    const uint32_t hw[10] = {h0.x, h0.y, h0.z, h0.w, h1.x, h1.y, h1.z, h1.w, h2.x, h2.y};
                    float m1 = 0.f, m2 = 0.f, rr = 0.f;
#pragma unroll
                    for (int i = 0; i < 10; i++) {
                        const float v0 = lo_f(hw[i]), v1 = hi_f(hw[i]);
                        m1 += v0 + v1;
                        m2 = fmaf(v0, v0, fmaf(v1, v1, m2));
                        rr = fmaf(v0, lo_f(wr[i]), fmaf(v1, hi_f(wr[i]), rr));
                    }
                    moments(warp_sum(m1), warp_sum(m2), m1, m2);
                    const float sg = bf16r(sigmoid_approx(bf16r((m1 * wsum - warp_sum(rr)) * m2)));
                    if (fb == b) { nmean = m1; rden = m2; sig = sg; }
                    __syncwarp();
                    if (ffn) {
                        const int yj = 2 * (fb & 1) + (fb >> 1);
                        uint32_t ypart = sb + SM_RED2 + yj * 128 + ((fg + 2 * yj) & 7) * 16;
                        __nv_bfloat16* out = p.out + fb * DM + fi * 16 + fg;
                        const float2 hw2 = lds64f(sb + SM_X + fb * HPITCH + ((fi >> 1) * 16 + (fg & 6) * 2 + (fi & 1) * 2) * 4);
                        const uint32_t w0 = __float_as_uint(hw2.x), w1 = __float_as_uint(hw2.y);
                        const float nh0 = (fg & 1) ? hi_f(w0) : lo_f(w0), nh1 = (fg & 1) ? hi_f(w1) : lo_f(w1);
                        const float ln0 = bf16r(bf16r(nmean - nh0) * rden) - nh0, ln1 = bf16r(bf16r(nmean - nh1) * rden) - nh1;
                        pin(ypart); pin(out);
                        fin_sync<6>(after(after(after(288, sig), ln0), ln1));
                        CK(10, lds32(ypart));
                        const float4 ya = sum4x4(ypart, 512), yb = sum4x4(ypart + 2048, 512);
                        const float4 y = make_float4(ya.x + yb.x, ya.y + yb.y, ya.z + yb.z, ya.w + yb.w);
                        const float y0 = -(((fb & 1) ? y.y : y.x) + __shfl_xor_sync(0xffffffffu, (fb & 1) ? y.x : y.y, 8));
                        const float y1 = -(((fb & 1) ? y.w : y.z) + __shfl_xor_sync(0xffffffffu, (fb & 1) ? y.z : y.w, 8));
                        const uint32_t ov = pack_bf16(fmaf(y0, sig, ln0), fmaf(y1, sig, ln1));
                        if (b == NB - 1) {
                            asm volatile("st.global.u16 [%0], %1;" :: "l"(out), "h"((unsigned short)(ov & 0xffffu)) : "memory");
                            asm volatile("st.global.u16 [%0], %1;" :: "l"(out + 8), "h"((unsigned short)(ov >> 16)) : "memory");
                        }
                        CK(11, 0);
                        if (lane == 0) TS2(13);
                    }
                }
            }
            if (is_f(cta) && ffn) {
                const int ks = (2 * fi + fw) % 12;
                const int far = near_side(sb) ^ 1;
                uint32_t* dst = &g_st.ax[ks >> 2].w[(~b & 1) * 2 + far][(fi / 6) * 128 + (ks & 3) * 32 + fb * 8 + (fg & 1) * 4 + ((fg >> 1) ^ (ks & 1))];
                uint32_t* dst2 = dst + (far ? -1024 : 1024);
                uint32_t part = sb + SM_RED + fw * 2560 + fb * 128 + ((fg + (fb & 2)) & 7) * 16;
                uint32_t psum = sb + SM_RED + fw * 2560 + 4 * 128 + ((fg + 4) & 7) * 16;
                pin(dst); pin(part); pin(psum);
                asm volatile("bar.sync 4, 320;" ::: "memory");
                CK(6, lds32(part));
                const float4 d = sum4x4(part, 640), cs = sum4x4(psum, 640);
                const float2 mo = lds64f(sb + SM_RED + 5120 + fb * 8);
                nmean = mo.x; rden = mo.y;
                const float g0 = fmaf(nmean, cs.x, -d.x), g1 = fmaf(nmean, cs.y, -d.y), ke = rden * -1.4426950408889634f, r2 = rden * rden;
                const float p0 = g0 * fmaf(-nmean, cs.z, d.z) * r2, p1 = g1 * fmaf(-nmean, cs.w, d.w) * r2;
                const uint32_t av = nonzero(pack_bf16(p0 * rcp_approx(1.0f + ex2_approx(g0 * ke)), p1 * rcp_approx(1.0f + ex2_approx(g1 * ke))));
                st_relaxed(dst, av);
                st_relaxed(dst2, av);
                CK(7, 0);
            }
        }
        warm.done(sb + SM_SCRAP);
        if (cta == 0 && tid == (NAUX + NWORK) * 32) { g_work[0] = 0; g_work[32] = 0; g_cnt_z[0] = 0; }
        return;
    }
    if (warp >= NAUX) {
        const int wk = warp - NAUX;
        const uint32_t bar = sb + BAR_KV + wk * 8;
        const uint32_t buf = sb + SM_KV + wk * TILE_BYTES;
        uint64_t pol;
        asm volatile("createpolicy.fractional.L2::evict_first.b64 %0, 1.0;" : "=l"(pol));
        const int nstatic = NWORK * grid;
        constexpr int POOL0 = NUNITS - NPOOL;
        int uk = wk * grid + cta;
        wait_time(t_start + K0_AT_NS + uk * KSWEEP_NS / nstatic);
        request_tile(buf, &p.k, uk, bar, pol);
        uint32_t koff[3], voff[3];
        {
            const int r = lane & 7, hf = (lane >> 3) & 1;
            const int kkey = hf ? 8 + (r ^ 1) : r;
            const int vh = lane >> 4;
            const int vkey = ((r & 1) ? 8 : 0) + (vh ? (r ^ 1) : r);
#pragma unroll
            for (int b = 0; b < 3; b++) {
                const int rk = 3 * kkey + b, rv = 3 * vkey + b;
                koff[b] = buf + rk * 128 + (((lane >> 4) ^ (rk & 7)) << 4);
                voff[b] = buf + rv * 128 + ((hf ^ (rv & 7)) << 4);
            }
        }
        uint32_t phase = 0;
        uint32_t qf[12][2];
        auto load_q = [&](int u) {
            const uint32_t* q = g_early[u / UPB].q[0][j];
#pragma unroll
            for (int i = 0; i < 4; i++) {
                const uint4 a = ld_relaxed_v4(q + i * 32);
                const float2 c = ld_relaxed_f2(q + i * 32 + 4);
                qf[3 * i][0] = a.x; qf[3 * i][1] = a.y; qf[3 * i + 1][0] = a.z; qf[3 * i + 1][1] = a.w;
                qf[3 * i + 2][0] = __float_as_uint(c.x); qf[3 * i + 2][1] = __float_as_uint(c.y);
            }
        };
        load_q(uk);
        int uq[LAG];
        uint32_t sq[LAG];
#pragma unroll
        for (int i = 0; i < LAG; i++) { uq[i] = -1; sq[i] = 0; }
        uint4 mv = make_uint4(0u, 0u, 0u, 0u);
        float freed = UPB;
        while (true) {
            const int uv = uq[0];
            uint32_t sv = sq[0];
#pragma unroll
            for (int i = 0; i + 1 < LAG; i++) { uq[i] = uq[i + 1]; sq[i] = sq[i + 1]; }
            uq[LAG - 1] = uk;
            if (uk < NUNITS) {
                PH(7);
#pragma unroll 1
                for (int it = 0; it < SPIN_MAX; it++) {
                    uint32_t lo = 0xffffffffu;
#pragma unroll
                    for (int i = 0; i < 12; i++) lo = min(lo, min(qf[i][0], qf[i][1]));
                    if (all(lo != 0)) break;
                    __nanosleep(250);
                    load_q(uk);
                }
                mbar_wait(bar, phase); phase ^= 1;
                PH(0); ARR();
                TSI(0, 16); TSI(1, 18);
                float acc[2][4][4] = {};
#pragma unroll
                for (int ks = 0; ks < 12; ks++) {
#pragma unroll
                    for (int mt = 0; mt < 4; mt++) {
                        uint32_t a[4];
                        ldsm4(a, (koff[ks >> 2] ^ ((ks & 3) << 5)) + mt * 6144);
                        mma16816(acc[ks & 1][mt], a, qf[ks][0], qf[ks][1]);
                    }
                }
                PH(1);
                TSI(0, 17); TSI(1, 19);
                if (uk < nstatic) wait_time(t_start + K1_AT_NS + uk * KSWEEP_NS / nstatic);
                if (uv < NUNITS) request_tile(buf, uv >= 0 ? &p.v : &p.k, uv >= 0 ? uv : uk + nstatic, bar, pol);
                const float sa = sel4(j, acc[0][0][0], acc[0][1][0], acc[0][2][0], acc[0][3][0]) + sel4(j, acc[1][0][0], acc[1][1][0], acc[1][2][0], acc[1][3][0]);
                const float sc = sel4(j, acc[0][0][2], acc[0][1][2], acc[0][2][2], acc[0][3][2]) + sel4(j, acc[1][0][2], acc[1][1][2], acc[1][2][2], acc[1][3][2]);
                const uint32_t raw = pack_bf16(sa, sc);
                const float scale = -0.07216878364870322f;
                const uint32_t sk = pack_bf16(lo_f(raw) * scale, hi_f(raw) * scale);
                sq[LAG - 1] = sk;
                if (uk >= POOL0) st_relaxed(&g_st.score[uk - POOL0][lane], sk ? sk : 0x80008000u);
                int a = (int)(sk << 16), b = (int)(sk & 0xffff0000u);
                a ^= (a >> 31) & 0x7fff0000; b ^= (b >> 31) & 0x7fff0000;
                const int mx = __reduce_max_sync(0xffffffffu, max(a, b));
                if (lane == 0) st_relaxed(&g_early[uk / UPB].umax[uk % UPB], (uint32_t)mx | 1u);
            }
            if (uv < 0) {
                uk += nstatic;
                load_q(uk);
                continue;
            }
            if (uv >= NUNITS) break;
            const int bh = uv / UPB;
#pragma unroll 1
            for (int it = 0; it < SPIN_MAX; it++) {
                if (all((mv.x & mv.y & mv.z & mv.w & 1u) && (uv < POOL0 || sv != 0) && freed == UPB)) break;
                mv = ld_relaxed_v4(&g_early[bh].umax[lane * 4]);
                if (bh >= RING && bh < RED0) freed = __uint_as_float(ld_relaxed_u32(&g_st.oacc[oidx(bh - RING, (lane & 7) * 8)].w));
                if (uv >= POOL0) sv = ld_relaxed_u32(&g_st.score[uv - POOL0][lane]);
            }
            PH(2);
            int un = NUNITS, vn = 0;
            draw(un, g_work, uk < NUNITS && lane == 0);
            uint32_t tdraw;
            asm volatile("mov.u32 %0, %%globaltimer_lo;" : "=r"(tdraw));
            draw(vn, g_work + 32, uq[0] >= POOL0 && lane == 0);
            int mx = __reduce_max_sync(0xffffffffu, max(max((int)mv.x, (int)mv.y), max((int)mv.z, (int)mv.w))) & 0xffff0000;
            mx ^= (mx >> 31) & 0x7fff0000;
            const float m = __int_as_float(mx);
            const float l2e = 1.4426950408889634f;
            const uint32_t pp = pack_bf16(exp2f((lo_f(sv) - m) * l2e), exp2f((hi_f(sv) - m) * l2e));
            uint32_t pb[8];
#pragma unroll
            for (int t = 0; t < 4; t++) {
                pb[2 * t] = __shfl_sync(0xffffffffu, pp, 8 * j + t);
                pb[2 * t + 1] = __shfl_sync(0xffffffffu, pp, 8 * j + 4 + t);
            }
            float lacc[4] = {};
            const uint32_t ones[4] = {0x3f803f80u, 0x3f803f80u, 0x3f803f80u, 0x3f803f80u};
#pragma unroll
            for (int t = 0; t < 4; t++) mma16816(lacc, ones, pb[2 * t], pb[2 * t + 1]);
            if (uv < nstatic) {
                asm volatile("bar.sync 2, %0;" :: "n"((NWORK + 2) * 32) : "memory");
                TSW(3);
            }
            const int grp = 16 * j + 4 * (g & 1) + (g >> 1);
            uint32_t mode = (bh >= RED0) + (bh >= NBH - 4);
            float tag = mode ? 1.f : (float)(bh + 1), tag2 = fmaf(__uint_as_float(voff[0]), 0.f, tag);
            void* dst = mode == 0 ? (void*)&g_ring[bh % RING][uv % UPB][grp] :
                        mode == 1 ? (void*)&g_st.oacc[oidx(bh, grp)] : (void*)&g_st.ox[0].w[uv % OREP * 2][oidx(bh & 3, grp) * 4];
            if (mode == 2 && lane < 2) red_f2(reinterpret_cast<float*>(&g_st.lx.w[lane][(bh & 3) * 256]), lacc[0], 1.f);
            un = __shfl_sync(0xffffffffu, un, 0) + (LAG + 1) * nstatic;
            vn = __shfl_sync(0xffffffffu, vn, 0);
            if (uq[0] >= POOL0) uq[0] = POOL0 + vn;
            if (vn == FW_TICKET && lane == 0) st_relaxed(g_st.fw_time, tdraw | 1u);
            if (uq[0] < NUNITS && un >= NUNITS) {
                mv = ld_relaxed_v4(&g_early[uq[0] / UPB].umax[lane * 4]);
                if (uq[0] < RED0 * UPB) freed = 0.f;
                if (uq[0] >= POOL0) sq[0] = ld_relaxed_u32(&g_st.score[uq[0] - POOL0][lane]);
            }
            pin(dst); pin(mode); pin(tag); pin(tag2); pin(voff[0]); pin(voff[1]); pin(voff[2]);
            PH(3);
            mbar_wait(bar, phase); phase ^= 1;
            PH(4); ARR(); CK(12, lds32(buf));
            float acc[12][4] = {};
#pragma unroll
            for (int t = 0; t < 4; t++) {
#pragma unroll
                for (int mt = 0; mt < 12; mt++) {
                    uint32_t a[4];
                    ldsm4t(a, (voff[mt >> 2] ^ ((mt & 3) << 5)) + t * 6144);
                    mma16816(acc[mt], a, pb[2 * t], pb[2 * t + 1]);
                }
            }
            PH(5);
            if (lane == 0) PROG(un);
            if (un < NUNITS || uq[0] < NUNITS) request_tile(buf, un < NUNITS ? &p.k : &p.v, un < NUNITS ? un : uq[0], bar, pol);
            if (un < NUNITS || uq[0] < NUNITS) CK(11, 0);
            float o[6];
#pragma unroll
            for (int e = 0; e < 6; e++) {
                const int q = e % 3, c = (e / 3) * 2;
                o[e] = sel4(j, acc[q][c], acc[3 + q][c], acc[6 + q][c], acc[9 + q][c]);
            }
            put_groups(dst, mode, o, tag, tag2);
            CK(13, 0);
            if (un < NUNITS) load_q(un);
            if (lane == 0) red_f2(&g_st.lsum[bh][0].x, lacc[0], 1.f);
            PH(6);
            if (uq[0] >= NUNITS && un >= NUNITS) break;
            uk = un;
            if (uq[0] < NUNITS && un < NUNITS) {
                const int nb = uq[0] / UPB;
                mv = ld_relaxed_v4(&g_early[nb].umax[lane * 4]);
                freed = nb >= RING && nb < RED0 ? __uint_as_float(ld_relaxed_u32(&g_st.oacc[oidx(nb - RING, (lane & 7) * 8)].w)) : UPB;
                if (uq[0] >= POOL0) sq[0] = ld_relaxed_u32(&g_st.score[uq[0] - POOL0][lane]);
            }
        }
        TSW(4 + wk);
        return;
    }

    __nv_bfloat16* xs = reinterpret_cast<__nv_bfloat16*>(smem + SM_X);
    float* red = reinterpret_cast<float*>(smem + SM_RED);
    const int frow = (lane & 7) + ((lane >> 4) << 3), fcol = (lane >> 3) & 1;
    const uint32_t f64b = sb + (frow * 4 + (fcol ^ ((frow >> 1) & 3))) * 16;
    if (cta < NQ_CTAS) {
        TS(26);
        if (warp >= 4) {
            uint2 xr[5];
#pragma unroll
            for (int i = 0; i < 5; i++) xr[i] = *reinterpret_cast<const uint2*>(p.x + (warp - 4) * DM + i * 128 + lane * 4);
            float v[20];
#pragma unroll
            for (int i = 0; i < 5; i++) {
                v[4 * i] = lo_f(xr[i].x); v[4 * i + 1] = hi_f(xr[i].x); v[4 * i + 2] = lo_f(xr[i].y); v[4 * i + 3] = hi_f(xr[i].y);
            }
            layernorm20(v);
#pragma unroll
            for (int i = 0; i < 5; i++)
                *reinterpret_cast<uint2*>(xs + (warp - 4) * XPITCH + i * 128 + lane * 4) =
                    make_uint2(pack_bf16(v[4 * i], v[4 * i + 1]), pack_bf16(v[4 * i + 2], v[4 * i + 3]));
        }
        aux_sync();
        TS(27);
        mbar_wait(sb + BAR_WQ + (warp >> 1) * 8, 0);
        TS(1);
        const uint32_t xfrag = sb + SM_X + ((g & 3) * XPITCH + 2 * j) * 2;
        float acc[3][4] = {};
#pragma unroll
        for (int s = 0; s < 5; s++) {
            const int ks = warp * 5 + s;
            const uint32_t b0 = lds32(xfrag + ks * 32), b1 = lds32(xfrag + ks * 32 + 16);
            const int row = ks * 16 + frow;
#pragma unroll
            for (int mt = 0; mt < 3; mt++) {
                uint32_t a[4];
                ldsm4t(a, sb + SM_W + (row * 6 + 2 * mt + fcol) * 16);
                mma16816(acc[mt], a, b0, b1);
            }
        }
        if (j < 2) {
#pragma unroll
            for (int mt = 0; mt < 3; mt++) {
                *reinterpret_cast<float2*>(red + warp * 216 + mt * 72 + g * 4 + 2 * j) = make_float2(acc[mt][0], acc[mt][1]);
                *reinterpret_cast<float2*>(red + warp * 216 + mt * 72 + 36 + g * 4 + 2 * j) = make_float2(acc[mt][2], acc[mt][3]);
            }
        }
        aux_sync();
        if (warp < 4) {
            const float* src = red + min(g, 5) * 36 + warp * 8 + j;
            float s0 = 0.f, s1 = 0.f;
#pragma unroll
            for (int w = 0; w < 8; w++) { s0 += src[w * 216]; s1 += src[w * 216 + 4]; }
            st_relaxed(&g_early[j * NH + (cta >> 2)].q[cta & 3][warp][g], pack_neg(s0, s1));
        }
        TS(28);
    }
    fin_sync<3>();
    mbar_wait(sb + BAR_WO, 0);
    TS(7);
    uint32_t part = sb + SM_RED + (warp * 32 + 8 * j + g) * 4;

#pragma unroll 1
    for (int b = 0; b < NB; b++) {
        if (cta >= NE_CTAS) {
            uint32_t a[6][2][4];
#pragma unroll
            for (int s = 0; s < 6; s++) {
#pragma unroll
                for (int mt = 0; mt < 2; mt++) ldsm4t(a[s][mt], (f64b ^ (mt * 32)) + SM_A + (warp * 6 + s) * 1024);
            }
            const int bh = b * NH + 28 + (warp >> 1);
            const int side = near_side(sb) ^ 1;
            const void* osrc[OREP];
#pragma unroll
            for (int c = 0; c < OREP; c++)
                osrc[c] = b == NB - 1 ? (const void*)&g_st.ox[c >> 1].w[side ^ (c & 1) * 3][oidx(bh & 3, (warp & 1) * 32 + lane) * 4] : &g_st.oacc[oidx(bh, (warp & 1) * 32 + lane)];
            const void* lsrc = b == NB - 1 ? (const void*)&g_st.lx.w[side][(bh & 3) * 256] : g_st.lsum[bh];
            wait_row_o(bh, 1);
            const float rl = rcp_approx(wait_sum(lsrc, UPB)) * (b == NB - 1 ? 1.f : 1.f / OREP), full = b == NB - 1 ? UPB : UPB * OREP;
            float4 ov;
            float px, py, pz;
            Warm warm;
#pragma unroll 1
            for (int it = 0; it < SPIN_MAX; it++) {
                wait_slot<PH_O>();
                float4 oc[OREP];
#pragma unroll
                for (int c = 0; c < OREP; c++) oc[c] = ld_relaxed_f4(osrc[c]);
                warm();
                ov = oc[0];
#pragma unroll
                for (int c = 1; c < OREP; c++) { ov.x += oc[c].x; ov.y += oc[c].y; ov.z += oc[c].z; ov.w += oc[c].w; }
                ov.x *= rl; ov.y *= rl; ov.z *= rl;
                px = __shfl_xor_sync(0xffffffffu, ov.x, 4); py = __shfl_xor_sync(0xffffffffu, ov.y, 4); pz = __shfl_xor_sync(0xffffffffu, ov.z, 4);
                if (all(ov.w == full)) break;
            }
            CK(0, __float_as_uint(ov.x));
            if (ov.x != 1.2345f && warp == 7) TSW(14);
            const uint32_t w[3] = {pack_bf16(ov.x, px), pack_bf16(ov.y, py), pack_bf16(ov.z, pz)};
            float acc[2][2][4] = {};
#pragma unroll
            for (int s = 0; s < 6; s++) {
                const uint32_t b0 = __shfl_sync(0xffffffffu, w[s % 3], (s / 3) * 16 + j);
                const uint32_t b1 = __shfl_sync(0xffffffffu, w[s % 3], (s / 3) * 16 + 8 + j);
#pragma unroll
                for (int mt = 0; mt < 2; mt++) mma16816(acc[mt][s & 1], a[s][mt], b0, b1);
            }
            sts32f(part, sel4(j, acc[0][0][0] + acc[0][1][0], acc[0][0][2] + acc[0][1][2], acc[1][0][0] + acc[1][1][0], acc[1][0][2] + acc[1][1][2]));
            CK(1, 0);
            fin_arrive<4>();
            warm.done(sb + SM_SCRAP);
            fin_sync<5>();
            if (cta < NE_CTAS + 4 && tid < 64) reinterpret_cast<uint4*>(&g_early[b * NH + 28 + cta - NE_CTAS])[tid] = make_uint4(0u, 0u, 0u, 0u);
        } else {
            const int bh = b * NH + (cta >> 2);
            if (warp == 0) wait_row_o(bh, UPB);
            aux_sync();
            if (warp < 5) {
                uint32_t ob[12][2];
                load_o<4>(ob, bh, 0, j);
                float acc[2][2][4] = {};
#pragma unroll
                for (int ks = 0; ks < 12; ks++) {
#pragma unroll
                    for (int mt = 0; mt < 2; mt++) {
                        uint32_t a[4];
                        ldsm4t(a, (f64b ^ (mt * 32)) + SM_A + warp * 12288 + ks * 1024);
                        mma16816(acc[mt][ks & 1], a, ob[ks][0], ob[ks][1]);
                    }
                }
                red_f2(&g_st.attn[b][(cta & 3) * 160 + warp * 32 + 8 * j + g].x,
                       sel4(j, acc[0][0][0] + acc[0][1][0], acc[0][0][2] + acc[0][1][2], acc[1][0][0] + acc[1][1][0], acc[1][0][2] + acc[1][1][2]), 1.f);
                TS(8);
            } else if (warp > 5 && (cta & 3) == 0) {
                reinterpret_cast<uint4*>(&g_early[bh])[tid - 192] = make_uint4(0u, 0u, 0u, 0u);
            }
        }
        if (b < NB - 2) continue;

        if (is_f(cta)) {
            uint32_t ga[10][2][4];
            uint4 hv[5] = {};
            const uint32_t hfrag = sb + SM_X + min(g, 4) * HPITCH + ((warp >> 1) * 80 + 4 * j) * 4;
#pragma unroll
            for (int s = 0; s < 5; s++) lds128_if(hv[s], hfrag + s * 64, b == NB - 1);
            if (b == NB - 1) mbar_wait(sb + BAR_FW + warp * 8, 0);
            if (warp == 7) TSW(10);
            CK(12, lds32(sb + SM_W));
#pragma unroll
            for (int s = 0; s < 10; s++) {
#pragma unroll
                for (int mt = 0; mt < 2; mt++) ldsm4t(ga[s][mt], (f64b ^ (mt * 32)) + SM_W + (warp * 10 + s) * 1024);
            }
            const uint32_t gpart = sb + SM_RED + (warp >> 1) * 640 + j * 256 + ((g + 2 * j) & 7) * 16 + (warp & 1) * 8;
            mbar_wait(sb + BAR_H, b & 1);
#pragma unroll
            for (int s = 0; s < 5; s++) lds128_if(hv[s], hfrag + s * 64, g == b);
            CK(4, hv[0].x);
            float acc[2][2][4] = {};
#pragma unroll
            for (int s = 0; s < 10; s++) {
#pragma unroll
                for (int mt = 0; mt < 2; mt++)
                    mma16816(acc[mt][s & 1], ga[s][mt], (s & 1) ? hv[s >> 1].z : hv[s >> 1].x, (s & 1) ? hv[s >> 1].w : hv[s >> 1].y);
            }
#pragma unroll
            for (int mt = 0; mt < 2; mt++) {
                if (j < 3) sts64f(gpart + mt * 2560, acc[mt][0][0] + acc[mt][1][0], acc[mt][0][2] + acc[mt][1][2]);
                if (j < 2) sts64f(gpart + mt * 2560 + 128, acc[mt][0][1] + acc[mt][1][1], acc[mt][0][3] + acc[mt][1][3]);
            }
            CK(5, 0);
            asm volatile("bar.arrive 4, 320;" ::: "memory");
        } else if (is_g(cta)) {
            const uint32_t* asrc = &g_st.ax[0].w[(~b & 1) * 2 + near_side(sb)][warp * 128 + ((g >> 2) * 2 + (j >> 1)) * 32 + (g & 3) * 8 + (j & 1) * 4];
            const uint32_t ypart = sb + SM_RED2 + warp * 512 + j * 128 + ((g + 2 * j) & 7) * 16;
            uint32_t wb[12][4];
            if (b == NB - 1) mbar_wait(sb + BAR_FW + warp * 8, 0);
            if (warp == 7) TSW(11);
            CK(13, lds32(sb + SM_W));
            {
                const int jj = (lane & 7) >> 1, q = jj >> 1, hi = lane >> 4;
                const uint32_t base = sb + SM_W + warp * 6144 + q * 512 + ((hi ^ q) * 4 + (jj & 1) * 2 + (lane & 1)) * 32 + ((fcol ^ hi ^ q) << 4);
#pragma unroll
                for (int s = 0; s < 12; s++) ldsm4t(wb[s], base + (s >> 2) * 2048 + (s & 1) * 1024 + (s & 2) * 128);
            }
            mbar_wait(sb + BAR_H, b & 1);
            uint4 va[3];
            Warm warm;
#pragma unroll 1
            for (int it = 0; it < SPIN_MAX; it++) {
                uint32_t lo = 0xffffffffu;
#pragma unroll
                for (int i = 0; i < 3; i++) va[i] = ld_relaxed_v4(asrc + i * 4096);
                warm();
#pragma unroll
                for (int i = 0; i < 3; i++) lo = min(min(lo, min(va[i].x, va[i].y)), min(va[i].z, va[i].w));
                if (all(lo != 0)) break;
            }
            CK(8, va[0].x);
            if (va[0].x != 0x12345 && warp == 7) TSW(15);
            float acc[6][4] = {};
#pragma unroll
            for (int s = 0; s < 12; s++) {
                const uint4 v = va[s >> 2];
                mma16816(acc[s % 6], wb[s], (s & 2) ? v.z : v.x, (s & 2) ? v.w : v.y);
            }
            float y[4];
#pragma unroll
            for (int e = 0; e < 4; e++) y[e] = j < 2 ? (acc[0][e] + acc[2][e]) + acc[4][e] : (acc[1][e] + acc[3][e]) + acc[5][e];
            sts128f(ypart, y[0], y[1], y[2], y[3]);
            CK(9, 0);
            fin_arrive<6>();
            warm.done(sb + SM_SCRAP);
        }
    }
}

typedef CUresult (*EncodeFn)(CUtensorMap*, CUtensorMapDataType, cuuint32_t, void*, const cuuint64_t*, const cuuint64_t*,
                             const cuuint32_t*, const cuuint32_t*, CUtensorMapInterleave, CUtensorMapSwizzle,
                             CUtensorMapL2promotion, CUtensorMapFloatOOBfill);

CUtensorMap make_map(EncodeFn enc, void* ptr, uint64_t cols, uint64_t rows, uint32_t bcols, uint32_t brows,
                     CUtensorMapSwizzle sw, CUtensorMapL2promotion promo) {
    CUtensorMap m;
    const cuuint64_t dims[2] = {cols, rows};
    const cuuint64_t strides[1] = {cols * 2};
    const cuuint32_t box[2] = {bcols, brows};
    const cuuint32_t es[2] = {1, 1};
    enc(&m, CU_TENSOR_MAP_DATA_TYPE_BFLOAT16, 2, ptr, dims, strides, box, es, CU_TENSOR_MAP_INTERLEAVE_NONE, sw, promo,
        CU_TENSOR_MAP_FLOAT_OOB_FILL_NONE);
    return m;
}

}

extern "C" void kernel_launch(void* const* d_in, const int* in_sizes, int n_in, void* d_out, int out_size) {
    (void)in_sizes; (void)n_in; (void)out_size;
    static EncodeFn enc = nullptr;
    static int sms = 0;
    if (!enc) {
        cudaDriverEntryPointQueryResult qr;
        cudaGetDriverEntryPoint("cuTensorMapEncodeTiled", (void**)&enc, cudaEnableDefault, &qr);
        int dev = 0;
        cudaGetDevice(&dev);
        cudaDeviceGetAttribute(&sms, cudaDevAttrMultiProcessorCount, dev);
        cudaFuncSetAttribute(fused_decode_kernel, cudaFuncAttributeMaxDynamicSharedMemorySize, SM_TOTAL);
    }
    if (sms < NCTAS) return;
    const CUtensorMapL2promotion WPROMO = CU_TENSOR_MAP_L2_PROMOTION_L2_128B;
    Params p;
    p.k = make_map(enc, d_in[1], 64, (uint64_t)NBH * SK * 3, 64, TILE_ROWS, CU_TENSOR_MAP_SWIZZLE_128B, CU_TENSOR_MAP_L2_PROMOTION_NONE);
    p.v = make_map(enc, d_in[2], 64, (uint64_t)NBH * SK * 3, 64, TILE_ROWS, CU_TENSOR_MAP_SWIZZLE_128B, CU_TENSOR_MAP_L2_PROMOTION_NONE);
    p.wq = make_map(enc, d_in[3], NH * DH, DM, 48, 160, CU_TENSOR_MAP_SWIZZLE_NONE, WPROMO);
    p.wo = make_map(enc, d_in[4], DM, NH * DH, 32, DH, CU_TENSOR_MAP_SWIZZLE_64B, WPROMO);
    p.wg = make_map(enc, d_in[7], FF, DM, 32, 160, CU_TENSOR_MAP_SWIZZLE_64B, WPROMO);
    p.wu = make_map(enc, d_in[8], FF, DM, 32, 160, CU_TENSOR_MAP_SWIZZLE_64B, WPROMO);
    {
        const cuuint64_t dims[4] = {DM, 2, 8, FF / 16}, strides[3] = {8 * DM * 2, DM * 2, 16 * DM * 2};
        const cuuint32_t box[4] = {16, 2, 8, 12}, es[4] = {1, 1, 1, 1};
        enc(&p.wd, CU_TENSOR_MAP_DATA_TYPE_BFLOAT16, 4, d_in[9], dims, strides, box, es, CU_TENSOR_MAP_INTERLEAVE_NONE,
            CU_TENSOR_MAP_SWIZZLE_32B, WPROMO, CU_TENSOR_MAP_FLOAT_OOB_FILL_NONE);
    }
    p.x = (const __nv_bfloat16*)d_in[0];
    p.wr = (const __nv_bfloat16*)d_in[6];
    p.out = (__nv_bfloat16*)d_out;
    fused_decode_kernel<<<NCTAS, NTHREADS, SM_TOTAL, cudaStreamPerThread>>>(p);
}
```

```cpp
#include <cuda_runtime.h>
#include <cuda_bf16.h>
#include <cuda.h>
#include <stdint.h>

namespace {

constexpr int NB = 4, NH = 32, SK = 8192, DH = 192, DM = 640, FF = 1536;
constexpr int NBH = NB * NH;
constexpr int TILE = 64;
constexpr int UPB = SK / TILE;
constexpr int NUNITS = NBH * UPB;
constexpr int TILE_BYTES = TILE * DH * 2;
constexpr int TILE_ROWS = TILE * 3;
constexpr int NCTAS = 132;
constexpr int NQ_CTAS = 128;
constexpr int NE_CTAS = 112;
__host__ __device__ constexpr bool is_f(int cta) { return cta < NE_CTAS && cta % 14 < 11 && !(cta & 1); }
__host__ __device__ constexpr bool is_g(int cta) { return cta < NE_CTAS && cta % 14 < 11 && (cta & 1); }
__host__ __device__ constexpr int ffn_slice(int cta) { return cta / 14 * ((cta & 1) ? 5 : 6) + cta % 14 / 2; }

#define NWORK 2
#define LAG 2
#define NPOOL 768
#define RED0 116
#define RING 11
#define OREP 2
#define K0_AT_NS 1150
#define WO_AT_NS (K0_AT_NS + 2000)
#define K1_AT_NS (K0_AT_NS + 4400)
constexpr int KSWEEP_NS = 2000, WO_STEP_NS = 75;
#define FW_TICKET (NPOOL + 32)
#define FW_AT_NS 2090
#define FW_GAP 280
#define FW_MID 2100
#define FW_GAP2 200
#define HGATE_NS 700
#define SLOT_TICKS 8
#define SLOT_OPEN 3
#define PH_O 0
#define PH_H 1
#define PH_M 4
#define NPROBE 24
constexpr int NAUX = 8;
constexpr int NTHREADS = (NAUX + NWORK + 2) * 32;
constexpr int SPIN_MAX = 1 << 22;

constexpr int SM_KV = 0;
constexpr int SM_A = SM_KV + NWORK * TILE_BYTES;
constexpr int SM_W = SM_A + 61440;
constexpr int SM_X = SM_W + 81920;
constexpr int XPITCH = 648;
constexpr int HPITCH = 1344;
constexpr int SM_RED = SM_X + 5 * HPITCH + 64;
constexpr int SM_RED2 = SM_RED + 8 * 48 * 4 * 4;
constexpr int SM_MISC = SM_RED2 + 4096;
constexpr int BAR_WQ = SM_MISC, SM_SCRAP = SM_MISC + 32, BAR_WO = SM_MISC + 40, SM_SIDE = SM_MISC + 48, BAR_H = SM_MISC + 56, BAR_FW = SM_MISC + 64;
constexpr int BAR_KV = BAR_FW + 64;
constexpr int SM_TOTAL = BAR_KV + NWORK * 8;
static_assert(SM_W % 1024 == 0 && NB * XPITCH * 2 <= 4 * HPITCH && SM_RED % 128 == 0, "smem layout");

struct Params {
    CUtensorMap k, v;
    CUtensorMap wq;
    CUtensorMap wo;
    CUtensorMap wg, wu;
    CUtensorMap wd;
    const __nv_bfloat16 *x, *wr;
    __nv_bfloat16* out;
};

struct Early {
    uint32_t q[4][4][8];
    uint32_t umax[UPB];
};
struct Twin { uint32_t w[4][1024]; };
constexpr int PROBE = 1024 - 32;
#define LSTRIDE 16
struct State {
    Twin ax[3];
    Twin hx;
    Twin ox[(OREP + 1) / 2];
    Twin lx;
    float4 oacc[NBH * 64];
    float2 attn[NB][DM];
    uint32_t fw_time[32];
    float2 lsum[NBH][LSTRIDE];
    uint32_t score[NPOOL][32];
};
__host__ __device__ constexpr int oidx(int row, int grp) {
    return (row >> 2) * 256 + ((row & 1) * 2 + (grp >> 5)) * 64 + (row & 2) * 16 + (grp & 31);
}
constexpr int STATE_V4 = ((sizeof(State) / 32 + NQ_CTAS - 1) / NQ_CTAS) * 2;
static_assert(sizeof(State) % 32 == 0, "State is cleared in whole sectors");
static_assert(sizeof(Early) == 64 * 16, "an Early entry is cleared by 64 threads");
struct Scratch {
    State st;
    unsigned work[64];
    unsigned cnt_z[32];
    Early early[NBH];
    alignas(4096) float4 ring[RING][UPB][64];
};
constexpr size_t PAGE = 2u << 20;
static_assert(sizeof(Scratch) <= PAGE, "scratch must fit one page");
__device__ __align__(128) unsigned char g_raw[2 * PAGE];
__device__ __forceinline__ Scratch* scratch() {
    return reinterpret_cast<Scratch*>((reinterpret_cast<uintptr_t>(g_raw) + PAGE - 1) & ~(uintptr_t)(PAGE - 1));
}
#define g_early scratch()->early
#define g_st scratch()->st
#define g_ring scratch()->ring
#define g_cnt_z scratch()->cnt_z
#define g_work scratch()->work
#define ALL_LOADERS 0
#define TS(i)
#define TSW(i)
#define TS2(i)
#define TSI(n, i)
#define PH(i)
#define CK(i, dep)
#define ARR()
#define PROG(u)

__device__ __forceinline__ uint32_t s2u(const void* p) { return (uint32_t)__cvta_generic_to_shared(p); }
__device__ __forceinline__ void mbar_init(uint32_t bar, int cnt) {
    asm volatile("mbarrier.init.shared::cta.b64 [%0], %1;" :: "r"(bar), "r"(cnt) : "memory");
}
__device__ __forceinline__ void mbar_wait(uint32_t bar, uint32_t parity) {
    asm volatile("{\n.reg .pred p;\n.reg .u32 n;\nmov.u32 n, 0;\nWAIT_LOOP:\n"
                 "mbarrier.try_wait.parity.shared::cta.b64 p, [%0], %1;\n"
                 "@p bra WAIT_DONE;\nadd.u32 n, n, 1;\nsetp.lt.u32 p, n, %2;\n@p bra WAIT_LOOP;\nWAIT_DONE:\n}"
                 :: "r"(bar), "r"(parity), "n"(SPIN_MAX) : "memory");
}
__device__ __forceinline__ void request_tile(uint32_t dst, const CUtensorMap* tm, int unit, uint32_t bar, uint64_t pol) {
    asm volatile("{\n.reg .pred p;\nelect.sync _|p, 0xffffffff;\n"
                 "@p mbarrier.arrive.expect_tx.shared::cta.b64 _, [%2], %6;\n"
                 "@p cp.async.bulk.tensor.2d.shared::cluster.global.mbarrier::complete_tx::bytes.L2::cache_hint "
                 "[%0], [%1, {%3, %4}], [%2], %5;\n}"
                 :: "r"(dst), "l"(tm), "r"(bar), "r"(0), "r"(unit * TILE_ROWS), "l"(pol), "n"(TILE_BYTES) : "memory");
}
__device__ __forceinline__ void put_groups(void* dst, int mode, const float (&o)[6], float tag, float tag2) {
    asm volatile("{\n.reg .pred s, t;\n.reg .b128 u, v;\n.reg .b64 a, b;\n"
                 "setp.eq.s32 s, %1, 0;\nsetp.ne.s32 t, %1, 2;\nxor.b64 a, %0, 4096;\n"
                 "@t bra.uni SINGLE;\n"
                 "red.relaxed.gpu.global.add.v4.f32 [a], {%2,%3,%4,%8};\n"
                 "red.relaxed.gpu.global.add.v4.f32 [a+128], {%5,%6,%7,%9};\n"
                 "SINGLE:\n"
                 "@s bra.uni STORE;\n"
                 "red.relaxed.gpu.global.add.v4.f32 [%0], {%2,%3,%4,%8};\n"
                 "red.relaxed.gpu.global.add.v4.f32 [%0+128], {%5,%6,%7,%9};\n"
                 "STORE:\n"
                 "mov.b64 a, {%2, %3};\nmov.b64 b, {%4, %8};\nmov.b128 u, {a, b};\n"
                 "mov.b64 a, {%5, %6};\nmov.b64 b, {%7, %9};\nmov.b128 v, {a, b};\n"
                 "@s st.relaxed.gpu.global.b128 [%0], u;\n@s st.relaxed.gpu.global.b128 [%0+128], v;\n}"
                 :: "l"(dst), "r"(mode), "f"(o[0]), "f"(o[1]), "f"(o[2]), "f"(o[3]), "f"(o[4]), "f"(o[5]), "f"(tag), "f"(tag2) : "memory");
}
__device__ __forceinline__ void request_box(uint32_t dst, const CUtensorMap* tm, int col, int row, uint32_t bar, uint32_t bytes) {
    asm volatile("{\n.reg .pred p, q;\nelect.sync _|p, 0xffffffff;\nsetp.ne.and.u32 q, %5, 0, p;\n"
                 "@q mbarrier.arrive.expect_tx.shared::cta.b64 _, [%2], %5;\n"
                 "@p cp.async.bulk.tensor.2d.shared::cluster.global.mbarrier::complete_tx::bytes [%0], [%1, {%3, %4}], [%2];\n}"
                 :: "r"(dst), "l"(tm), "r"(bar), "r"(col), "r"(row), "r"(bytes) : "memory");
}
__device__ __forceinline__ uint32_t lds32(uint32_t addr) {
    uint32_t v;
    asm volatile("ld.shared.u32 %0, [%1];" : "=r"(v) : "r"(addr) : "memory");
    return v;
}
__device__ __forceinline__ void ldsm4(uint32_t (&r)[4], uint32_t addr) {
    asm volatile("ldmatrix.sync.aligned.m8n8.x4.shared.b16 {%0,%1,%2,%3}, [%4];"
                 : "=r"(r[0]), "=r"(r[1]), "=r"(r[2]), "=r"(r[3]) : "r"(addr) : "memory");
}
__device__ __forceinline__ void ldsm4t(uint32_t (&r)[4], uint32_t addr) {
    asm volatile("ldmatrix.sync.aligned.m8n8.x4.trans.shared.b16 {%0,%1,%2,%3}, [%4];"
                 : "=r"(r[0]), "=r"(r[1]), "=r"(r[2]), "=r"(r[3]) : "r"(addr) : "memory");
}
__device__ __forceinline__ void mma16816(float (&c)[4], const uint32_t (&a)[4], uint32_t b0, uint32_t b1) {
    asm volatile("mma.sync.aligned.m16n8k16.row.col.f32.bf16.bf16.f32 {%0,%1,%2,%3}, {%4,%5,%6,%7}, {%8,%9}, {%0,%1,%2,%3};"
                 : "+f"(c[0]), "+f"(c[1]), "+f"(c[2]), "+f"(c[3])
                 : "r"(a[0]), "r"(a[1]), "r"(a[2]), "r"(a[3]), "r"(b0), "r"(b1));
}
struct Warm {
    float c[4] = {};
    __device__ __forceinline__ void operator()() {
        asm volatile("mma.sync.aligned.m16n8k8.row.col.f32.bf16.bf16.f32 {%0,%1,%2,%3}, {%4,%4}, {%4}, {%0,%1,%2,%3};"
                     : "+f"(c[0]), "+f"(c[1]), "+f"(c[2]), "+f"(c[3]) : "r"(0));
    }
    __device__ __forceinline__ void done(uint32_t scrap) {
        asm volatile("{\n.reg .pred p;\nsetp.gt.f32 p, %1, 0f3f800000;\n@p st.shared.f32 [%0], %1;\n}" :: "r"(scrap), "f"(c[0]) : "memory");
    }
};
__device__ __forceinline__ uint4 ld_relaxed_v4(const void* p) {
    uint4 v;
    asm volatile("ld.relaxed.gpu.global.v4.u32 {%0,%1,%2,%3}, [%4];" : "=r"(v.x), "=r"(v.y), "=r"(v.z), "=r"(v.w) : "l"(p) : "memory");
    return v;
}
__device__ __forceinline__ float4 ld_relaxed_f4(const void* p) {
    float4 v;
    asm volatile("ld.relaxed.gpu.global.v4.f32 {%0,%1,%2,%3}, [%4];" : "=f"(v.x), "=f"(v.y), "=f"(v.z), "=f"(v.w) : "l"(p) : "memory");
    return v;
}
__device__ __forceinline__ float2 ld_relaxed_f2(const void* p) {
    float2 v;
    asm volatile("ld.relaxed.gpu.global.v2.f32 {%0,%1}, [%2];" : "=f"(v.x), "=f"(v.y) : "l"(p) : "memory");
    return v;
}
__device__ __forceinline__ float4 ld_relaxed_b128(const void* p) {
    float4 v;
    asm volatile("{\n.reg .b128 t;\n.reg .b64 a, b;\nld.relaxed.gpu.global.b128 t, [%4];\nmov.b128 {a, b}, t;\n"
                 "mov.b64 {%0, %1}, a;\nmov.b64 {%2, %3}, b;\n}" : "=f"(v.x), "=f"(v.y), "=f"(v.z), "=f"(v.w) : "l"(p) : "memory");
    return v;
}
__device__ __forceinline__ void st_relaxed_b128(void* p, float x, float y, float z, float w) {
    asm volatile("{\n.reg .b128 t;\n.reg .b64 a, b;\nmov.b64 a, {%1, %2};\nmov.b64 b, {%3, %4};\nmov.b128 t, {a, b};\n"
                 "st.relaxed.gpu.global.b128 [%0], t;\n}" :: "l"(p), "f"(x), "f"(y), "f"(z), "f"(w) : "memory");
}
__device__ __forceinline__ unsigned ld_acquire(const unsigned* p) {
    unsigned v;
    asm volatile("ld.acquire.gpu.global.u32 %0, [%1];" : "=r"(v) : "l"(p) : "memory");
    return v;
}
__device__ __forceinline__ void st_relaxed(void* p, uint32_t v) {
    asm volatile("st.relaxed.gpu.global.u32 [%0], %1;" :: "l"(p), "r"(v) : "memory");
}
__device__ __forceinline__ void red_f2(float* p, float a, float b) {
    asm volatile("red.relaxed.gpu.global.add.v2.f32 [%0], {%1,%2};" :: "l"(p), "f"(a), "f"(b) : "memory");
}
__device__ __forceinline__ void draw(int& ticket, unsigned* ctr, bool pred) {
    asm volatile("{\n.reg .pred p;\nsetp.ne.u32 p, %2, 0;\n@p atom.relaxed.gpu.global.inc.u32 %0, [%1], 0x7fffffff;\n}"
                 : "+r"(ticket) : "l"(ctr), "r"((uint32_t)pred) : "memory");
}
__device__ __forceinline__ void red_release(unsigned* p) {
    asm volatile("red.release.gpu.global.add.u32 [%0], 1;" :: "l"(p) : "memory");
}
__device__ __forceinline__ uint32_t ld_relaxed_u32(const void* p) {
    uint32_t v;
    asm volatile("ld.relaxed.gpu.global.u32 %0, [%1];" : "=r"(v) : "l"(p) : "memory");
    return v;
}
__device__ __forceinline__ float rcp_approx(float v) {
    float r;
    asm("rcp.approx.ftz.f32 %0, %1;" : "=f"(r) : "f"(v));
    return r;
}
__device__ __forceinline__ float ex2_approx(float v) {
    float e;
    asm("ex2.approx.ftz.f32 %0, %1;" : "=f"(e) : "f"(v));
    return e;
}
__device__ __forceinline__ float sigmoid_approx(float v) { return rcp_approx(1.0f + ex2_approx(v * -1.4426950408889634f)); }
__device__ __forceinline__ float sqrt_approx(float v) {
    float r;
    asm("sqrt.approx.ftz.f32 %0, %1;" : "=f"(r) : "f"(v));
    return r;
}
__device__ __forceinline__ bool all(bool v) { return __all_sync(0xffffffffu, v); }
__device__ __forceinline__ void wait_count(const unsigned* p, unsigned target) {
#pragma unroll 1
    for (int it = 0; it < SPIN_MAX; it++) {
        if (all(ld_acquire(p) >= target)) break;
        __nanosleep(400);
    }
}
__device__ __forceinline__ float wait_sum(const void* p, float n, int nap = 0) {
    float2 v;
#pragma unroll 1
    for (int it = 0; it < SPIN_MAX; it++) {
        v = ld_relaxed_f2(p);
        if (all(v.y >= n)) break;
        if (all(v.y == 0.f)) __nanosleep(600);
        else if (nap) __nanosleep(nap);
    }
    return v.x;
}
__device__ __forceinline__ void wait_row(int bh, float n) { wait_sum(g_st.lsum[bh], n); }
__device__ __forceinline__ void wait_row_o(int bh, float n) {
    wait_row(bh, n);
    if (bh >= RED0) return;
#pragma unroll 1
    for (int it = 0; it < SPIN_MAX; it++) {
        if (all(__uint_as_float(ld_relaxed_u32(&g_st.oacc[oidx(bh, 0)].w)) == UPB)) break;
        __nanosleep(300);
    }
}
constexpr uint32_t SLOT_K = (uint32_t)(((1ull << 32) + SLOT_TICKS - 1) / SLOT_TICKS);
#define SLOT_ASM(t, n, p, phase, k, open) \
    "mov.u32 " n ", 0;\nSLOT:\nmov.u32 " t ", %%globaltimer_lo;\nadd.u32 " n ", " n ", 1;\nsetp.lt.u32 " p ", " n ", 24;\nshr.u32 " t ", " t ", 5;\n" \
    "mad.lo.u32 " t ", " t ", " k ", " phase ";\nsetp.ge.and.u32 " p ", " t ", " open ", " p ";\n@" p " bra.uni SLOT;\n"
template <int PHASE> __host__ __device__ constexpr uint32_t slot_phase() { return SLOT_K / 2 - PHASE * SLOT_K; }
template <int PHASE> __device__ __forceinline__ void wait_slot() {
    if (PHASE < 0) return;
    asm volatile("{\n.reg .pred p;\n.reg .b32 t, n;\n" SLOT_ASM("t", "n", "p", "%0", "%1", "%2") "}"
                 :: "n"(slot_phase<PHASE>()), "n"(SLOT_K), "n"(SLOT_OPEN * SLOT_K) : "memory");
}
__device__ __forceinline__ void wait_time(uint32_t t) {
#pragma unroll 1
    for (int it = 0; it < SPIN_MAX; it++) {
        uint32_t now;
        asm volatile("mov.u32 %0, %%globaltimer_lo;" : "=r"(now));
        if (all((int)(now - t) >= 0)) break;
    }
}
__device__ __forceinline__ void wait_clock(uint32_t t, Warm& warm) { while (!all((int)(clock() - t) >= 0)) { warm(); } }
__device__ __forceinline__ uint32_t pack_bf16(float lo, float hi) {
    uint32_t r;
    asm("cvt.rn.bf16x2.f32 %0, %1, %2;" : "=r"(r) : "f"(hi), "f"(lo));
    return r;
}
__device__ __forceinline__ float bf16r(float v) { return __uint_as_float(pack_bf16(0.f, v)); }
__device__ __forceinline__ uint32_t nonzero(uint32_t w) { return w ? w : 0x80008000u; }
__device__ __forceinline__ uint32_t pack_neg(float lo, float hi) { return nonzero(pack_bf16(-lo, -hi)); }
__device__ __forceinline__ float lo_f(uint32_t v) { return __uint_as_float(v << 16); }
__device__ __forceinline__ float hi_f(uint32_t v) { return __uint_as_float(v & 0xffff0000u); }
__device__ __forceinline__ float warp_sum(float v) {
#pragma unroll
    for (int o = 16; o; o >>= 1) v += __shfl_xor_sync(0xffffffffu, v, o);
    return v;
}
__device__ __forceinline__ void layernorm20(float (&v)[20]) {
    float s = 0.f;
#pragma unroll
    for (int i = 0; i < 20; i++) s += v[i];
    const float mean = warp_sum(s) * (1.0f / DM);
    float q = 0.f;
#pragma unroll
    for (int i = 0; i < 20; i++) { const float d = v[i] - mean; q += d * d; }
    const float var = bf16r(warp_sum(q) * (1.0f / DM));
    const float m = bf16r(mean);
    const float rden = 1.0f / bf16r(sqrtf(bf16r(var + 1e-5f)));
#pragma unroll
    for (int i = 0; i < 20; i++) v[i] = bf16r(bf16r(v[i] - m) * rden);
}

__device__ __forceinline__ void moments(float m1, float m2, float& nmean, float& rden) {
    m1 *= 1.0f / DM;
    const float var = bf16r(fmaxf(fmaf(-m1, m1, m2 * (1.0f / DM)), 0.f));
    nmean = bf16r(m1);
    rden = rcp_approx(bf16r(sqrt_approx(bf16r(var + 1e-5f))));
}
__device__ __forceinline__ float sel4(int j, float a, float b, float c, float d) {
    float lo, hi, r;
    asm("{\n.reg .pred p;\nsetp.ne.s32 p, %3, 0;\nselp.f32 %0, %2, %1, p;\n}" : "=f"(lo) : "f"(a), "f"(b), "r"(j & 1));
    asm("{\n.reg .pred p;\nsetp.ne.s32 p, %3, 0;\nselp.f32 %0, %2, %1, p;\n}" : "=f"(hi) : "f"(c), "f"(d), "r"(j & 1));
    asm("{\n.reg .pred p;\nsetp.ne.s32 p, %3, 0;\nselp.f32 %0, %2, %1, p;\n}" : "=f"(r) : "f"(lo), "f"(hi), "r"(j & 2));
    return r;
}
template <typename T> __device__ __forceinline__ void pin(T*& p) { asm volatile("" : "+l"(p)); }
__device__ __forceinline__ void pin(uint32_t& v) { asm volatile("" : "+r"(v)); }
__device__ __forceinline__ void pin(float& v) { asm volatile("" : "+f"(v)); }
__device__ __forceinline__ uint32_t after(uint32_t n, float v) {
    asm volatile("{\n.reg .pred p;\nsetp.eq.u32 p, %1, 0x7fc1a5a5;\n@p add.u32 %0, %0, 32;\n}" : "+r"(n) : "r"(__float_as_uint(v)));
    return n;
}
__device__ __forceinline__ float2 lds64f(uint32_t addr) {
    float2 v;
    asm volatile("ld.shared.v2.f32 {%0,%1}, [%2];" : "=f"(v.x), "=f"(v.y) : "r"(addr) : "memory");
    return v;
}
__device__ __forceinline__ void sts32f(uint32_t addr, float v) { asm volatile("st.shared.f32 [%0], %1;" :: "r"(addr), "f"(v) : "memory"); }
template <int ID> __device__ __forceinline__ void fin_arrive() { asm volatile("bar.arrive %0, 288;" :: "n"(ID) : "memory"); }
template <int ID> __device__ __forceinline__ void fin_sync() { asm volatile("bar.sync %0, 288;" :: "n"(ID) : "memory"); }
template <int ID> __device__ __forceinline__ void fin_sync(uint32_t n) { asm volatile("bar.sync %0, %1;" :: "n"(ID), "r"(n) : "memory"); }
__device__ __forceinline__ float2 sum8(uint32_t addr, int pitch) {
    float2 t[8];
#pragma unroll
    for (int w = 0; w < 8; w++) t[w] = lds64f(addr + w * pitch);
    return make_float2(((t[0].x + t[1].x) + (t[2].x + t[3].x)) + ((t[4].x + t[5].x) + (t[6].x + t[7].x)),
                       ((t[0].y + t[1].y) + (t[2].y + t[3].y)) + ((t[4].y + t[5].y) + (t[6].y + t[7].y)));
}
__device__ __forceinline__ float4 sum4x4(uint32_t addr, int pitch) {
    float4 t[4];
#pragma unroll
    for (int w = 0; w < 4; w++)
        asm volatile("ld.shared.v4.f32 {%0,%1,%2,%3}, [%4];" : "=f"(t[w].x), "=f"(t[w].y), "=f"(t[w].z), "=f"(t[w].w) : "r"(addr + w * pitch) : "memory");
    return make_float4((t[0].x + t[1].x) + (t[2].x + t[3].x), (t[0].y + t[1].y) + (t[2].y + t[3].y),
                       (t[0].z + t[1].z) + (t[2].z + t[3].z), (t[0].w + t[1].w) + (t[2].w + t[3].w));
}
__device__ __forceinline__ void sts64f(uint32_t addr, float x, float y) {
    asm volatile("st.shared.v2.f32 [%0], {%1,%2};" :: "r"(addr), "f"(x), "f"(y) : "memory");
}
__device__ __forceinline__ void lds128_if(uint4& v, uint32_t addr, bool pred) {
    asm volatile("{\n.reg .pred p;\nsetp.ne.u32 p, %5, 0;\n@p ld.shared.v4.u32 {%0,%1,%2,%3}, [%4];\n}"
                 : "+r"(v.x), "+r"(v.y), "+r"(v.z), "+r"(v.w) : "r"(addr), "r"((uint32_t)pred) : "memory");
}
__device__ __forceinline__ void ld_relaxed_v4_if(uint4& v, const void* p, bool pred) {
    asm volatile("{\n.reg .pred p;\nsetp.ne.u32 p, %5, 0;\n@p ld.relaxed.gpu.global.v4.u32 {%0,%1,%2,%3}, [%4];\n}"
                 : "+r"(v.x), "+r"(v.y), "+r"(v.z), "+r"(v.w) : "l"(p), "r"((uint32_t)pred) : "memory");
}
__device__ __forceinline__ void sts128f(uint32_t addr, float x, float y, float z, float w) {
    asm volatile("st.shared.v4.f32 [%0], {%1,%2,%3,%4};" :: "r"(addr), "f"(x), "f"(y), "f"(z), "f"(w) : "memory");
}
template <int NJ>
__device__ __forceinline__ void load_o(uint32_t (&ob)[3 * NJ][2], int bh, int J0, int j) {
    float4 v[NJ][4];
    float2 l;
#pragma unroll 1
    for (int it = 0; it < SPIN_MAX; it++) {
#pragma unroll
        for (int J = 0; J < NJ; J++) {
#pragma unroll
            for (int e = 0; e < 4; e++) v[J][e] = ld_relaxed_f4(&g_st.oacc[oidx(bh, j)] + oidx(0, (J0 + J) * 16 + e * 4));
        }
        l = ld_relaxed_f2(g_st.lsum[bh]);
        bool ok = l.y == UPB;
#pragma unroll
        for (int J = 0; J < NJ; J++) {
#pragma unroll
            for (int e = 0; e < 4; e++) ok &= v[J][e].w == UPB;
        }
        if (all(ok)) break;
    }
    const float rl = __fdividef(1.0f, l.x);
#pragma unroll
    for (int J = 0; J < NJ; J++) {
        ob[3 * J][0] = pack_bf16(v[J][0].x * rl, v[J][1].x * rl);     ob[3 * J][1] = pack_bf16(v[J][2].x * rl, v[J][3].x * rl);
        ob[3 * J + 1][0] = pack_bf16(v[J][0].y * rl, v[J][1].y * rl); ob[3 * J + 1][1] = pack_bf16(v[J][2].y * rl, v[J][3].y * rl);
        ob[3 * J + 2][0] = pack_bf16(v[J][0].z * rl, v[J][1].z * rl); ob[3 * J + 2][1] = pack_bf16(v[J][2].z * rl, v[J][3].z * rl);
    }
}
__device__ __forceinline__ int near_side(uint32_t sb) {
    uint32_t v;
    asm volatile("ld.volatile.shared.u32 %0, [%1];" : "=r"(v) : "r"(sb + SM_SIDE) : "memory");
    return v;
}
__device__ __forceinline__ void poll_row(uint4& a, uint4& b, uint2& c, const void* pa, const void* pb, const void* pc, uint32_t sa, uint32_t sc,
                                         bool arrive, bool nap, uint32_t bar, Warm& warm) {
    asm volatile("{\n.reg .pred p, q, r, s;\n.reg .b32 m, n, it;\n"
                 "setp.ne.u32 r, %19, 0;\nsetp.ne.u32 s, %20, 0;\nmov.u32 it, 0;\n"
                 "POLL:\n"
                 SLOT_ASM("m", "n", "p", "%23", "%24", "%25")
                 "ld.relaxed.gpu.global.v4.u32 {%0,%1,%2,%3}, [%14];\n"
                 "ld.relaxed.gpu.global.v4.u32 {%4,%5,%6,%7}, [%15];\n"
                 "ld.relaxed.gpu.global.v2.u32 {%8,%9}, [%16];\n"
                 "add.u32 it, it, 1;\nsetp.ge.u32 q, it, %21;\n"
                 "mov.u32 m, 0;\nmma.sync.aligned.m16n8k8.row.col.f32.bf16.bf16.f32 {%10,%11,%12,%13}, {m,m}, {m}, {%10,%11,%12,%13};\n"
                 "st.shared.v4.u32 [%17], {%0,%1,%2,%3};\n"
                 "st.shared.v4.u32 [%17+512], {%4,%5,%6,%7};\n"
                 "st.shared.v2.u32 [%18], {%8,%9};\n"
                 "min.u32 m, %0, %1;\nmin.u32 m, m, %2;\nmin.u32 n, %3, %4;\nmin.u32 n, n, %5;\nmin.u32 m, m, %6;\nmin.u32 m, m, %7;\n"
                 "min.u32 n, n, m;\nmin.u32 m, %8, %9;\nmin.u32 m, m, n;\n"
                 "setp.ne.or.u32 p, m, 0, q;\n"
                 "vote.sync.all.pred p, p, 0xffffffff;\n"
                 "and.pred q, p, r;\n"
                 "bar.warp.sync 0xffffffff;\n"
                 "@q mbarrier.arrive.shared::cta.b64 _, [%22];\n"
                 "@p bra.uni DONE;\n"
                 "@s nanosleep.u32 500;\n"
                 "bra.uni POLL;\n"
                 "DONE:\n}"
                 : "=&r"(a.x), "=&r"(a.y), "=&r"(a.z), "=&r"(a.w), "=&r"(b.x), "=&r"(b.y), "=&r"(b.z), "=&r"(b.w), "=&r"(c.x), "=&r"(c.y),
                   "+f"(warm.c[0]), "+f"(warm.c[1]), "+f"(warm.c[2]), "+f"(warm.c[3])
                 : "l"(pa), "l"(pb), "l"(pc), "r"(sa), "r"(sc), "r"((uint32_t)arrive), "r"((uint32_t)nap), "n"(SPIN_MAX), "r"(bar),
                   "n"(slot_phase<PH_H>()), "n"(SLOT_K), "n"(SLOT_OPEN * SLOT_K) : "memory");
}
__device__ __forceinline__ void aux_sync() { asm volatile("bar.sync 1, 256;" ::: "memory"); }

__global__ void __launch_bounds__(NTHREADS, 1)
fused_decode_kernel(const __grid_constant__ Params p) {
    extern __shared__ __align__(1024) unsigned char smem[];
    const uint32_t sb = s2u(smem);
    const int tid = threadIdx.x, cta = blockIdx.x;
    if (tid < 32 && cta < NQ_CTAS) {
        asm volatile("{\n.reg .pred p;\nelect.sync _|p, 0xffffffff;\n"
                     "@p mbarrier.init.shared::cta.b64 [%2], 1;\n"
                     "@p fence.mbarrier_init.release.cluster;\n"
                     "@p mbarrier.arrive.expect_tx.shared::cta.b64 _, [%2], 15360;\n"
                     "@p cp.async.bulk.tensor.2d.shared::cluster.global.mbarrier::complete_tx::bytes [%0], [%1, {%3, %4}], [%2];\n"
                     "@p mbarrier.init.shared::cta.b64 [%2+8], 1;\n@p mbarrier.init.shared::cta.b64 [%2+16], 1;\n"
                     "@p mbarrier.init.shared::cta.b64 [%2+24], 1;\n"
                     "@p fence.mbarrier_init.release.cluster;\n"
                     "@p mbarrier.arrive.expect_tx.shared::cta.b64 _, [%2+8], 15360;\n"
                     "@p cp.async.bulk.tensor.2d.shared::cluster.global.mbarrier::complete_tx::bytes [%0+15360], [%1, {%3, %5}], [%2+8];\n"
                     "@p mbarrier.arrive.expect_tx.shared::cta.b64 _, [%2+16], 15360;\n"
                     "@p cp.async.bulk.tensor.2d.shared::cluster.global.mbarrier::complete_tx::bytes [%0+30720], [%1, {%3, %6}], [%2+16];\n"
                     "@p mbarrier.arrive.expect_tx.shared::cta.b64 _, [%2+24], 15360;\n"
                     "@p cp.async.bulk.tensor.2d.shared::cluster.global.mbarrier::complete_tx::bytes [%0+46080], [%1, {%3, %7}], [%2+24];\n}"
                     :: "r"(sb + SM_W), "l"(&p.wq), "r"(sb + BAR_WQ), "r"(cta * 48), "r"(0), "r"(160), "r"(320), "r"(480) : "memory");
    }
    const int warp = __shfl_sync(0xffffffffu, tid >> 5, 0), lane = tid & 31;
    constexpr int grid = NCTAS;
    const int g = lane >> 2, j = lane & 3;
    uint32_t t_start;
    asm volatile("mov.u32 %0, %%globaltimer_lo;" : "=r"(t_start));
    TS(0);
    if (tid == 32) {
        mbar_init(sb + BAR_WO, 1);
        mbar_init(sb + BAR_H, 1);
#pragma unroll
        for (int i = 0; i < 8 + NWORK; i++) mbar_init(sb + BAR_FW + i * 8, 1);
        sts32f(sb + SM_SIDE, 0.f);
        asm volatile("fence.mbarrier_init.release.cluster;" ::: "memory");
        asm volatile("fence.proxy.async.shared::cta;" ::: "memory");
    }
    __syncthreads();
    if (warp >= NAUX + NWORK) {
        const int fw = warp - (NAUX + NWORK), fi = ffn_slice(cta);
        if (fw == 0) {
            if (cta < NQ_CTAS) {
#pragma unroll
                for (int i = lane; i < STATE_V4; i += 32)
                    if (cta * STATE_V4 + i < (int)(sizeof(State) / 16)) reinterpret_cast<uint4*>(&g_st)[cta * STATE_V4 + i] = make_uint4(0u, 0u, 0u, 0u);
                __syncwarp();
                if (lane == 0) red_release(g_cnt_z);
            }
            TSW(2); wait_count(g_cnt_z, NQ_CTAS); TSW(29);
            asm volatile("bar.arrive 2, %0;" :: "n"((NWORK + 2) * 32) : "memory");
            fin_arrive<3>();
        } else {
#pragma unroll 1
            for (int n = cta < NE_CTAS ? 5 : 4, i = n - 1; i >= 0; i--) {
                const int head = cta < NE_CTAS ? cta >> 2 : 28 + i;
                wait_time(t_start + WO_AT_NS + (NH - 1 - head) * WO_STEP_NS);
                request_box(sb + SM_A + i * 12288, &p.wo, cta < NE_CTAS ? (cta & 3) * 160 + i * 32 : (cta - NE_CTAS) * 32,
                            head * DH, sb + BAR_WO, i == n - 1 ? n * 12288 : 0);
            }
            asm volatile("bar.sync 2, %0;" :: "n"((NWORK + 2) * 32) : "memory");
            uint32_t best[2] = {~0u, ~0u};
#pragma unroll 1
            for (int i = 0; i < NPROBE; i++) {
#pragma unroll
                for (int c = 0; c < 2; c++) {
                    uint32_t t0 = clock(), t1 = t0;
                    int v = 0;
                    draw(v, &g_st.hx.w[c][PROBE], lane == 0);
                    asm volatile("{\n.reg .pred p;\nsetp.ne.u32 p, %1, 0xffffffff;\n@p mov.u32 %0, %%clock;\n}" : "+r"(t1) : "r"(v) : "memory");
                    best[c] = min(best[c], t1 - t0);
                }
                __nanosleep(1000);
            }
            if (lane == 0) sts32f(sb + SM_SIDE, __uint_as_float(best[1] < best[0]));
        }
        int job = cta;
        auto sum_rows = [&](int row_end) {
#pragma unroll 1
            for (; job < 8 * min(row_end, RED0); job += NCTAS) {
                const int row = job >> 3, grp = (job & 7) * 8 + (lane & 7);
                wait_row(row, UPB);
                const float4* src = &g_ring[row % RING][lane >> 3][grp];
                float sx = 0.f, sy = 0.f, sz = 0.f;
#pragma unroll 1
                for (int i = 0; i < 2; i++, src += 64 * 64) {
                    float4 v[16];
#pragma unroll 1
                    for (int it = 0; it < SPIN_MAX; it++) {
                        bool ok = true;
#pragma unroll
                        for (int k = 0; k < 16; k++) v[k] = ld_relaxed_b128(src + k * 4 * 64);
#pragma unroll
                        for (int k = 0; k < 16; k++) ok &= v[k].w == (float)(row + 1);
                        if (all(ok)) break;
                    }
#pragma unroll
                    for (int k = 0; k < 16; k++) { sx += v[k].x; sy += v[k].y; sz += v[k].z; }
                }
#pragma unroll
                for (int o = 8; o < 32; o <<= 1) {
                    sx += __shfl_xor_sync(0xffffffffu, sx, o); sy += __shfl_xor_sync(0xffffffffu, sy, o); sz += __shfl_xor_sync(0xffffffffu, sz, o);
                }
                if (lane < 8) st_relaxed_b128(&g_st.oacc[oidx(row, grp)], sx, sy, sz, UPB);
            }
        };
        const int ho0 = lane / 20 * 256 + lane % 20 * 4, ho1 = (lane + 32) / 20 * 256 + (lane + 32) % 20 * 4, ho2 = 3 * 256 + 16 + 2 * lane;
        uint32_t wr[10] = {};
        float wsum = 0.f;
        if (is_g(cta) && fw == 0) {
#pragma unroll
            for (int i = 0; i < 10; i++) {
                const int w = 4 * lane + 128 * (i >> 2) + (i & 3) - (i >= 8 ? 2 * lane : 0);
                wr[i] = *reinterpret_cast<const uint32_t*>(p.wr + (w >> 4) * 32 + (w & 3) * 8 + ((w >> 1) & 6));
                wsum += lo_f(wr[i]) + hi_f(wr[i]);
            }
            wsum = warp_sum(wsum);
        }
        const int fb = lane >> 3, fg = lane & 7;
        if (fw == 0) {
#pragma unroll
            for (int i = lane; i < DM / 2; i += 32) sts32f(sb + SM_X + 4 * HPITCH + i * 4, __uint_as_float(0x3f803f80u));
        }
        Warm warm;
        float nmean = 0.f, rden = 0.f, sig = 0.f;
#pragma unroll 1
        for (int b = 0; b < NB; b++) {
            const bool ffn = b >= NB - 2;
            if (fw == 0) {
                sum_rows((b + 1) * NH);
                if (ffn) asm volatile("bar.arrive 8, 64;" ::: "memory");
            } else if (ffn) {
                asm volatile("bar.sync 8, 64;" ::: "memory");
                if (b == NB - 1 && (is_f(cta) || is_g(cta) || ALL_LOADERS)) {
                    uint32_t t0 = 0;
#pragma unroll 1
                    for (int it = 0; it < SPIN_MAX; it++) {
                        t0 = ld_relaxed_u32(g_st.fw_time);
                        if (all(t0 != 0)) break;
                        __nanosleep(150);
                    }
                    asm volatile("fence.proxy.async.shared::cta;" ::: "memory");
                    wait_time(t0 + FW_AT_NS);
                    TSW(9);
                    uint32_t t = clock() + (is_f(cta) ? ((fi & 1) * 24 + (fi >> 1)) * FW_GAP / 48 : FW_MID + ((fi & 3) * 10 + (fi >> 2)) * FW_GAP2 / 40);
#pragma unroll 1
                    for (int i = 0; i < 8; i++) {
                        const uint32_t bar = sb + BAR_FW + i * 8;
                        if (is_f(cta)) {
                            wait_clock(t, warm);
                            request_box(sb + SM_W + i * 10240, (i & 1) ? &p.wu : &p.wg, fi * 32, (i >> 1) * 160, bar, 10240);
                            t += FW_GAP;
                        } else if (is_g(cta)) {
                            wait_clock(t, warm);
                            asm volatile("{\n.reg .pred p;\nelect.sync _|p, 0xffffffff;\n"
                                         "@p mbarrier.arrive.expect_tx.shared::cta.b64 _, [%2], 6144;\n"
                                         "@p cp.async.bulk.tensor.4d.shared::cluster.global.mbarrier::complete_tx::bytes [%0], [%1, {%3, %4, %4, %5}], [%2];\n}"
                                         :: "r"(sb + SM_W + i * 6144), "l"(&p.wd), "r"(bar), "r"(fi * 16), "r"(0), "r"(i * 12) : "memory");
                            t += FW_GAP2;
                        }
                    }
                }
                if (is_f(cta)) {
                    const uint32_t* src = &g_st.hx.w[near_side(sb)][min(fb, b) * 256 + 96];
                    float4 m;
#pragma unroll 1
                    for (int it = 0; it < SPIN_MAX; it++) {
                        wait_slot<PH_M>();
                        m = ld_relaxed_f4(src);
                        warm();
                        if (all(m.y + m.w == 2 * (NCTAS - NE_CTAS))) break;
                        if (b < NB - 1) __nanosleep(500);
                    }
                    moments(m.x, m.z, m.x, m.z);
                    sts64f(sb + SM_RED + 5120 + fb * 8, m.x, m.z);
                }
            }
            if (fw == 0 && cta >= NE_CTAS) {
                const int lc = cta - NE_CTAS, col = lc * 32 + 2 * (lane & 15);
                const uint32_t xv = *reinterpret_cast<const uint32_t*>(p.x + b * DM + col);
                uint32_t* dst = &(ffn ? g_st.hx.w : g_st.lx.w + 2)[lane >> 4][(b & 1) * 128 + lc / 5 * 256 + lc % 5 * 16 + (col & 6) * 2 + ((col >> 3) & 3)];
                uint32_t part = sb + SM_RED + (lane & 15) * 8;
                wait_row(b * NH + 28, 1);
                float4 early;
#pragma unroll 1
                for (int it = 0; it < SPIN_MAX; it++) {
                    early = ld_relaxed_f4(&g_st.attn[b][col]);
                    if (all(early.y == NE_CTAS / 4 && early.w == NE_CTAS / 4)) break;
                }
                if (early.x != 1.2345f && lane == 0) TS2(6);
                CK(1, __float_as_uint(early.x));
                const float x0 = -(lo_f(xv) + early.x), x1 = -(hi_f(xv) + early.z);
                fin_sync<4>(after(after(288, x0), x1));
                CK(2, lds32(sb + SM_RED));
                const float2 late = sum8(part, 128);
                const uint32_t hv = nonzero(pack_bf16(x0 - late.x, x1 - late.y));
                st_relaxed(dst, hv);
                if (ffn) st_relaxed(dst + 2048, hv);
                CK(3, 0);
                float m = lane < 16 ? lo_f(hv) + hi_f(hv) : fmaf(lo_f(hv), lo_f(hv), hi_f(hv) * hi_f(hv));
#pragma unroll
                for (int o = 1; o < 16; o <<= 1) m += __shfl_xor_sync(0xffffffffu, m, o);
                if ((lane & 14) == 0) red_f2(reinterpret_cast<float*>(&g_st.hx.w[lane & 1][b * 256 + 96 + (lane >> 4) * 2]), m, 1.f);
                fin_arrive<5>();
            }
            if (fw == 0 && (is_g(cta) || is_f(cta))) {
                const uint32_t* src = &(ffn ? g_st.hx.w : g_st.lx.w + 2)[near_side(sb) ^ (ffn && is_g(cta) ? 3 : 0)][(b & 1) * 128];
                const uint32_t hrow = sb + SM_X + b * HPITCH;
                wait_sum(b == NB - 1 ? (const void*)&g_st.lx.w[near_side(sb) ^ 1][3 * 256] : g_st.lsum[b * NH + NH - 1], UPB, 100);
                wait_clock(clock() + HGATE_NS * 2, warm);
                uint4 h0, h1;
                uint2 h2;
                poll_row(h0, h1, h2, src + ho0, src + ho1, src + ho2, hrow + lane * 16, hrow + 1024 + lane * 8, ffn && lane == 0, b < NB - 1, sb + BAR_H, warm);
                CK(4, h0.x);
                if (is_g(cta)) {
                    const uint32_t hw[10] = {h0.x, h0.y, h0.z, h0.w, h1.x, h1.y, h1.z, h1.w, h2.x, h2.y};
                    float m1 = 0.f, m2 = 0.f, rr = 0.f;
#pragma unroll
                    for (int i = 0; i < 10; i++) {
                        const float v0 = lo_f(hw[i]), v1 = hi_f(hw[i]);
                        m1 += v0 + v1;
                        m2 = fmaf(v0, v0, fmaf(v1, v1, m2));
                        rr = fmaf(v0, lo_f(wr[i]), fmaf(v1, hi_f(wr[i]), rr));
                    }
                    moments(warp_sum(m1), warp_sum(m2), m1, m2);
                    const float sg = bf16r(sigmoid_approx(bf16r((m1 * wsum - warp_sum(rr)) * m2)));
                    if (fb == b) { nmean = m1; rden = m2; sig = sg; }
                    __syncwarp();
                    if (ffn) {
                        const int yj = 2 * (fb & 1) + (fb >> 1);
                        uint32_t ypart = sb + SM_RED2 + yj * 128 + ((fg + 2 * yj) & 7) * 16;
                        __nv_bfloat16* out = p.out + fb * DM + fi * 16 + fg;
                        const float2 hw2 = lds64f(sb + SM_X + fb * HPITCH + ((fi >> 1) * 16 + (fg & 6) * 2 + (fi & 1) * 2) * 4);
                        const uint32_t w0 = __float_as_uint(hw2.x), w1 = __float_as_uint(hw2.y);
                        const float nh0 = (fg & 1) ? hi_f(w0) : lo_f(w0), nh1 = (fg & 1) ? hi_f(w1) : lo_f(w1);
                        const float ln0 = bf16r(bf16r(nmean - nh0) * rden) - nh0, ln1 = bf16r(bf16r(nmean - nh1) * rden) - nh1;
                        pin(ypart); pin(out);
                        fin_sync<6>(after(after(after(288, sig), ln0), ln1));
                        CK(10, lds32(ypart));
                        const float4 ya = sum4x4(ypart, 512), yb = sum4x4(ypart + 2048, 512);
                        const float4 y = make_float4(ya.x + yb.x, ya.y + yb.y, ya.z + yb.z, ya.w + yb.w);
                        const float y0 = -(((fb & 1) ? y.y : y.x) + __shfl_xor_sync(0xffffffffu, (fb & 1) ? y.x : y.y, 8));
                        const float y1 = -(((fb & 1) ? y.w : y.z) + __shfl_xor_sync(0xffffffffu, (fb & 1) ? y.z : y.w, 8));
                        const uint32_t ov = pack_bf16(fmaf(y0, sig, ln0), fmaf(y1, sig, ln1));
                        if (b == NB - 1) {
                            asm volatile("st.global.u16 [%0], %1;" :: "l"(out), "h"((unsigned short)(ov & 0xffffu)) : "memory");
                            asm volatile("st.global.u16 [%0], %1;" :: "l"(out + 8), "h"((unsigned short)(ov >> 16)) : "memory");
                        }
                        CK(11, 0);
                        if (lane == 0) TS2(13);
                    }
                }
            }
            if (is_f(cta) && ffn) {
                const int ks = (2 * fi + fw) % 12;
                const int far = near_side(sb) ^ 1;
                uint32_t* dst = &g_st.ax[ks >> 2].w[(~b & 1) * 2 + far][(fi / 6) * 128 + (ks & 3) * 32 + fb * 8 + (fg & 1) * 4 + ((fg >> 1) ^ (ks & 1))];
                uint32_t* dst2 = dst + (far ? -1024 : 1024);
                uint32_t part = sb + SM_RED + fw * 2560 + fb * 128 + ((fg + (fb & 2)) & 7) * 16;
                uint32_t psum = sb + SM_RED + fw * 2560 + 4 * 128 + ((fg + 4) & 7) * 16;
                pin(dst); pin(part); pin(psum);
                asm volatile("bar.sync 4, 320;" ::: "memory");
                CK(6, lds32(part));
                const float4 d = sum4x4(part, 640), cs = sum4x4(psum, 640);
                const float2 mo = lds64f(sb + SM_RED + 5120 + fb * 8);
                nmean = mo.x; rden = mo.y;
                const float g0 = fmaf(nmean, cs.x, -d.x), g1 = fmaf(nmean, cs.y, -d.y), ke = rden * -1.4426950408889634f, r2 = rden * rden;
                const float p0 = g0 * fmaf(-nmean, cs.z, d.z) * r2, p1 = g1 * fmaf(-nmean, cs.w, d.w) * r2;
                const uint32_t av = nonzero(pack_bf16(p0 * rcp_approx(1.0f + ex2_approx(g0 * ke)), p1 * rcp_approx(1.0f + ex2_approx(g1 * ke))));
                st_relaxed(dst, av);
                st_relaxed(dst2, av);
                CK(7, 0);
            }
        }
        warm.done(sb + SM_SCRAP);
        if (cta == 0 && tid == (NAUX + NWORK) * 32) { g_work[0] = 0; g_work[32] = 0; g_cnt_z[0] = 0; }
        return;
    }
    if (warp >= NAUX) {
        const int wk = warp - NAUX;
        const uint32_t bar = sb + BAR_KV + wk * 8;
        const uint32_t buf = sb + SM_KV + wk * TILE_BYTES;
        uint64_t pol;
        asm volatile("createpolicy.fractional.L2::evict_first.b64 %0, 1.0;" : "=l"(pol));
        const int nstatic = NWORK * grid;
        constexpr int POOL0 = NUNITS - NPOOL;
        int uk = wk * grid + cta;
        wait_time(t_start + K0_AT_NS + uk * KSWEEP_NS / nstatic);
        request_tile(buf, &p.k, uk, bar, pol);
        uint32_t koff[3], voff[3];
        {
            const int r = lane & 7, hf = (lane >> 3) & 1;
            const int kkey = hf ? 8 + (r ^ 1) : r;
            const int vh = lane >> 4;
            const int vkey = ((r & 1) ? 8 : 0) + (vh ? (r ^ 1) : r);
#pragma unroll
            for (int b = 0; b < 3; b++) {
                const int rk = 3 * kkey + b, rv = 3 * vkey + b;
                koff[b] = buf + rk * 128 + (((lane >> 4) ^ (rk & 7)) << 4);
                voff[b] = buf + rv * 128 + ((hf ^ (rv & 7)) << 4);
            }
        }
        uint32_t phase = 0;
        uint32_t qf[12][2];
        auto load_q = [&](int u) {
            const uint32_t* q = g_early[u / UPB].q[0][j];
#pragma unroll
            for (int i = 0; i < 4; i++) {
                const uint4 a = ld_relaxed_v4(q + i * 32);
                const float2 c = ld_relaxed_f2(q + i * 32 + 4);
                qf[3 * i][0] = a.x; qf[3 * i][1] = a.y; qf[3 * i + 1][0] = a.z; qf[3 * i + 1][1] = a.w;
                qf[3 * i + 2][0] = __float_as_uint(c.x); qf[3 * i + 2][1] = __float_as_uint(c.y);
            }
        };
        load_q(uk);
        int uq[LAG];
        uint32_t sq[LAG];
#pragma unroll
        for (int i = 0; i < LAG; i++) { uq[i] = -1; sq[i] = 0; }
        uint4 mv = make_uint4(0u, 0u, 0u, 0u);
        float freed = UPB;
        while (true) {
            const int uv = uq[0];
            uint32_t sv = sq[0];
#pragma unroll
            for (int i = 0; i + 1 < LAG; i++) { uq[i] = uq[i + 1]; sq[i] = sq[i + 1]; }
            uq[LAG - 1] = uk;
            if (uk < NUNITS) {
                PH(7);
#pragma unroll 1
                for (int it = 0; it < SPIN_MAX; it++) {
                    uint32_t lo = 0xffffffffu;
#pragma unroll
                    for (int i = 0; i < 12; i++) lo = min(lo, min(qf[i][0], qf[i][1]));
                    if (all(lo != 0)) break;
                    __nanosleep(250);
                    load_q(uk);
                }
                mbar_wait(bar, phase); phase ^= 1;
                PH(0); ARR();
                TSI(0, 16); TSI(1, 18);
                float acc[2][4][4] = {};
#pragma unroll
                for (int ks = 0; ks < 12; ks++) {
#pragma unroll
                    for (int mt = 0; mt < 4; mt++) {
                        uint32_t a[4];
                        ldsm4(a, (koff[ks >> 2] ^ ((ks & 3) << 5)) + mt * 6144);
                        mma16816(acc[ks & 1][mt], a, qf[ks][0], qf[ks][1]);
                    }
                }
                PH(1);
                TSI(0, 17); TSI(1, 19);
                if (uk < nstatic) wait_time(t_start + K1_AT_NS + uk * KSWEEP_NS / nstatic);
                if (uv < NUNITS) request_tile(buf, uv >= 0 ? &p.v : &p.k, uv >= 0 ? uv : uk + nstatic, bar, pol);
                const float sa = sel4(j, acc[0][0][0], acc[0][1][0], acc[0][2][0], acc[0][3][0]) + sel4(j, acc[1][0][0], acc[1][1][0], acc[1][2][0], acc[1][3][0]);
                const float sc = sel4(j, acc[0][0][2], acc[0][1][2], acc[0][2][2], acc[0][3][2]) + sel4(j, acc[1][0][2], acc[1][1][2], acc[1][2][2], acc[1][3][2]);
                const uint32_t raw = pack_bf16(sa, sc);
                const float scale = -0.07216878364870322f;
                const uint32_t sk = pack_bf16(lo_f(raw) * scale, hi_f(raw) * scale);
                sq[LAG - 1] = sk;
                if (uk >= POOL0) st_relaxed(&g_st.score[uk - POOL0][lane], sk ? sk : 0x80008000u);
                int a = (int)(sk << 16), b = (int)(sk & 0xffff0000u);
                a ^= (a >> 31) & 0x7fff0000; b ^= (b >> 31) & 0x7fff0000;
                const int mx = __reduce_max_sync(0xffffffffu, max(a, b));
                if (lane == 0) st_relaxed(&g_early[uk / UPB].umax[uk % UPB], (uint32_t)mx | 1u);
            }
            if (uv < 0) {
                uk += nstatic;
                load_q(uk);
                continue;
            }
            if (uv >= NUNITS) break;
            const int bh = uv / UPB;
#pragma unroll 1
            for (int it = 0; it < SPIN_MAX; it++) {
                if (all((mv.x & mv.y & mv.z & mv.w & 1u) && (uv < POOL0 || sv != 0) && freed == UPB)) break;
                mv = ld_relaxed_v4(&g_early[bh].umax[lane * 4]);
                if (bh >= RING && bh < RED0) freed = __uint_as_float(ld_relaxed_u32(&g_st.oacc[oidx(bh - RING, (lane & 7) * 8)].w));
                if (uv >= POOL0) sv = ld_relaxed_u32(&g_st.score[uv - POOL0][lane]);
            }
            PH(2);
            int un = NUNITS, vn = 0;
            draw(un, g_work, uk < NUNITS && lane == 0);
            uint32_t tdraw;
            asm volatile("mov.u32 %0, %%globaltimer_lo;" : "=r"(tdraw));
            draw(vn, g_work + 32, uq[0] >= POOL0 && lane == 0);
            int mx = __reduce_max_sync(0xffffffffu, max(max((int)mv.x, (int)mv.y), max((int)mv.z, (int)mv.w))) & 0xffff0000;
            mx ^= (mx >> 31) & 0x7fff0000;
            const float m = __int_as_float(mx);
            const float l2e = 1.4426950408889634f;
            const uint32_t pp = pack_bf16(exp2f((lo_f(sv) - m) * l2e), exp2f((hi_f(sv) - m) * l2e));
            uint32_t pb[8];
#pragma unroll
            for (int t = 0; t < 4; t++) {
                pb[2 * t] = __shfl_sync(0xffffffffu, pp, 8 * j + t);
                pb[2 * t + 1] = __shfl_sync(0xffffffffu, pp, 8 * j + 4 + t);
            }
            float lacc[4] = {};
            const uint32_t ones[4] = {0x3f803f80u, 0x3f803f80u, 0x3f803f80u, 0x3f803f80u};
#pragma unroll
            for (int t = 0; t < 4; t++) mma16816(lacc, ones, pb[2 * t], pb[2 * t + 1]);
            if (uv < nstatic) {
                asm volatile("bar.sync 2, %0;" :: "n"((NWORK + 2) * 32) : "memory");
                TSW(3);
            }
            const int grp = 16 * j + 4 * (g & 1) + (g >> 1);
            uint32_t mode = (bh >= RED0) + (bh >= NBH - 4);
            float tag = mode ? 1.f : (float)(bh + 1), tag2 = fmaf(__uint_as_float(voff[0]), 0.f, tag);
            void* dst = mode == 0 ? (void*)&g_ring[bh % RING][uv % UPB][grp] :
                        mode == 1 ? (void*)&g_st.oacc[oidx(bh, grp)] : (void*)&g_st.ox[0].w[uv % OREP * 2 + (~(near_side(sb) ^ uv % OREP) & 1)][oidx(bh & 3, grp) * 4];
            if (mode == 2 && lane < 2) red_f2(reinterpret_cast<float*>(&g_st.lx.w[lane][(bh & 3) * 256]), lacc[0], 1.f);
            un = __shfl_sync(0xffffffffu, un, 0) + (LAG + 1) * nstatic;
            vn = __shfl_sync(0xffffffffu, vn, 0);
            if (uq[0] >= POOL0) uq[0] = POOL0 + vn;
            if (vn == FW_TICKET && lane == 0) st_relaxed(g_st.fw_time, tdraw | 1u);
            if (uq[0] < NUNITS && un >= NUNITS) {
                mv = ld_relaxed_v4(&g_early[uq[0] / UPB].umax[lane * 4]);
                if (uq[0] < RED0 * UPB) freed = 0.f;
                if (uq[0] >= POOL0) sq[0] = ld_relaxed_u32(&g_st.score[uq[0] - POOL0][lane]);
            }
            pin(dst); pin(mode); pin(tag); pin(tag2); pin(voff[0]); pin(voff[1]); pin(voff[2]);
            PH(3);
            mbar_wait(bar, phase); phase ^= 1;
            PH(4); ARR(); CK(12, lds32(buf));
            float acc[12][4] = {};
#pragma unroll
            for (int t = 0; t < 4; t++) {
#pragma unroll
                for (int mt = 0; mt < 12; mt++) {
                    uint32_t a[4];
                    ldsm4t(a, (voff[mt >> 2] ^ ((mt & 3) << 5)) + t * 6144);
                    mma16816(acc[mt], a, pb[2 * t], pb[2 * t + 1]);
                }
            }
            PH(5);
            if (lane == 0) PROG(un);
            if (un < NUNITS || uq[0] < NUNITS) request_tile(buf, un < NUNITS ? &p.k : &p.v, un < NUNITS ? un : uq[0], bar, pol);
            if (un < NUNITS || uq[0] < NUNITS) CK(11, 0);
            float o[6];
#pragma unroll
            for (int e = 0; e < 6; e++) {
                const int q = e % 3, c = (e / 3) * 2;
                o[e] = sel4(j, acc[q][c], acc[3 + q][c], acc[6 + q][c], acc[9 + q][c]);
            }
            put_groups(dst, mode, o, tag, tag2);
            CK(13, 0);
            if (un < NUNITS) load_q(un);
            if (lane == 0) red_f2(&g_st.lsum[bh][0].x, lacc[0], 1.f);
            PH(6);
            if (uq[0] >= NUNITS && un >= NUNITS) break;
            uk = un;
            if (uq[0] < NUNITS && un < NUNITS) {
                const int nb = uq[0] / UPB;
                mv = ld_relaxed_v4(&g_early[nb].umax[lane * 4]);
                freed = nb >= RING && nb < RED0 ? __uint_as_float(ld_relaxed_u32(&g_st.oacc[oidx(nb - RING, (lane & 7) * 8)].w)) : UPB;
                if (uq[0] >= POOL0) sq[0] = ld_relaxed_u32(&g_st.score[uq[0] - POOL0][lane]);
            }
        }
        TSW(4 + wk);
        return;
    }

    __nv_bfloat16* xs = reinterpret_cast<__nv_bfloat16*>(smem + SM_X);
    float* red = reinterpret_cast<float*>(smem + SM_RED);
    const int frow = (lane & 7) + ((lane >> 4) << 3), fcol = (lane >> 3) & 1;
    const uint32_t f64b = sb + (frow * 4 + (fcol ^ ((frow >> 1) & 3))) * 16;
    if (cta < NQ_CTAS) {
        TS(26);
        if (warp >= 4) {
            uint2 xr[5];
#pragma unroll
            for (int i = 0; i < 5; i++) xr[i] = *reinterpret_cast<const uint2*>(p.x + (warp - 4) * DM + i * 128 + lane * 4);
            float v[20];
#pragma unroll
            for (int i = 0; i < 5; i++) {
                v[4 * i] = lo_f(xr[i].x); v[4 * i + 1] = hi_f(xr[i].x); v[4 * i + 2] = lo_f(xr[i].y); v[4 * i + 3] = hi_f(xr[i].y);
            }
            layernorm20(v);
#pragma unroll
            for (int i = 0; i < 5; i++)
                *reinterpret_cast<uint2*>(xs + (warp - 4) * XPITCH + i * 128 + lane * 4) =
                    make_uint2(pack_bf16(v[4 * i], v[4 * i + 1]), pack_bf16(v[4 * i + 2], v[4 * i + 3]));
        }
        aux_sync();
        TS(27);
        mbar_wait(sb + BAR_WQ + (warp >> 1) * 8, 0);
        TS(1);
        const uint32_t xfrag = sb + SM_X + ((g & 3) * XPITCH + 2 * j) * 2;
        float acc[3][4] = {};
#pragma unroll
        for (int s = 0; s < 5; s++) {
            const int ks = warp * 5 + s;
            const uint32_t b0 = lds32(xfrag + ks * 32), b1 = lds32(xfrag + ks * 32 + 16);
            const int row = ks * 16 + frow;
#pragma unroll
            for (int mt = 0; mt < 3; mt++) {
                uint32_t a[4];
                ldsm4t(a, sb + SM_W + (row * 6 + 2 * mt + fcol) * 16);
                mma16816(acc[mt], a, b0, b1);
            }
        }
        if (j < 2) {
#pragma unroll
            for (int mt = 0; mt < 3; mt++) {
                *reinterpret_cast<float2*>(red + warp * 216 + mt * 72 + g * 4 + 2 * j) = make_float2(acc[mt][0], acc[mt][1]);
                *reinterpret_cast<float2*>(red + warp * 216 + mt * 72 + 36 + g * 4 + 2 * j) = make_float2(acc[mt][2], acc[mt][3]);
            }
        }
        aux_sync();
        if (warp < 4) {
            const float* src = red + min(g, 5) * 36 + warp * 8 + j;
            float s0 = 0.f, s1 = 0.f;
#pragma unroll
            for (int w = 0; w < 8; w++) { s0 += src[w * 216]; s1 += src[w * 216 + 4]; }
            st_relaxed(&g_early[j * NH + (cta >> 2)].q[cta & 3][warp][g], pack_neg(s0, s1));
        }
        TS(28);
    }
    fin_sync<3>();
    mbar_wait(sb + BAR_WO, 0);
    TS(7);
    uint32_t part = sb + SM_RED + (warp * 32 + 8 * j + g) * 4;

#pragma unroll 1
    for (int b = 0; b < NB; b++) {
        if (cta >= NE_CTAS) {
            uint32_t a[6][2][4];
#pragma unroll
            for (int s = 0; s < 6; s++) {
#pragma unroll
                for (int mt = 0; mt < 2; mt++) ldsm4t(a[s][mt], (f64b ^ (mt * 32)) + SM_A + (warp * 6 + s) * 1024);
            }
            const int bh = b * NH + 28 + (warp >> 1);
            const int side = near_side(sb) ^ 1;
            const void* osrc[OREP];
#pragma unroll
            for (int c = 0; c < OREP; c++)
                osrc[c] = b == NB - 1 ? (const void*)&g_st.ox[c >> 1].w[side ^ (c & 1) * 3][oidx(bh & 3, (warp & 1) * 32 + lane) * 4] : &g_st.oacc[oidx(bh, (warp & 1) * 32 + lane)];
            const void* lsrc = b == NB - 1 ? (const void*)&g_st.lx.w[side][(bh & 3) * 256] : g_st.lsum[bh];
            wait_row_o(bh, 1);
            const float rl = rcp_approx(wait_sum(lsrc, UPB)) * (b == NB - 1 ? 1.f : 1.f / OREP), full = b == NB - 1 ? UPB : UPB * OREP;
            float4 ov;
            float px, py, pz;
            Warm warm;
#pragma unroll 1
            for (int it = 0; it < SPIN_MAX; it++) {
                wait_slot<PH_O>();
                float4 oc[OREP];
#pragma unroll
                for (int c = 0; c < OREP; c++) oc[c] = ld_relaxed_f4(osrc[c]);
                warm();
                ov = oc[0];
#pragma unroll
                for (int c = 1; c < OREP; c++) { ov.x += oc[c].x; ov.y += oc[c].y; ov.z += oc[c].z; ov.w += oc[c].w; }
                ov.x *= rl; ov.y *= rl; ov.z *= rl;
                px = __shfl_xor_sync(0xffffffffu, ov.x, 4); py = __shfl_xor_sync(0xffffffffu, ov.y, 4); pz = __shfl_xor_sync(0xffffffffu, ov.z, 4);
                if (all(ov.w == full)) break;
            }
            CK(0, __float_as_uint(ov.x));
            if (ov.x != 1.2345f && warp == 7) TSW(14);
            const uint32_t w[3] = {pack_bf16(ov.x, px), pack_bf16(ov.y, py), pack_bf16(ov.z, pz)};
            float acc[2][2][4] = {};
#pragma unroll
            for (int s = 0; s < 6; s++) {
                const uint32_t b0 = __shfl_sync(0xffffffffu, w[s % 3], (s / 3) * 16 + j);
                const uint32_t b1 = __shfl_sync(0xffffffffu, w[s % 3], (s / 3) * 16 + 8 + j);
#pragma unroll
                for (int mt = 0; mt < 2; mt++) mma16816(acc[mt][s & 1], a[s][mt], b0, b1);
            }
            sts32f(part, sel4(j, acc[0][0][0] + acc[0][1][0], acc[0][0][2] + acc[0][1][2], acc[1][0][0] + acc[1][1][0], acc[1][0][2] + acc[1][1][2]));
            CK(1, 0);
            fin_arrive<4>();
            warm.done(sb + SM_SCRAP);
            fin_sync<5>();
            if (cta < NE_CTAS + 4 && tid < 64) reinterpret_cast<uint4*>(&g_early[b * NH + 28 + cta - NE_CTAS])[tid] = make_uint4(0u, 0u, 0u, 0u);
        } else {
            const int bh = b * NH + (cta >> 2);
            if (warp == 0) wait_row_o(bh, UPB);
            aux_sync();
            if (warp < 5) {
                uint32_t ob[12][2];
                load_o<4>(ob, bh, 0, j);
                float acc[2][2][4] = {};
#pragma unroll
                for (int ks = 0; ks < 12; ks++) {
#pragma unroll
                    for (int mt = 0; mt < 2; mt++) {
                        uint32_t a[4];
                        ldsm4t(a, (f64b ^ (mt * 32)) + SM_A + warp * 12288 + ks * 1024);
                        mma16816(acc[mt][ks & 1], a, ob[ks][0], ob[ks][1]);
                    }
                }
                red_f2(&g_st.attn[b][(cta & 3) * 160 + warp * 32 + 8 * j + g].x,
                       sel4(j, acc[0][0][0] + acc[0][1][0], acc[0][0][2] + acc[0][1][2], acc[1][0][0] + acc[1][1][0], acc[1][0][2] + acc[1][1][2]), 1.f);
                TS(8);
            } else if (warp > 5 && (cta & 3) == 0) {
                reinterpret_cast<uint4*>(&g_early[bh])[tid - 192] = make_uint4(0u, 0u, 0u, 0u);
            }
        }
        if (b < NB - 2) continue;

        if (is_f(cta)) {
            uint32_t ga[10][2][4];
            uint4 hv[5] = {};
            const uint32_t hfrag = sb + SM_X + min(g, 4) * HPITCH + ((warp >> 1) * 80 + 4 * j) * 4;
#pragma unroll
            for (int s = 0; s < 5; s++) lds128_if(hv[s], hfrag + s * 64, b == NB - 1);
            if (b == NB - 1) mbar_wait(sb + BAR_FW + warp * 8, 0);
            if (warp == 7) TSW(10);
            CK(12, lds32(sb + SM_W));
#pragma unroll
            for (int s = 0; s < 10; s++) {
#pragma unroll
                for (int mt = 0; mt < 2; mt++) ldsm4t(ga[s][mt], (f64b ^ (mt * 32)) + SM_W + (warp * 10 + s) * 1024);
            }
            const uint32_t gpart = sb + SM_RED + (warp >> 1) * 640 + j * 256 + ((g + 2 * j) & 7) * 16 + (warp & 1) * 8;
            mbar_wait(sb + BAR_H, b & 1);
#pragma unroll
            for (int s = 0; s < 5; s++) lds128_if(hv[s], hfrag + s * 64, g == b);
            CK(4, hv[0].x);
            float acc[2][2][4] = {};
#pragma unroll
            for (int s = 0; s < 10; s++) {
#pragma unroll
                for (int mt = 0; mt < 2; mt++)
                    mma16816(acc[mt][s & 1], ga[s][mt], (s & 1) ? hv[s >> 1].z : hv[s >> 1].x, (s & 1) ? hv[s >> 1].w : hv[s >> 1].y);
            }
#pragma unroll
            for (int mt = 0; mt < 2; mt++) {
                if (j < 3) sts64f(gpart + mt * 2560, acc[mt][0][0] + acc[mt][1][0], acc[mt][0][2] + acc[mt][1][2]);
                if (j < 2) sts64f(gpart + mt * 2560 + 128, acc[mt][0][1] + acc[mt][1][1], acc[mt][0][3] + acc[mt][1][3]);
            }
            CK(5, 0);
            asm volatile("bar.arrive 4, 320;" ::: "memory");
        } else if (is_g(cta)) {
            const uint32_t* asrc = &g_st.ax[0].w[(~b & 1) * 2 + near_side(sb)][warp * 128 + ((g >> 2) * 2 + (j >> 1)) * 32 + (g & 3) * 8 + (j & 1) * 4];
            const uint32_t ypart = sb + SM_RED2 + warp * 512 + j * 128 + ((g + 2 * j) & 7) * 16;
            uint32_t wb[12][4];
            uint4 va[3] = {};
            uint32_t lo[3] = {};
            auto ask = [&]() {
#pragma unroll
                for (int i = 0; i < 3; i++) ld_relaxed_v4_if(va[i], asrc + i * 4096, lo[i] == 0);
            };
            auto complete = [&]() {
#pragma unroll
                for (int i = 0; i < 3; i++) lo[i] = min(min(va[i].x, va[i].y), min(va[i].z, va[i].w));
                return all(min(lo[0], min(lo[1], lo[2])) != 0);
            };
            const int jj = (lane & 7) >> 1, q = jj >> 1, hi = lane >> 4;
            const uint32_t wsrc = sb + SM_W + warp * 6144 + q * 512 + ((hi ^ q) * 4 + (jj & 1) * 2 + (lane & 1)) * 32 + ((fcol ^ hi ^ q) << 4);
            mbar_wait(sb + BAR_H, b & 1);
            if (b == NB - 1) mbar_wait(sb + BAR_FW + warp * 8, 0);
            if (warp == 7) TSW(11);
            CK(13, lds32(sb + SM_W));
            ask();
#pragma unroll
            for (int s = 0; s < 12; s++) ldsm4t(wb[s], wsrc + (s >> 2) * 2048 + (s & 1) * 1024 + (s & 2) * 128);
            Warm warm;
            if (!complete()) {
#pragma unroll 1
                for (int it = 0; it < SPIN_MAX; it++) {
                    ask();
                    warm();
                    if (complete()) break;
                }
            }
            CK(8, va[0].x);
            if (va[0].x != 0x12345 && warp == 7) TSW(15);
            float acc[6][4] = {};
#pragma unroll
            for (int s = 0; s < 12; s++) {
                const uint4 v = va[s >> 2];
                mma16816(acc[s % 6], wb[s], (s & 2) ? v.z : v.x, (s & 2) ? v.w : v.y);
            }
            float y[4];
#pragma unroll
            for (int e = 0; e < 4; e++) y[e] = j < 2 ? (acc[0][e] + acc[2][e]) + acc[4][e] : (acc[1][e] + acc[3][e]) + acc[5][e];
            sts128f(ypart, y[0], y[1], y[2], y[3]);
            CK(9, 0);
            fin_arrive<6>();
            warm.done(sb + SM_SCRAP);
        }
    }
}

typedef CUresult (*EncodeFn)(CUtensorMap*, CUtensorMapDataType, cuuint32_t, void*, const cuuint64_t*, const cuuint64_t*,
                             const cuuint32_t*, const cuuint32_t*, CUtensorMapInterleave, CUtensorMapSwizzle,
                             CUtensorMapL2promotion, CUtensorMapFloatOOBfill);

CUtensorMap make_map(EncodeFn enc, void* ptr, uint64_t cols, uint64_t rows, uint32_t bcols, uint32_t brows,
                     CUtensorMapSwizzle sw, CUtensorMapL2promotion promo) {
    CUtensorMap m;
    const cuuint64_t dims[2] = {cols, rows};
    const cuuint64_t strides[1] = {cols * 2};
    const cuuint32_t box[2] = {bcols, brows};
    const cuuint32_t es[2] = {1, 1};
    enc(&m, CU_TENSOR_MAP_DATA_TYPE_BFLOAT16, 2, ptr, dims, strides, box, es, CU_TENSOR_MAP_INTERLEAVE_NONE, sw, promo,
        CU_TENSOR_MAP_FLOAT_OOB_FILL_NONE);
    return m;
}

}

extern "C" void kernel_launch(void* const* d_in, const int* in_sizes, int n_in, void* d_out, int out_size) {
    (void)in_sizes; (void)n_in; (void)out_size;
    static EncodeFn enc = nullptr;
    static int sms = 0;
    if (!enc) {
        cudaDriverEntryPointQueryResult qr;
        cudaGetDriverEntryPoint("cuTensorMapEncodeTiled", (void**)&enc, cudaEnableDefault, &qr);
        int dev = 0;
        cudaGetDevice(&dev);
        cudaDeviceGetAttribute(&sms, cudaDevAttrMultiProcessorCount, dev);
        cudaFuncSetAttribute(fused_decode_kernel, cudaFuncAttributeMaxDynamicSharedMemorySize, SM_TOTAL);
    }
    if (sms < NCTAS) return;
    const CUtensorMapL2promotion WPROMO = CU_TENSOR_MAP_L2_PROMOTION_L2_128B;
    Params p;
    p.k = make_map(enc, d_in[1], 64, (uint64_t)NBH * SK * 3, 64, TILE_ROWS, CU_TENSOR_MAP_SWIZZLE_128B, CU_TENSOR_MAP_L2_PROMOTION_NONE);
    p.v = make_map(enc, d_in[2], 64, (uint64_t)NBH * SK * 3, 64, TILE_ROWS, CU_TENSOR_MAP_SWIZZLE_128B, CU_TENSOR_MAP_L2_PROMOTION_NONE);
    p.wq = make_map(enc, d_in[3], NH * DH, DM, 48, 160, CU_TENSOR_MAP_SWIZZLE_NONE, WPROMO);
    p.wo = make_map(enc, d_in[4], DM, NH * DH, 32, DH, CU_TENSOR_MAP_SWIZZLE_64B, WPROMO);
    p.wg = make_map(enc, d_in[7], FF, DM, 32, 160, CU_TENSOR_MAP_SWIZZLE_64B, WPROMO);
    p.wu = make_map(enc, d_in[8], FF, DM, 32, 160, CU_TENSOR_MAP_SWIZZLE_64B, WPROMO);
    {
        const cuuint64_t dims[4] = {DM, 2, 8, FF / 16}, strides[3] = {8 * DM * 2, DM * 2, 16 * DM * 2};
        const cuuint32_t box[4] = {16, 2, 8, 12}, es[4] = {1, 1, 1, 1};
        enc(&p.wd, CU_TENSOR_MAP_DATA_TYPE_BFLOAT16, 4, d_in[9], dims, strides, box, es, CU_TENSOR_MAP_INTERLEAVE_NONE,
            CU_TENSOR_MAP_SWIZZLE_32B, WPROMO, CU_TENSOR_MAP_FLOAT_OOB_FILL_NONE);
    }
    p.x = (const __nv_bfloat16*)d_in[0];
    p.wr = (const __nv_bfloat16*)d_in[6];
    p.out = (__nv_bfloat16*)d_out;
    fused_decode_kernel<<<NCTAS, NTHREADS, SM_TOTAL, cudaStreamPerThread>>>(p);
}
```

```cpp
#include <cuda_runtime.h>
#include <cuda_bf16.h>
#include <cuda.h>
#include <stdint.h>

namespace {

constexpr int NB = 4, NH = 32, SK = 8192, DH = 192, DM = 640, FF = 1536;
constexpr int NBH = NB * NH;
constexpr int TILE = 64;
constexpr int UPB = SK / TILE;
constexpr int NUNITS = NBH * UPB;
constexpr int TILE_BYTES = TILE * DH * 2;
constexpr int TILE_ROWS = TILE * 3;
constexpr int NCTAS = 132;
constexpr int NQ_CTAS = 128;
constexpr int NE_CTAS = 112;
__host__ __device__ constexpr bool is_f(int cta) { return cta < NE_CTAS && cta % 14 < 11 && !(cta & 1); }
__host__ __device__ constexpr bool is_g(int cta) { return cta < NE_CTAS && cta % 14 < 11 && (cta & 1); }
__host__ __device__ constexpr int ffn_slice(int cta) { return cta / 14 * ((cta & 1) ? 5 : 6) + cta % 14 / 2; }

#define NWORK 2
#define LAG 2
#define NPOOL 768
#define RED0 116
#define RING 11
#define OREP 2
#define K0_AT_NS 1150
#define WO_AT_NS (K0_AT_NS + 2000)
#define K1_AT_NS (K0_AT_NS + 4400)
constexpr int KSWEEP_NS = 2000, WO_STEP_NS = 75;
#define FW_TICKET (NPOOL + 32)
#define FW_AT_NS 2090
#define FW_GAP 280
#define FW_MID 2100
#define FW_GAP2 200
#define HGATE_NS 700
#define SLOT_TICKS 9
#define SLOT_OPEN 3
#define PH_O 0
#define PH_H 8
#define PH_M 2
#define NPROBE 24
static_assert(FW_TICKET < NPOOL + NWORK * NCTAS, "every worker draws one ticket beyond the pool");
constexpr int NAUX = 8;
constexpr int NTHREADS = (NAUX + NWORK + 2) * 32;
constexpr int SPIN_MAX = 1 << 22;

constexpr int SM_KV = 0;
constexpr int SM_A = SM_KV + NWORK * TILE_BYTES;
constexpr int SM_W = SM_A + 61440;
constexpr int SM_X = SM_W + 81920;
constexpr int XPITCH = 648;
constexpr int HPITCH = 1344;
constexpr int SM_RED = SM_X + 5 * HPITCH + 64;
constexpr int SM_RED2 = SM_RED + 8 * 48 * 4 * 4;
constexpr int SM_MISC = SM_RED2 + 4096;
constexpr int BAR_WQ = SM_MISC, SM_SCRAP = SM_MISC + 32, BAR_WO = SM_MISC + 40, SM_SIDE = SM_MISC + 48, BAR_H = SM_MISC + 56, BAR_FW = SM_MISC + 64;
constexpr int BAR_KV = BAR_FW + 64;
constexpr int SM_TOTAL = BAR_KV + NWORK * 8;
static_assert(SM_W % 1024 == 0 && NB * XPITCH * 2 <= 4 * HPITCH && SM_RED % 128 == 0, "smem layout");

struct Params {
    CUtensorMap k, v;
    CUtensorMap wq;
    CUtensorMap wo;
    CUtensorMap wg, wu;
    CUtensorMap wd;
    const __nv_bfloat16 *x, *wr;
    __nv_bfloat16* out;
};

struct Early {
    uint32_t q[4][4][8];
    uint32_t umax[UPB];
};
struct Twin { uint32_t w[4][1024]; };
constexpr int PROBE = 1024 - 32;
#define LSTRIDE 16
struct State {
    Twin ax[3];
    Twin hx;
    Twin ox[(OREP + 1) / 2];
    Twin lx;
    float4 oacc[NBH * 64];
    float2 attn[NB][DM];
    uint32_t fw_time[32];
    float2 lsum[NBH][LSTRIDE];
    uint32_t score[NPOOL][32];
};
__host__ __device__ constexpr int oidx(int row, int grp) {
    return (row >> 2) * 256 + ((row & 1) * 2 + (grp >> 5)) * 64 + (row & 2) * 16 + (grp & 31);
}
constexpr int STATE_V4 = ((sizeof(State) / 32 + NQ_CTAS - 1) / NQ_CTAS) * 2;
static_assert(sizeof(State) % 32 == 0, "State is cleared in whole sectors");
static_assert(sizeof(Early) == 64 * 16, "an Early entry is cleared by 64 threads");
struct Scratch {
    State st;
    unsigned work[64];
    unsigned cnt_z[32];
    Early early[NBH];
    alignas(4096) float4 ring[RING][UPB][64];
};
constexpr size_t PAGE = 2u << 20;
static_assert(sizeof(Scratch) <= PAGE, "scratch must fit one page");
__device__ __align__(128) unsigned char g_raw[2 * PAGE];
__device__ __forceinline__ Scratch* scratch() {
    return reinterpret_cast<Scratch*>((reinterpret_cast<uintptr_t>(g_raw) + PAGE - 1) & ~(uintptr_t)(PAGE - 1));
}
#define g_early scratch()->early
#define g_st scratch()->st
#define g_ring scratch()->ring
#define g_cnt_z scratch()->cnt_z
#define g_work scratch()->work
#define ALL_LOADERS 0
#define TS(i)
#define TSW(i)
#define TS2(i)
#define TSI(n, i)
#define PH(i)
#define CK(i, dep)
#define ARR()
#define PROG(u)

__device__ __forceinline__ uint32_t s2u(const void* p) { return (uint32_t)__cvta_generic_to_shared(p); }
__device__ __forceinline__ void mbar_init(uint32_t bar, int cnt) {
    asm volatile("mbarrier.init.shared::cta.b64 [%0], %1;" :: "r"(bar), "r"(cnt) : "memory");
}
__device__ __forceinline__ void mbar_wait(uint32_t bar, uint32_t parity) {
    asm volatile("{\n.reg .pred p;\n.reg .u32 n;\nmov.u32 n, 0;\nWAIT_LOOP:\n"
                 "mbarrier.try_wait.parity.shared::cta.b64 p, [%0], %1;\n"
                 "@p bra WAIT_DONE;\nadd.u32 n, n, 1;\nsetp.lt.u32 p, n, %2;\n@p bra WAIT_LOOP;\nWAIT_DONE:\n}"
                 :: "r"(bar), "r"(parity), "n"(SPIN_MAX) : "memory");
}
__device__ __forceinline__ void request_tile(uint32_t dst, const CUtensorMap* tm, int unit, uint32_t bar, uint64_t pol) {
    asm volatile("{\n.reg .pred p;\nelect.sync _|p, 0xffffffff;\n"
                 "@p mbarrier.arrive.expect_tx.shared::cta.b64 _, [%2], %6;\n"
                 "@p cp.async.bulk.tensor.2d.shared::cluster.global.mbarrier::complete_tx::bytes.L2::cache_hint "
                 "[%0], [%1, {%3, %4}], [%2], %5;\n}"
                 :: "r"(dst), "l"(tm), "r"(bar), "r"(0), "r"(unit * TILE_ROWS), "l"(pol), "n"(TILE_BYTES) : "memory");
}
__device__ __forceinline__ void put_groups(void* dst, int mode, const float (&o)[6], float tag, float tag2) {
    asm volatile("{\n.reg .pred s, t;\n.reg .b128 u, v;\n.reg .b64 a, b;\n"
                 "setp.eq.s32 s, %1, 0;\nsetp.ne.s32 t, %1, 2;\nxor.b64 a, %0, 4096;\n"
                 "@t bra.uni SINGLE;\n"
                 "red.relaxed.gpu.global.add.v4.f32 [a], {%2,%3,%4,%8};\n"
                 "red.relaxed.gpu.global.add.v4.f32 [a+128], {%5,%6,%7,%9};\n"
                 "SINGLE:\n"
                 "@s bra.uni STORE;\n"
                 "red.relaxed.gpu.global.add.v4.f32 [%0], {%2,%3,%4,%8};\n"
                 "red.relaxed.gpu.global.add.v4.f32 [%0+128], {%5,%6,%7,%9};\n"
                 "STORE:\n"
                 "mov.b64 a, {%2, %3};\nmov.b64 b, {%4, %8};\nmov.b128 u, {a, b};\n"
                 "mov.b64 a, {%5, %6};\nmov.b64 b, {%7, %9};\nmov.b128 v, {a, b};\n"
                 "@s st.relaxed.gpu.global.b128 [%0], u;\n@s st.relaxed.gpu.global.b128 [%0+128], v;\n}"
                 :: "l"(dst), "r"(mode), "f"(o[0]), "f"(o[1]), "f"(o[2]), "f"(o[3]), "f"(o[4]), "f"(o[5]), "f"(tag), "f"(tag2) : "memory");
}
__device__ __forceinline__ void request_box(uint32_t dst, const CUtensorMap* tm, int col, int row, uint32_t bar, uint32_t bytes) {
    asm volatile("{\n.reg .pred p, q;\nelect.sync _|p, 0xffffffff;\nsetp.ne.and.u32 q, %5, 0, p;\n"
                 "@q mbarrier.arrive.expect_tx.shared::cta.b64 _, [%2], %5;\n"
                 "@p cp.async.bulk.tensor.2d.shared::cluster.global.mbarrier::complete_tx::bytes [%0], [%1, {%3, %4}], [%2];\n}"
                 :: "r"(dst), "l"(tm), "r"(bar), "r"(col), "r"(row), "r"(bytes) : "memory");
}
__device__ __forceinline__ uint32_t lds32(uint32_t addr) {
    uint32_t v;
    asm volatile("ld.shared.u32 %0, [%1];" : "=r"(v) : "r"(addr) : "memory");
    return v;
}
__device__ __forceinline__ void ldsm4(uint32_t (&r)[4], uint32_t addr) {
    asm volatile("ldmatrix.sync.aligned.m8n8.x4.shared.b16 {%0,%1,%2,%3}, [%4];"
                 : "=r"(r[0]), "=r"(r[1]), "=r"(r[2]), "=r"(r[3]) : "r"(addr) : "memory");
}
__device__ __forceinline__ void ldsm4t(uint32_t (&r)[4], uint32_t addr) {
    asm volatile("ldmatrix.sync.aligned.m8n8.x4.trans.shared.b16 {%0,%1,%2,%3}, [%4];"
                 : "=r"(r[0]), "=r"(r[1]), "=r"(r[2]), "=r"(r[3]) : "r"(addr) : "memory");
}
__device__ __forceinline__ void mma16816(float (&c)[4], const uint32_t (&a)[4], uint32_t b0, uint32_t b1) {
    asm volatile("mma.sync.aligned.m16n8k16.row.col.f32.bf16.bf16.f32 {%0,%1,%2,%3}, {%4,%5,%6,%7}, {%8,%9}, {%0,%1,%2,%3};"
                 : "+f"(c[0]), "+f"(c[1]), "+f"(c[2]), "+f"(c[3])
                 : "r"(a[0]), "r"(a[1]), "r"(a[2]), "r"(a[3]), "r"(b0), "r"(b1));
}
struct Warm {
    float c[4] = {};
    __device__ __forceinline__ void operator()() {
        asm volatile("mma.sync.aligned.m16n8k8.row.col.f32.bf16.bf16.f32 {%0,%1,%2,%3}, {%4,%4}, {%4}, {%0,%1,%2,%3};"
                     : "+f"(c[0]), "+f"(c[1]), "+f"(c[2]), "+f"(c[3]) : "r"(0));
    }
    __device__ __forceinline__ void done(uint32_t scrap) {
        asm volatile("{\n.reg .pred p;\nsetp.gt.f32 p, %1, 0f3f800000;\n@p st.shared.f32 [%0], %1;\n}" :: "r"(scrap), "f"(c[0]) : "memory");
    }
};
__device__ __forceinline__ uint4 ld_relaxed_v4(const void* p) {
    uint4 v;
    asm volatile("ld.relaxed.gpu.global.v4.u32 {%0,%1,%2,%3}, [%4];" : "=r"(v.x), "=r"(v.y), "=r"(v.z), "=r"(v.w) : "l"(p) : "memory");
    return v;
}
__device__ __forceinline__ float4 ld_relaxed_f4(const void* p) {
    float4 v;
    asm volatile("ld.relaxed.gpu.global.v4.f32 {%0,%1,%2,%3}, [%4];" : "=f"(v.x), "=f"(v.y), "=f"(v.z), "=f"(v.w) : "l"(p) : "memory");
    return v;
}
__device__ __forceinline__ float2 ld_relaxed_f2(const void* p) {
    float2 v;
    asm volatile("ld.relaxed.gpu.global.v2.f32 {%0,%1}, [%2];" : "=f"(v.x), "=f"(v.y) : "l"(p) : "memory");
    return v;
}
__device__ __forceinline__ float4 ld_relaxed_b128(const void* p) {
    float4 v;
    asm volatile("{\n.reg .b128 t;\n.reg .b64 a, b;\nld.relaxed.gpu.global.b128 t, [%4];\nmov.b128 {a, b}, t;\n"
                 "mov.b64 {%0, %1}, a;\nmov.b64 {%2, %3}, b;\n}" : "=f"(v.x), "=f"(v.y), "=f"(v.z), "=f"(v.w) : "l"(p) : "memory");
    return v;
}
__device__ __forceinline__ void st_relaxed_b128(void* p, float x, float y, float z, float w) {
    asm volatile("{\n.reg .b128 t;\n.reg .b64 a, b;\nmov.b64 a, {%1, %2};\nmov.b64 b, {%3, %4};\nmov.b128 t, {a, b};\n"
                 "st.relaxed.gpu.global.b128 [%0], t;\n}" :: "l"(p), "f"(x), "f"(y), "f"(z), "f"(w) : "memory");
}
__device__ __forceinline__ unsigned ld_acquire(const unsigned* p) {
    unsigned v;
    asm volatile("ld.acquire.gpu.global.u32 %0, [%1];" : "=r"(v) : "l"(p) : "memory");
    return v;
}
__device__ __forceinline__ void st_relaxed(void* p, uint32_t v) {
    asm volatile("st.relaxed.gpu.global.u32 [%0], %1;" :: "l"(p), "r"(v) : "memory");
}
__device__ __forceinline__ void red_f2(float* p, float a, float b) {
    asm volatile("red.relaxed.gpu.global.add.v2.f32 [%0], {%1,%2};" :: "l"(p), "f"(a), "f"(b) : "memory");
}
__device__ __forceinline__ void draw(int& ticket, unsigned* ctr, bool pred) {
    asm volatile("{\n.reg .pred p;\nsetp.ne.u32 p, %2, 0;\n@p atom.relaxed.gpu.global.inc.u32 %0, [%1], 0x7fffffff;\n}"
                 : "+r"(ticket) : "l"(ctr), "r"((uint32_t)pred) : "memory");
}
__device__ __forceinline__ void red_release(unsigned* p) {
    asm volatile("red.release.gpu.global.add.u32 [%0], 1;" :: "l"(p) : "memory");
}
__device__ __forceinline__ uint32_t ld_relaxed_u32(const void* p) {
    uint32_t v;
    asm volatile("ld.relaxed.gpu.global.u32 %0, [%1];" : "=r"(v) : "l"(p) : "memory");
    return v;
}
__device__ __forceinline__ float rcp_approx(float v) {
    float r;
    asm("rcp.approx.ftz.f32 %0, %1;" : "=f"(r) : "f"(v));
    return r;
}
__device__ __forceinline__ float ex2_approx(float v) {
    float e;
    asm("ex2.approx.ftz.f32 %0, %1;" : "=f"(e) : "f"(v));
    return e;
}
__device__ __forceinline__ float sigmoid_approx(float v) { return rcp_approx(1.0f + ex2_approx(v * -1.4426950408889634f)); }
__device__ __forceinline__ float sqrt_approx(float v) {
    float r;
    asm("sqrt.approx.ftz.f32 %0, %1;" : "=f"(r) : "f"(v));
    return r;
}
__device__ __forceinline__ bool all(bool v) { return __all_sync(0xffffffffu, v); }
__device__ __forceinline__ void wait_count(const unsigned* p, unsigned target) {
#pragma unroll 1
    for (int it = 0; it < SPIN_MAX; it++) {
        if (all(ld_acquire(p) >= target)) break;
        __nanosleep(400);
    }
}
__device__ __forceinline__ float wait_sum(const void* p, float n, int nap = 0) {
    float2 v;
#pragma unroll 1
    for (int it = 0; it < SPIN_MAX; it++) {
        v = ld_relaxed_f2(p);
        if (all(v.y >= n)) break;
        if (all(v.y == 0.f)) __nanosleep(600);
        else if (nap) __nanosleep(nap);
    }
    return v.x;
}
__device__ __forceinline__ void wait_row(int bh, float n) { wait_sum(g_st.lsum[bh], n); }
__device__ __forceinline__ void wait_row_o(int bh, float n) {
    wait_row(bh, n);
    if (bh >= RED0) return;
#pragma unroll 1
    for (int it = 0; it < SPIN_MAX; it++) {
        if (all(__uint_as_float(ld_relaxed_u32(&g_st.oacc[oidx(bh, 0)].w)) == UPB)) break;
        __nanosleep(300);
    }
}
constexpr uint32_t SLOT_K = (uint32_t)(((1ull << 32) + SLOT_TICKS - 1) / SLOT_TICKS);
#define SLOT_ASM(t, n, p, phase, k, open) \
    "mov.u32 " n ", 0;\nSLOT:\nmov.u32 " t ", %%globaltimer_lo;\nadd.u32 " n ", " n ", 1;\nsetp.lt.u32 " p ", " n ", 24;\nshr.u32 " t ", " t ", 5;\n" \
    "mad.lo.u32 " t ", " t ", " k ", " phase ";\nsetp.ge.and.u32 " p ", " t ", " open ", " p ";\n@" p " bra.uni SLOT;\n"
template <int PHASE> __host__ __device__ constexpr uint32_t slot_phase() { return SLOT_K / 2 - PHASE * SLOT_K; }
template <int PHASE> __device__ __forceinline__ void wait_slot() {
    if (PHASE < 0) return;
    asm volatile("{\n.reg .pred p;\n.reg .b32 t, n;\n" SLOT_ASM("t", "n", "p", "%0", "%1", "%2") "}"
                 :: "n"(slot_phase<PHASE>()), "n"(SLOT_K), "n"(SLOT_OPEN * SLOT_K) : "memory");
}
__device__ __forceinline__ void wait_time(uint32_t t) {
#pragma unroll 1
    for (int it = 0; it < SPIN_MAX; it++) {
        uint32_t now;
        asm volatile("mov.u32 %0, %%globaltimer_lo;" : "=r"(now));
        if (all((int)(now - t) >= 0)) break;
    }
}
__device__ __forceinline__ void wait_clock(uint32_t t, Warm& warm) { while (!all((int)(clock() - t) >= 0)) { warm(); } }
__device__ __forceinline__ uint32_t pack_bf16(float lo, float hi) {
    uint32_t r;
    asm("cvt.rn.bf16x2.f32 %0, %1, %2;" : "=r"(r) : "f"(hi), "f"(lo));
    return r;
}
__device__ __forceinline__ float bf16r(float v) { return __uint_as_float(pack_bf16(0.f, v)); }
__device__ __forceinline__ uint32_t nonzero(uint32_t w) { return w ? w : 0x80008000u; }
__device__ __forceinline__ uint32_t pack_neg(float lo, float hi) { return nonzero(pack_bf16(-lo, -hi)); }
__device__ __forceinline__ float lo_f(uint32_t v) { return __uint_as_float(v << 16); }
__device__ __forceinline__ float hi_f(uint32_t v) { return __uint_as_float(v & 0xffff0000u); }
__device__ __forceinline__ float warp_sum(float v) {
#pragma unroll
    for (int o = 16; o; o >>= 1) v += __shfl_xor_sync(0xffffffffu, v, o);
    return v;
}
__device__ __forceinline__ void layernorm20(float (&v)[20]) {
    float s = 0.f;
#pragma unroll
    for (int i = 0; i < 20; i++) s += v[i];
    const float mean = warp_sum(s) * (1.0f / DM);
    float q = 0.f;
#pragma unroll
    for (int i = 0; i < 20; i++) { const float d = v[i] - mean; q += d * d; }
    const float var = bf16r(warp_sum(q) * (1.0f / DM));
    const float m = bf16r(mean);
    const float rden = 1.0f / bf16r(sqrtf(bf16r(var + 1e-5f)));
#pragma unroll
    for (int i = 0; i < 20; i++) v[i] = bf16r(bf16r(v[i] - m) * rden);
}

__device__ __forceinline__ void moments(float m1, float m2, float& nmean, float& rden) {
    m1 *= 1.0f / DM;
    const float var = bf16r(fmaxf(fmaf(-m1, m1, m2 * (1.0f / DM)), 0.f));
    nmean = bf16r(m1);
    rden = rcp_approx(bf16r(sqrt_approx(bf16r(var + 1e-5f))));
}
__device__ __forceinline__ float sel4(int j, float a, float b, float c, float d) {
    float lo, hi, r;
    asm("{\n.reg .pred p;\nsetp.ne.s32 p, %3, 0;\nselp.f32 %0, %2, %1, p;\n}" : "=f"(lo) : "f"(a), "f"(b), "r"(j & 1));
    asm("{\n.reg .pred p;\nsetp.ne.s32 p, %3, 0;\nselp.f32 %0, %2, %1, p;\n}" : "=f"(hi) : "f"(c), "f"(d), "r"(j & 1));
    asm("{\n.reg .pred p;\nsetp.ne.s32 p, %3, 0;\nselp.f32 %0, %2, %1, p;\n}" : "=f"(r) : "f"(lo), "f"(hi), "r"(j & 2));
    return r;
}
template <typename T> __device__ __forceinline__ void pin(T*& p) { asm volatile("" : "+l"(p)); }
__device__ __forceinline__ void pin(uint32_t& v) { asm volatile("" : "+r"(v)); }
__device__ __forceinline__ void pin(float& v) { asm volatile("" : "+f"(v)); }
__device__ __forceinline__ uint32_t after(uint32_t n, float v) {
    asm volatile("{\n.reg .pred p;\nsetp.eq.u32 p, %1, 0x7fc1a5a5;\n@p add.u32 %0, %0, 32;\n}" : "+r"(n) : "r"(__float_as_uint(v)));
    return n;
}
__device__ __forceinline__ float2 lds64f(uint32_t addr) {
    float2 v;
    asm volatile("ld.shared.v2.f32 {%0,%1}, [%2];" : "=f"(v.x), "=f"(v.y) : "r"(addr) : "memory");
    return v;
}
__device__ __forceinline__ void sts32f(uint32_t addr, float v) { asm volatile("st.shared.f32 [%0], %1;" :: "r"(addr), "f"(v) : "memory"); }
template <int ID> __device__ __forceinline__ void fin_arrive() { asm volatile("bar.arrive %0, 288;" :: "n"(ID) : "memory"); }
template <int ID> __device__ __forceinline__ void fin_sync() { asm volatile("bar.sync %0, 288;" :: "n"(ID) : "memory"); }
template <int ID> __device__ __forceinline__ void fin_sync(uint32_t n) { asm volatile("bar.sync %0, %1;" :: "n"(ID), "r"(n) : "memory"); }
__device__ __forceinline__ float2 sum8(uint32_t addr, int pitch) {
    float2 t[8];
#pragma unroll
    for (int w = 0; w < 8; w++) t[w] = lds64f(addr + w * pitch);
    return make_float2(((t[0].x + t[1].x) + (t[2].x + t[3].x)) + ((t[4].x + t[5].x) + (t[6].x + t[7].x)),
                       ((t[0].y + t[1].y) + (t[2].y + t[3].y)) + ((t[4].y + t[5].y) + (t[6].y + t[7].y)));
}
__device__ __forceinline__ float4 sum4x4(uint32_t addr, int pitch) {
    float4 t[4];
#pragma unroll
    for (int w = 0; w < 4; w++)
        asm volatile("ld.shared.v4.f32 {%0,%1,%2,%3}, [%4];" : "=f"(t[w].x), "=f"(t[w].y), "=f"(t[w].z), "=f"(t[w].w) : "r"(addr + w * pitch) : "memory");
    return make_float4((t[0].x + t[1].x) + (t[2].x + t[3].x), (t[0].y + t[1].y) + (t[2].y + t[3].y),
                       (t[0].z + t[1].z) + (t[2].z + t[3].z), (t[0].w + t[1].w) + (t[2].w + t[3].w));
}
__device__ __forceinline__ void sts64f(uint32_t addr, float x, float y) {
    asm volatile("st.shared.v2.f32 [%0], {%1,%2};" :: "r"(addr), "f"(x), "f"(y) : "memory");
}
__device__ __forceinline__ void lds128_if(uint4& v, uint32_t addr, bool pred) {
    asm volatile("{\n.reg .pred p;\nsetp.ne.u32 p, %5, 0;\n@p ld.shared.v4.u32 {%0,%1,%2,%3}, [%4];\n}"
                 : "+r"(v.x), "+r"(v.y), "+r"(v.z), "+r"(v.w) : "r"(addr), "r"((uint32_t)pred) : "memory");
}
__device__ __forceinline__ void ld_relaxed_v4_if(uint4& v, const void* p, bool pred) {
    asm volatile("{\n.reg .pred p;\nsetp.ne.u32 p, %5, 0;\n@p ld.relaxed.gpu.global.v4.u32 {%0,%1,%2,%3}, [%4];\n}"
                 : "+r"(v.x), "+r"(v.y), "+r"(v.z), "+r"(v.w) : "l"(p), "r"((uint32_t)pred) : "memory");
}
__device__ __forceinline__ void sts128f(uint32_t addr, float x, float y, float z, float w) {
    asm volatile("st.shared.v4.f32 [%0], {%1,%2,%3,%4};" :: "r"(addr), "f"(x), "f"(y), "f"(z), "f"(w) : "memory");
}
template <int NJ>
__device__ __forceinline__ void load_o(uint32_t (&ob)[3 * NJ][2], int bh, int J0, int j) {
    float4 v[NJ][4];
    float2 l;
#pragma unroll 1
    for (int it = 0; it < SPIN_MAX; it++) {
#pragma unroll
        for (int J = 0; J < NJ; J++) {
#pragma unroll
            for (int e = 0; e < 4; e++) v[J][e] = ld_relaxed_f4(&g_st.oacc[oidx(bh, j)] + oidx(0, (J0 + J) * 16 + e * 4));
        }
        l = ld_relaxed_f2(g_st.lsum[bh]);
        bool ok = l.y == UPB;
#pragma unroll
        for (int J = 0; J < NJ; J++) {
#pragma unroll
            for (int e = 0; e < 4; e++) ok &= v[J][e].w == UPB;
        }
        if (all(ok)) break;
    }
    const float rl = __fdividef(1.0f, l.x);
#pragma unroll
    for (int J = 0; J < NJ; J++) {
        ob[3 * J][0] = pack_bf16(v[J][0].x * rl, v[J][1].x * rl);     ob[3 * J][1] = pack_bf16(v[J][2].x * rl, v[J][3].x * rl);
        ob[3 * J + 1][0] = pack_bf16(v[J][0].y * rl, v[J][1].y * rl); ob[3 * J + 1][1] = pack_bf16(v[J][2].y * rl, v[J][3].y * rl);
        ob[3 * J + 2][0] = pack_bf16(v[J][0].z * rl, v[J][1].z * rl); ob[3 * J + 2][1] = pack_bf16(v[J][2].z * rl, v[J][3].z * rl);
    }
}
__device__ __forceinline__ int near_side(uint32_t sb) {
    uint32_t v;
    asm volatile("ld.volatile.shared.u32 %0, [%1];" : "=r"(v) : "r"(sb + SM_SIDE) : "memory");
    return v;
}
__device__ __forceinline__ void poll_row(uint4& a, uint4& b, uint2& c, const void* pa, const void* pb, const void* pc, uint32_t sa, uint32_t sc,
                                         bool arrive, bool nap, uint32_t bar, Warm& warm) {
    asm volatile("{\n.reg .pred p, q, r, s;\n.reg .b32 m, n, it;\n"
                 "setp.ne.u32 r, %19, 0;\nsetp.ne.u32 s, %20, 0;\nmov.u32 it, 0;\n"
                 "POLL:\n"
                 SLOT_ASM("m", "n", "p", "%23", "%24", "%25")
                 "ld.relaxed.gpu.global.v4.u32 {%0,%1,%2,%3}, [%14];\n"
                 "ld.relaxed.gpu.global.v4.u32 {%4,%5,%6,%7}, [%15];\n"
                 "ld.relaxed.gpu.global.v2.u32 {%8,%9}, [%16];\n"
                 "add.u32 it, it, 1;\nsetp.ge.u32 q, it, %21;\n"
                 "mov.u32 m, 0;\nmma.sync.aligned.m16n8k8.row.col.f32.bf16.bf16.f32 {%10,%11,%12,%13}, {m,m}, {m}, {%10,%11,%12,%13};\n"
                 "st.shared.v4.u32 [%17], {%0,%1,%2,%3};\n"
                 "st.shared.v4.u32 [%17+512], {%4,%5,%6,%7};\n"
                 "st.shared.v2.u32 [%18], {%8,%9};\n"
                 "min.u32 m, %0, %1;\nmin.u32 m, m, %2;\nmin.u32 n, %3, %4;\nmin.u32 n, n, %5;\nmin.u32 m, m, %6;\nmin.u32 m, m, %7;\n"
                 "min.u32 n, n, m;\nmin.u32 m, %8, %9;\nmin.u32 m, m, n;\n"
                 "setp.ne.or.u32 p, m, 0, q;\n"
                 "vote.sync.all.pred p, p, 0xffffffff;\n"
                 "and.pred q, p, r;\n"
                 "bar.warp.sync 0xffffffff;\n"
                 "@q mbarrier.arrive.shared::cta.b64 _, [%22];\n"
                 "@p bra.uni DONE;\n"
                 "@s nanosleep.u32 500;\n"
                 "bra.uni POLL;\n"
                 "DONE:\n}"
                 : "=&r"(a.x), "=&r"(a.y), "=&r"(a.z), "=&r"(a.w), "=&r"(b.x), "=&r"(b.y), "=&r"(b.z), "=&r"(b.w), "=&r"(c.x), "=&r"(c.y),
                   "+f"(warm.c[0]), "+f"(warm.c[1]), "+f"(warm.c[2]), "+f"(warm.c[3])
                 : "l"(pa), "l"(pb), "l"(pc), "r"(sa), "r"(sc), "r"((uint32_t)arrive), "r"((uint32_t)nap), "n"(SPIN_MAX), "r"(bar),
                   "n"(slot_phase<PH_H>()), "n"(SLOT_K), "n"(SLOT_OPEN * SLOT_K) : "memory");
}
__device__ __forceinline__ void aux_sync() { asm volatile("bar.sync 1, 256;" ::: "memory"); }

__global__ void __launch_bounds__(NTHREADS, 1)
fused_decode_kernel(const __grid_constant__ Params p) {
    extern __shared__ __align__(1024) unsigned char smem[];
    const uint32_t sb = s2u(smem);
    const int tid = threadIdx.x, cta = blockIdx.x;
    if (tid < 32 && cta < NQ_CTAS) {
        asm volatile("{\n.reg .pred p;\nelect.sync _|p, 0xffffffff;\n"
                     "@p mbarrier.init.shared::cta.b64 [%2], 1;\n"
                     "@p fence.mbarrier_init.release.cluster;\n"
                     "@p mbarrier.arrive.expect_tx.shared::cta.b64 _, [%2], 15360;\n"
                     "@p cp.async.bulk.tensor.2d.shared::cluster.global.mbarrier::complete_tx::bytes [%0], [%1, {%3, %4}], [%2];\n"
                     "@p mbarrier.init.shared::cta.b64 [%2+8], 1;\n@p mbarrier.init.shared::cta.b64 [%2+16], 1;\n"
                     "@p mbarrier.init.shared::cta.b64 [%2+24], 1;\n"
                     "@p fence.mbarrier_init.release.cluster;\n"
                     "@p mbarrier.arrive.expect_tx.shared::cta.b64 _, [%2+8], 15360;\n"
                     "@p cp.async.bulk.tensor.2d.shared::cluster.global.mbarrier::complete_tx::bytes [%0+15360], [%1, {%3, %5}], [%2+8];\n"
                     "@p mbarrier.arrive.expect_tx.shared::cta.b64 _, [%2+16], 15360;\n"
                     "@p cp.async.bulk.tensor.2d.shared::cluster.global.mbarrier::complete_tx::bytes [%0+30720], [%1, {%3, %6}], [%2+16];\n"
                     "@p mbarrier.arrive.expect_tx.shared::cta.b64 _, [%2+24], 15360;\n"
                     "@p cp.async.bulk.tensor.2d.shared::cluster.global.mbarrier::complete_tx::bytes [%0+46080], [%1, {%3, %7}], [%2+24];\n}"
                     :: "r"(sb + SM_W), "l"(&p.wq), "r"(sb + BAR_WQ), "r"(cta * 48), "r"(0), "r"(160), "r"(320), "r"(480) : "memory");
    }
    const int warp = __shfl_sync(0xffffffffu, tid >> 5, 0), lane = tid & 31;
    constexpr int grid = NCTAS;
    const int g = lane >> 2, j = lane & 3;
    uint32_t t_start;
    asm volatile("mov.u32 %0, %%globaltimer_lo;" : "=r"(t_start));
    TS(0);
    if (tid == 32) {
        mbar_init(sb + BAR_WO, 1);
        mbar_init(sb + BAR_H, 1);
#pragma unroll
        for (int i = 0; i < 8 + NWORK; i++) mbar_init(sb + BAR_FW + i * 8, 1);
        sts32f(sb + SM_SIDE, 0.f);
        asm volatile("fence.mbarrier_init.release.cluster;" ::: "memory");
        asm volatile("fence.proxy.async.shared::cta;" ::: "memory");
    }
    __syncthreads();
    if (warp >= NAUX + NWORK) {
        const int fw = warp - (NAUX + NWORK), fi = ffn_slice(cta);
        if (fw == 0) {
            if (cta < NQ_CTAS) {
#pragma unroll
                for (int i = lane; i < STATE_V4; i += 32)
                    if (cta * STATE_V4 + i < (int)(sizeof(State) / 16)) reinterpret_cast<uint4*>(&g_st)[cta * STATE_V4 + i] = make_uint4(0u, 0u, 0u, 0u);
                __syncwarp();
                if (lane == 0) red_release(g_cnt_z);
            }
            TSW(2); wait_count(g_cnt_z, NQ_CTAS); TSW(29);
            asm volatile("bar.arrive 2, %0;" :: "n"((NWORK + 2) * 32) : "memory");
            fin_arrive<3>();
        } else {
#pragma unroll 1
            for (int n = cta < NE_CTAS ? 5 : 4, i = n - 1; i >= 0; i--) {
                const int head = cta < NE_CTAS ? cta >> 2 : 28 + i;
                wait_time(t_start + WO_AT_NS + (NH - 1 - head) * WO_STEP_NS);
                request_box(sb + SM_A + i * 12288, &p.wo, cta < NE_CTAS ? (cta & 3) * 160 + i * 32 : (cta - NE_CTAS) * 32,
                            head * DH, sb + BAR_WO, i == n - 1 ? n * 12288 : 0);
            }
            asm volatile("bar.sync 2, %0;" :: "n"((NWORK + 2) * 32) : "memory");
            uint32_t best[2] = {~0u, ~0u};
#pragma unroll 1
            for (int i = 0; i < NPROBE; i++) {
#pragma unroll
                for (int c = 0; c < 2; c++) {
                    uint32_t t0 = clock(), t1 = t0;
                    int v = 0;
                    draw(v, &g_st.hx.w[c][PROBE], lane == 0);
                    asm volatile("{\n.reg .pred p;\nsetp.ne.u32 p, %1, 0xffffffff;\n@p mov.u32 %0, %%clock;\n}" : "+r"(t1) : "r"(v) : "memory");
                    best[c] = min(best[c], t1 - t0);
                }
                __nanosleep(1000);
            }
            if (lane == 0) sts32f(sb + SM_SIDE, __uint_as_float(best[1] < best[0]));
        }
        int job = cta;
        auto sum_rows = [&](int row_end) {
#pragma unroll 1
            for (; job < 8 * min(row_end, RED0); job += NCTAS) {
                const int row = job >> 3, grp = (job & 7) * 8 + (lane & 7);
                wait_row(row, UPB);
                const float4* src = &g_ring[row % RING][lane >> 3][grp];
                float sx = 0.f, sy = 0.f, sz = 0.f;
#pragma unroll 1
                for (int i = 0; i < 2; i++, src += 64 * 64) {
                    float4 v[16];
#pragma unroll 1
                    for (int it = 0; it < SPIN_MAX; it++) {
                        bool ok = true;
#pragma unroll
                        for (int k = 0; k < 16; k++) v[k] = ld_relaxed_b128(src + k * 4 * 64);
#pragma unroll
                        for (int k = 0; k < 16; k++) ok &= v[k].w == (float)(row + 1);
                        if (all(ok)) break;
                    }
#pragma unroll
                    for (int k = 0; k < 16; k++) { sx += v[k].x; sy += v[k].y; sz += v[k].z; }
                }
#pragma unroll
                for (int o = 8; o < 32; o <<= 1) {
                    sx += __shfl_xor_sync(0xffffffffu, sx, o); sy += __shfl_xor_sync(0xffffffffu, sy, o); sz += __shfl_xor_sync(0xffffffffu, sz, o);
                }
                if (lane < 8) st_relaxed_b128(&g_st.oacc[oidx(row, grp)], sx, sy, sz, UPB);
            }
        };
        const int ho0 = lane / 20 * 256 + lane % 20 * 4, ho1 = (lane + 32) / 20 * 256 + (lane + 32) % 20 * 4, ho2 = 3 * 256 + 16 + 2 * lane;
        uint32_t wr[10] = {};
        float wsum = 0.f;
        if (is_g(cta) && fw == 0) {
#pragma unroll
            for (int i = 0; i < 10; i++) {
                const int w = 4 * lane + 128 * (i >> 2) + (i & 3) - (i >= 8 ? 2 * lane : 0);
                wr[i] = *reinterpret_cast<const uint32_t*>(p.wr + (w >> 4) * 32 + (w & 3) * 8 + ((w >> 1) & 6));
                wsum += lo_f(wr[i]) + hi_f(wr[i]);
            }
            wsum = warp_sum(wsum);
        }
        const int fb = lane >> 3, fg = lane & 7;
        if (fw == 0) {
#pragma unroll
            for (int i = lane; i < DM / 2; i += 32) sts32f(sb + SM_X + 4 * HPITCH + i * 4, __uint_as_float(0x3f803f80u));
        }
        Warm warm;
        float nmean = 0.f, rden = 0.f, sig = 0.f;
#pragma unroll 1
        for (int b = 0; b < NB; b++) {
            const bool ffn = b >= NB - 2;
            if (fw == 0) {
                sum_rows((b + 1) * NH);
                if (ffn) asm volatile("bar.arrive 8, 64;" ::: "memory");
            } else if (ffn) {
                asm volatile("bar.sync 8, 64;" ::: "memory");
                if (b == NB - 1 && (is_f(cta) || is_g(cta) || ALL_LOADERS)) {
                    uint32_t t0 = 0;
#pragma unroll 1
                    for (int it = 0; it < SPIN_MAX; it++) {
                        t0 = ld_relaxed_u32(g_st.fw_time);
                        if (all(t0 != 0)) break;
                        __nanosleep(150);
                    }
                    asm volatile("fence.proxy.async.shared::cta;" ::: "memory");
                    wait_time(t0 + FW_AT_NS);
                    TSW(9);
                    uint32_t t = clock() + (is_f(cta) ? ((fi & 1) * 24 + (fi >> 1)) * FW_GAP / 48 : FW_MID + ((fi & 3) * 10 + (fi >> 2)) * FW_GAP2 / 40);
#pragma unroll 1
                    for (int i = 0; i < 8; i++) {
                        const uint32_t bar = sb + BAR_FW + i * 8;
                        if (is_f(cta)) {
                            wait_clock(t, warm);
                            request_box(sb + SM_W + i * 10240, (i & 1) ? &p.wu : &p.wg, fi * 32, (i >> 1) * 160, bar, 10240);
                            t += FW_GAP;
                        } else if (is_g(cta)) {
                            wait_clock(t, warm);
                            asm volatile("{\n.reg .pred p;\nelect.sync _|p, 0xffffffff;\n"
                                         "@p mbarrier.arrive.expect_tx.shared::cta.b64 _, [%2], 6144;\n"
                                         "@p cp.async.bulk.tensor.4d.shared::cluster.global.mbarrier::complete_tx::bytes [%0], [%1, {%3, %4, %4, %5}], [%2];\n}"
                                         :: "r"(sb + SM_W + i * 6144), "l"(&p.wd), "r"(bar), "r"(fi * 16), "r"(0), "r"(i * 12) : "memory");
                            t += FW_GAP2;
                        }
                    }
                }
                if (is_f(cta)) {
                    const uint32_t* src = &g_st.hx.w[near_side(sb)][min(fb, b) * 256 + 96];
                    float4 m;
#pragma unroll 1
                    for (int it = 0; it < SPIN_MAX; it++) {
                        wait_slot<PH_M>();
                        m = ld_relaxed_f4(src);
                        warm();
                        if (all(m.y + m.w == 2 * (NCTAS - NE_CTAS))) break;
                        if (b < NB - 1) __nanosleep(500);
                    }
                    moments(m.x, m.z, m.x, m.z);
                    sts64f(sb + SM_RED + 5120 + fb * 8, m.x, m.z);
                }
            }
            if (fw == 0 && cta >= NE_CTAS) {
                const int lc = cta - NE_CTAS, col = lc * 32 + 2 * (lane & 15);
                const uint32_t xv = *reinterpret_cast<const uint32_t*>(p.x + b * DM + col);
                uint32_t* dst = &(ffn ? g_st.hx.w : g_st.lx.w + 2)[lane >> 4][(b & 1) * 128 + lc / 5 * 256 + lc % 5 * 16 + (col & 6) * 2 + ((col >> 3) & 3)];
                uint32_t part = sb + SM_RED + (lane & 15) * 8;
                wait_row(b * NH + 28, 1);
                float4 early;
#pragma unroll 1
                for (int it = 0; it < SPIN_MAX; it++) {
                    early = ld_relaxed_f4(&g_st.attn[b][col]);
                    if (all(early.y == NE_CTAS / 4 && early.w == NE_CTAS / 4)) break;
                }
                if (early.x != 1.2345f && lane == 0) TS2(6);
                CK(1, __float_as_uint(early.x));
                const float x0 = -(lo_f(xv) + early.x), x1 = -(hi_f(xv) + early.z);
                fin_sync<4>(after(after(288, x0), x1));
                CK(2, lds32(sb + SM_RED));
                const float2 late = sum8(part, 128);
                const uint32_t hv = nonzero(pack_bf16(x0 - late.x, x1 - late.y));
                st_relaxed(dst, hv);
                if (ffn) st_relaxed(dst + 2048, hv);
                CK(3, 0);
                float m = lane < 16 ? lo_f(hv) + hi_f(hv) : fmaf(lo_f(hv), lo_f(hv), hi_f(hv) * hi_f(hv));
#pragma unroll
                for (int o = 1; o < 16; o <<= 1) m += __shfl_xor_sync(0xffffffffu, m, o);
                if ((lane & 14) == 0) red_f2(reinterpret_cast<float*>(&g_st.hx.w[lane & 1][b * 256 + 96 + (lane >> 4) * 2]), m, 1.f);
                fin_arrive<5>();
            }
            if (fw == 0 && (is_g(cta) || is_f(cta))) {
                const uint32_t* src = &(ffn ? g_st.hx.w : g_st.lx.w + 2)[near_side(sb) ^ (ffn && is_g(cta) ? 3 : 0)][(b & 1) * 128];
                const uint32_t hrow = sb + SM_X + b * HPITCH;
                wait_sum(b == NB - 1 ? (const void*)&g_st.lx.w[near_side(sb) ^ 1][3 * 256] : g_st.lsum[b * NH + NH - 1], UPB, 100);
                wait_clock(clock() + HGATE_NS * 2, warm);
                uint4 h0, h1;
                uint2 h2;
                poll_row(h0, h1, h2, src + ho0, src + ho1, src + ho2, hrow + lane * 16, hrow + 1024 + lane * 8, ffn && lane == 0, b < NB - 1, sb + BAR_H, warm);
                CK(4, h0.x);
                if (is_g(cta)) {
                    const uint32_t hw[10] = {h0.x, h0.y, h0.z, h0.w, h1.x, h1.y, h1.z, h1.w, h2.x, h2.y};
                    float m1 = 0.f, m2 = 0.f, rr = 0.f;
#pragma unroll
                    for (int i = 0; i < 10; i++) {
                        const float v0 = lo_f(hw[i]), v1 = hi_f(hw[i]);
                        m1 += v0 + v1;
                        m2 = fmaf(v0, v0, fmaf(v1, v1, m2));
                        rr = fmaf(v0, lo_f(wr[i]), fmaf(v1, hi_f(wr[i]), rr));
                    }
                    moments(warp_sum(m1), warp_sum(m2), m1, m2);
                    const float sg = bf16r(sigmoid_approx(bf16r((m1 * wsum - warp_sum(rr)) * m2)));
                    if (fb == b) { nmean = m1; rden = m2; sig = sg; }
                    __syncwarp();
                    if (ffn) {
                        const int yj = 2 * (fb & 1) + (fb >> 1);
                        uint32_t ypart = sb + SM_RED2 + yj * 128 + ((fg + 2 * yj) & 7) * 16;
                        __nv_bfloat16* out = p.out + fb * DM + fi * 16 + fg;
                        const float2 hw2 = lds64f(sb + SM_X + fb * HPITCH + ((fi >> 1) * 16 + (fg & 6) * 2 + (fi & 1) * 2) * 4);
                        const uint32_t w0 = __float_as_uint(hw2.x), w1 = __float_as_uint(hw2.y);
                        const float nh0 = (fg & 1) ? hi_f(w0) : lo_f(w0), nh1 = (fg & 1) ? hi_f(w1) : lo_f(w1);
                        const float ln0 = bf16r(bf16r(nmean - nh0) * rden) - nh0, ln1 = bf16r(bf16r(nmean - nh1) * rden) - nh1;
                        pin(ypart); pin(out);
                        fin_sync<6>(after(after(after(288, sig), ln0), ln1));
                        CK(10, lds32(ypart));
                        const float4 ya = sum4x4(ypart, 512), yb = sum4x4(ypart + 2048, 512);
                        const float4 y = make_float4(ya.x + yb.x, ya.y + yb.y, ya.z + yb.z, ya.w + yb.w);
                        const float y0 = -(((fb & 1) ? y.y : y.x) + __shfl_xor_sync(0xffffffffu, (fb & 1) ? y.x : y.y, 8));
                        const float y1 = -(((fb & 1) ? y.w : y.z) + __shfl_xor_sync(0xffffffffu, (fb & 1) ? y.z : y.w, 8));
                        const uint32_t ov = pack_bf16(fmaf(y0, sig, ln0), fmaf(y1, sig, ln1));
                        asm volatile("{\n.reg .pred p;\n.reg .b16 lo, hi;\nsetp.ne.u32 p, %2, 0;\nmov.b32 {lo, hi}, %1;\n"
                                     "@p st.global.u16 [%0], lo;\n@p st.global.u16 [%0+16], hi;\n"
                                     "@p exit;\n"
                                     "}" :: "l"(out), "r"(ov), "r"((uint32_t)(b == NB - 1)) : "memory");
                        CK(11, 0);
                        if (lane == 0) TS2(13);
                    }
                }
            }
            if (is_f(cta) && ffn) {
                const int ks = (2 * fi + fw) % 12;
                const int far = near_side(sb) ^ 1;
                uint32_t* dst = &g_st.ax[ks >> 2].w[(~b & 1) * 2 + far][(fi / 6) * 128 + (ks & 3) * 32 + fb * 8 + (fg & 1) * 4 + ((fg >> 1) ^ (ks & 1))];
                uint32_t* dst2 = dst + (far ? -1024 : 1024);
                uint32_t part = sb + SM_RED + fw * 2560 + fb * 128 + ((fg + (fb & 2)) & 7) * 16;
                uint32_t psum = sb + SM_RED + fw * 2560 + 4 * 128 + ((fg + 4) & 7) * 16;
                pin(dst); pin(part); pin(psum);
                asm volatile("bar.sync 4, 320;" ::: "memory");
                CK(6, lds32(part));
                const float4 d = sum4x4(part, 640), cs = sum4x4(psum, 640);
                const float2 mo = lds64f(sb + SM_RED + 5120 + fb * 8);
                nmean = mo.x; rden = mo.y;
                const float g0 = fmaf(nmean, cs.x, -d.x), g1 = fmaf(nmean, cs.y, -d.y), ke = rden * -1.4426950408889634f, r2 = rden * rden;
                const float p0 = g0 * fmaf(-nmean, cs.z, d.z) * r2, p1 = g1 * fmaf(-nmean, cs.w, d.w) * r2;
                const uint32_t av = nonzero(pack_bf16(p0 * rcp_approx(1.0f + ex2_approx(g0 * ke)), p1 * rcp_approx(1.0f + ex2_approx(g1 * ke))));
                st_relaxed(dst, av);
                st_relaxed(dst2, av);
                CK(7, 0);
            }
        }
        warm.done(sb + SM_SCRAP);
        if (cta == 0 && tid == (NAUX + NWORK) * 32) { g_work[0] = 0; g_work[32] = 0; g_cnt_z[0] = 0; }
        return;
    }
    if (warp >= NAUX) {
        const int wk = warp - NAUX;
        const uint32_t bar = sb + BAR_KV + wk * 8;
        const uint32_t buf = sb + SM_KV + wk * TILE_BYTES;
        uint64_t pol;
        asm volatile("createpolicy.fractional.L2::evict_first.b64 %0, 1.0;" : "=l"(pol));
        const int nstatic = NWORK * grid;
        constexpr int POOL0 = NUNITS - NPOOL;
        int uk = wk * grid + cta;
        wait_time(t_start + K0_AT_NS + uk * KSWEEP_NS / nstatic);
        request_tile(buf, &p.k, uk, bar, pol);
        uint32_t koff[3], voff[3];
        {
            const int r = lane & 7, hf = (lane >> 3) & 1;
            const int kkey = hf ? 8 + (r ^ 1) : r;
            const int vh = lane >> 4;
            const int vkey = ((r & 1) ? 8 : 0) + (vh ? (r ^ 1) : r);
#pragma unroll
            for (int b = 0; b < 3; b++) {
                const int rk = 3 * kkey + b, rv = 3 * vkey + b;
                koff[b] = buf + rk * 128 + (((lane >> 4) ^ (rk & 7)) << 4);
                voff[b] = buf + rv * 128 + ((hf ^ (rv & 7)) << 4);
            }
        }
        uint32_t phase = 0;
        uint32_t qf[12][2];
        auto load_q = [&](int u) {
            const uint32_t* q = g_early[u / UPB].q[0][j];
#pragma unroll
            for (int i = 0; i < 4; i++) {
                const uint4 a = ld_relaxed_v4(q + i * 32);
                const float2 c = ld_relaxed_f2(q + i * 32 + 4);
                qf[3 * i][0] = a.x; qf[3 * i][1] = a.y; qf[3 * i + 1][0] = a.z; qf[3 * i + 1][1] = a.w;
                qf[3 * i + 2][0] = __float_as_uint(c.x); qf[3 * i + 2][1] = __float_as_uint(c.y);
            }
        };
        load_q(uk);
        int uq[LAG];
        uint32_t sq[LAG];
#pragma unroll
        for (int i = 0; i < LAG; i++) { uq[i] = -1; sq[i] = 0; }
        uint4 mv = make_uint4(0u, 0u, 0u, 0u);
        float freed = UPB;
        while (true) {
            const int uv = uq[0];
            uint32_t sv = sq[0];
#pragma unroll
            for (int i = 0; i + 1 < LAG; i++) { uq[i] = uq[i + 1]; sq[i] = sq[i + 1]; }
            uq[LAG - 1] = uk;
            if (uk < NUNITS) {
                PH(7);
#pragma unroll 1
                for (int it = 0; it < SPIN_MAX; it++) {
                    uint32_t lo = 0xffffffffu;
#pragma unroll
                    for (int i = 0; i < 12; i++) lo = min(lo, min(qf[i][0], qf[i][1]));
                    if (all(lo != 0)) break;
                    __nanosleep(250);
                    load_q(uk);
                }
                mbar_wait(bar, phase); phase ^= 1;
                PH(0); ARR();
                TSI(0, 16); TSI(1, 18);
                float acc[2][4][4] = {};
#pragma unroll
                for (int ks = 0; ks < 12; ks++) {
#pragma unroll
                    for (int mt = 0; mt < 4; mt++) {
                        uint32_t a[4];
                        ldsm4(a, (koff[ks >> 2] ^ ((ks & 3) << 5)) + mt * 6144);
                        mma16816(acc[ks & 1][mt], a, qf[ks][0], qf[ks][1]);
                    }
                }
                PH(1);
                TSI(0, 17); TSI(1, 19);
                if (uk < nstatic) wait_time(t_start + K1_AT_NS + uk * KSWEEP_NS / nstatic);
                if (uv < NUNITS) request_tile(buf, uv >= 0 ? &p.v : &p.k, uv >= 0 ? uv : uk + nstatic, bar, pol);
                const float sa = sel4(j, acc[0][0][0], acc[0][1][0], acc[0][2][0], acc[0][3][0]) + sel4(j, acc[1][0][0], acc[1][1][0], acc[1][2][0], acc[1][3][0]);
                const float sc = sel4(j, acc[0][0][2], acc[0][1][2], acc[0][2][2], acc[0][3][2]) + sel4(j, acc[1][0][2], acc[1][1][2], acc[1][2][2], acc[1][3][2]);
                const uint32_t raw = pack_bf16(sa, sc);
                const float scale = -0.07216878364870322f;
                const uint32_t sk = pack_bf16(lo_f(raw) * scale, hi_f(raw) * scale);
                sq[LAG - 1] = sk;
                if (uk >= POOL0) st_relaxed(&g_st.score[uk - POOL0][lane], sk ? sk : 0x80008000u);
                int a = (int)(sk << 16), b = (int)(sk & 0xffff0000u);
                a ^= (a >> 31) & 0x7fff0000; b ^= (b >> 31) & 0x7fff0000;
                const int mx = __reduce_max_sync(0xffffffffu, max(a, b));
                if (lane == 0) st_relaxed(&g_early[uk / UPB].umax[uk % UPB], (uint32_t)mx | 1u);
            }
            if (uv < 0) {
                uk += nstatic;
                load_q(uk);
                continue;
            }
            if (uv >= NUNITS) break;
            const int bh = uv / UPB;
#pragma unroll 1
            for (int it = 0; it < SPIN_MAX; it++) {
                if (all((mv.x & mv.y & mv.z & mv.w & 1u) && (uv < POOL0 || sv != 0) && freed == UPB)) break;
                mv = ld_relaxed_v4(&g_early[bh].umax[lane * 4]);
                if (bh >= RING && bh < RED0) freed = __uint_as_float(ld_relaxed_u32(&g_st.oacc[oidx(bh - RING, (lane & 7) * 8)].w));
                if (uv >= POOL0) sv = ld_relaxed_u32(&g_st.score[uv - POOL0][lane]);
            }
            PH(2); CK(8, sv);
            int un = NUNITS, vn = 0;
            draw(un, g_work, uk < NUNITS && lane == 0);
            uint32_t tdraw;
            asm volatile("mov.u32 %0, %%globaltimer_lo;" : "=r"(tdraw));
            draw(vn, g_work + 32, uq[0] >= POOL0 && lane == 0);
            int mx = __reduce_max_sync(0xffffffffu, max(max((int)mv.x, (int)mv.y), max((int)mv.z, (int)mv.w))) & 0xffff0000;
            mx ^= (mx >> 31) & 0x7fff0000;
            const float m = __int_as_float(mx);
            const float l2e = 1.4426950408889634f;
            const uint32_t pp = pack_bf16(exp2f((lo_f(sv) - m) * l2e), exp2f((hi_f(sv) - m) * l2e));
            uint32_t pb[8];
#pragma unroll
            for (int t = 0; t < 4; t++) {
                pb[2 * t] = __shfl_sync(0xffffffffu, pp, 8 * j + t);
                pb[2 * t + 1] = __shfl_sync(0xffffffffu, pp, 8 * j + 4 + t);
            }
            float lacc[4] = {};
            const uint32_t ones[4] = {0x3f803f80u, 0x3f803f80u, 0x3f803f80u, 0x3f803f80u};
#pragma unroll
            for (int t = 0; t < 4; t++) mma16816(lacc, ones, pb[2 * t], pb[2 * t + 1]);
            if (uv < nstatic) {
                asm volatile("bar.sync 2, %0;" :: "n"((NWORK + 2) * 32) : "memory");
                TSW(3);
            }
            const int grp = 16 * j + 4 * (g & 1) + (g >> 1);
            uint32_t mode = (bh >= RED0) + (bh >= NBH - 4);
            float tag = mode ? 1.f : (float)(bh + 1), tag2 = fmaf(__uint_as_float(voff[0]), 0.f, tag);
            void* dst = mode == 0 ? (void*)&g_ring[bh % RING][uv % UPB][grp] :
                        mode == 1 ? (void*)&g_st.oacc[oidx(bh, grp)] : (void*)&g_st.ox[0].w[uv % OREP * 2 + (~(near_side(sb) ^ uv % OREP) & 1)][oidx(bh & 3, grp) * 4];
            if (mode == 2 && lane < 2) red_f2(reinterpret_cast<float*>(&g_st.lx.w[lane][(bh & 3) * 256]), lacc[0], 1.f);
            CK(10, __float_as_uint(lacc[0]));
            un = __shfl_sync(0xffffffffu, un, 0) + (LAG + 1) * nstatic;
            vn = __shfl_sync(0xffffffffu, vn, 0);
            if (uq[0] >= POOL0) uq[0] = POOL0 + vn;
            if (vn == FW_TICKET && lane == 0) st_relaxed(g_st.fw_time, tdraw | 1u);
            if (uq[0] < NUNITS && un >= NUNITS) {
                mv = ld_relaxed_v4(&g_early[uq[0] / UPB].umax[lane * 4]);
                if (uq[0] < RED0 * UPB) freed = 0.f;
                if (uq[0] >= POOL0) sq[0] = ld_relaxed_u32(&g_st.score[uq[0] - POOL0][lane]);
            }
            pin(dst); pin(mode); pin(tag); pin(tag2); pin(voff[0]); pin(voff[1]); pin(voff[2]);
            PH(3); CK(9, vn);
            mbar_wait(bar, phase); phase ^= 1;
            PH(4); ARR(); CK(12, lds32(buf));
            float acc[12][4] = {};
#pragma unroll
            for (int t = 0; t < 4; t++) {
#pragma unroll
                for (int mt = 0; mt < 12; mt++) {
                    uint32_t a[4];
                    ldsm4t(a, (voff[mt >> 2] ^ ((mt & 3) << 5)) + t * 6144);
                    mma16816(acc[mt], a, pb[2 * t], pb[2 * t + 1]);
                }
            }
            PH(5);
            if (lane == 0) PROG(un);
            if (un < NUNITS || uq[0] < NUNITS) request_tile(buf, un < NUNITS ? &p.k : &p.v, un < NUNITS ? un : uq[0], bar, pol);
            if (un < NUNITS || uq[0] < NUNITS) CK(11, 0);
            float o[6];
#pragma unroll
            for (int e = 0; e < 6; e++) {
                const int q = e % 3, c = (e / 3) * 2;
                o[e] = sel4(j, acc[q][c], acc[3 + q][c], acc[6 + q][c], acc[9 + q][c]);
            }
            put_groups(dst, mode, o, tag, tag2);
            CK(13, 0);
            if (un < NUNITS) load_q(un);
            if (lane == 0) red_f2(&g_st.lsum[bh][0].x, lacc[0], 1.f);
            PH(6);
            if (uq[0] >= NUNITS && un >= NUNITS) break;
            uk = un;
            if (uq[0] < NUNITS && un < NUNITS) {
                const int nb = uq[0] / UPB;
                mv = ld_relaxed_v4(&g_early[nb].umax[lane * 4]);
                freed = nb >= RING && nb < RED0 ? __uint_as_float(ld_relaxed_u32(&g_st.oacc[oidx(nb - RING, (lane & 7) * 8)].w)) : UPB;
                if (uq[0] >= POOL0) sq[0] = ld_relaxed_u32(&g_st.score[uq[0] - POOL0][lane]);
            }
        }
        TSW(4 + wk);
        return;
    }

    __nv_bfloat16* xs = reinterpret_cast<__nv_bfloat16*>(smem + SM_X);
    float* red = reinterpret_cast<float*>(smem + SM_RED);
    const int frow = (lane & 7) + ((lane >> 4) << 3), fcol = (lane >> 3) & 1;
    const uint32_t f64b = sb + (frow * 4 + (fcol ^ ((frow >> 1) & 3))) * 16;
    if (cta < NQ_CTAS) {
        TS(26);
        if (warp >= 4) {
            uint2 xr[5];
#pragma unroll
            for (int i = 0; i < 5; i++) xr[i] = *reinterpret_cast<const uint2*>(p.x + (warp - 4) * DM + i * 128 + lane * 4);
            float v[20];
#pragma unroll
            for (int i = 0; i < 5; i++) {
                v[4 * i] = lo_f(xr[i].x); v[4 * i + 1] = hi_f(xr[i].x); v[4 * i + 2] = lo_f(xr[i].y); v[4 * i + 3] = hi_f(xr[i].y);
            }
            layernorm20(v);
#pragma unroll
            for (int i = 0; i < 5; i++)
                *reinterpret_cast<uint2*>(xs + (warp - 4) * XPITCH + i * 128 + lane * 4) =
                    make_uint2(pack_bf16(v[4 * i], v[4 * i + 1]), pack_bf16(v[4 * i + 2], v[4 * i + 3]));
        }
        aux_sync();
        TS(27);
        mbar_wait(sb + BAR_WQ + (warp >> 1) * 8, 0);
        TS(1);
        const uint32_t xfrag = sb + SM_X + ((g & 3) * XPITCH + 2 * j) * 2;
        float acc[3][4] = {};
#pragma unroll
        for (int s = 0; s < 5; s++) {
            const int ks = warp * 5 + s;
            const uint32_t b0 = lds32(xfrag + ks * 32), b1 = lds32(xfrag + ks * 32 + 16);
            const int row = ks * 16 + frow;
#pragma unroll
            for (int mt = 0; mt < 3; mt++) {
                uint32_t a[4];
                ldsm4t(a, sb + SM_W + (row * 6 + 2 * mt + fcol) * 16);
                mma16816(acc[mt], a, b0, b1);
            }
        }
        if (j < 2) {
#pragma unroll
            for (int mt = 0; mt < 3; mt++) {
                *reinterpret_cast<float2*>(red + warp * 216 + mt * 72 + g * 4 + 2 * j) = make_float2(acc[mt][0], acc[mt][1]);
                *reinterpret_cast<float2*>(red + warp * 216 + mt * 72 + 36 + g * 4 + 2 * j) = make_float2(acc[mt][2], acc[mt][3]);
            }
        }
        aux_sync();
        if (warp < 4) {
            const float* src = red + min(g, 5) * 36 + warp * 8 + j;
            float s0 = 0.f, s1 = 0.f;
#pragma unroll
            for (int w = 0; w < 8; w++) { s0 += src[w * 216]; s1 += src[w * 216 + 4]; }
            st_relaxed(&g_early[j * NH + (cta >> 2)].q[cta & 3][warp][g], pack_neg(s0, s1));
        }
        TS(28);
    }
    fin_sync<3>();
    mbar_wait(sb + BAR_WO, 0);
    TS(7);
    uint32_t part = sb + SM_RED + (warp * 32 + 8 * j + g) * 4;

#pragma unroll 1
    for (int b = 0; b < NB; b++) {
        if (cta >= NE_CTAS) {
            uint32_t a[6][2][4];
#pragma unroll
            for (int s = 0; s < 6; s++) {
#pragma unroll
                for (int mt = 0; mt < 2; mt++) ldsm4t(a[s][mt], (f64b ^ (mt * 32)) + SM_A + (warp * 6 + s) * 1024);
            }
            const int bh = b * NH + 28 + (warp >> 1);
            const int side = near_side(sb) ^ 1;
            const void* osrc[OREP];
#pragma unroll
            for (int c = 0; c < OREP; c++)
                osrc[c] = b == NB - 1 ? (const void*)&g_st.ox[c >> 1].w[side ^ (c & 1) * 3][oidx(bh & 3, (warp & 1) * 32 + lane) * 4] : &g_st.oacc[oidx(bh, (warp & 1) * 32 + lane)];
            const void* lsrc = b == NB - 1 ? (const void*)&g_st.lx.w[side][(bh & 3) * 256] : g_st.lsum[bh];
            wait_row_o(bh, 1);
            const float rl = rcp_approx(wait_sum(lsrc, UPB)) * (b == NB - 1 ? 1.f : 1.f / OREP), full = b == NB - 1 ? UPB : UPB * OREP;
            float4 ov;
            float px, py, pz;
            Warm warm;
#pragma unroll 1
            for (int it = 0; it < SPIN_MAX; it++) {
                wait_slot<PH_O>();
                float4 oc[OREP];
#pragma unroll
                for (int c = 0; c < OREP; c++) oc[c] = ld_relaxed_f4(osrc[c]);
                warm();
                ov = oc[0];
#pragma unroll
                for (int c = 1; c < OREP; c++) { ov.x += oc[c].x; ov.y += oc[c].y; ov.z += oc[c].z; ov.w += oc[c].w; }
                ov.x *= rl; ov.y *= rl; ov.z *= rl;
                px = __shfl_xor_sync(0xffffffffu, ov.x, 4); py = __shfl_xor_sync(0xffffffffu, ov.y, 4); pz = __shfl_xor_sync(0xffffffffu, ov.z, 4);
                if (all(ov.w == full)) break;
            }
            CK(0, __float_as_uint(ov.x));
            if (ov.x != 1.2345f && warp == 7) TSW(14);
            const uint32_t w[3] = {pack_bf16(ov.x, px), pack_bf16(ov.y, py), pack_bf16(ov.z, pz)};
            float acc[2][2][4] = {};
#pragma unroll
            for (int s = 0; s < 6; s++) {
                const uint32_t b0 = __shfl_sync(0xffffffffu, w[s % 3], (s / 3) * 16 + j);
                const uint32_t b1 = __shfl_sync(0xffffffffu, w[s % 3], (s / 3) * 16 + 8 + j);
#pragma unroll
                for (int mt = 0; mt < 2; mt++) mma16816(acc[mt][s & 1], a[s][mt], b0, b1);
            }
            sts32f(part, sel4(j, acc[0][0][0] + acc[0][1][0], acc[0][0][2] + acc[0][1][2], acc[1][0][0] + acc[1][1][0], acc[1][0][2] + acc[1][1][2]));
            CK(1, 0);
            fin_arrive<4>();
            warm.done(sb + SM_SCRAP);
            fin_sync<5>();
            if (cta < NE_CTAS + 4 && tid < 64) reinterpret_cast<uint4*>(&g_early[b * NH + 28 + cta - NE_CTAS])[tid] = make_uint4(0u, 0u, 0u, 0u);
        } else {
            const int bh = b * NH + (cta >> 2);
            if (warp == 0) wait_row_o(bh, UPB);
            aux_sync();
            if (warp < 5) {
                uint32_t ob[12][2];
                load_o<4>(ob, bh, 0, j);
                float acc[2][2][4] = {};
#pragma unroll
                for (int ks = 0; ks < 12; ks++) {
#pragma unroll
                    for (int mt = 0; mt < 2; mt++) {
                        uint32_t a[4];
                        ldsm4t(a, (f64b ^ (mt * 32)) + SM_A + warp * 12288 + ks * 1024);
                        mma16816(acc[mt][ks & 1], a, ob[ks][0], ob[ks][1]);
                    }
                }
                red_f2(&g_st.attn[b][(cta & 3) * 160 + warp * 32 + 8 * j + g].x,
                       sel4(j, acc[0][0][0] + acc[0][1][0], acc[0][0][2] + acc[0][1][2], acc[1][0][0] + acc[1][1][0], acc[1][0][2] + acc[1][1][2]), 1.f);
                TS(8);
            } else if (warp > 5 && (cta & 3) == 0) {
                reinterpret_cast<uint4*>(&g_early[bh])[tid - 192] = make_uint4(0u, 0u, 0u, 0u);
            }
        }
        if (b < NB - 2) continue;

        if (is_f(cta)) {
            uint32_t ga[10][2][4];
            uint4 hv[5] = {};
            const uint32_t hfrag = sb + SM_X + min(g, 4) * HPITCH + ((warp >> 1) * 80 + 4 * j) * 4;
#pragma unroll
            for (int s = 0; s < 5; s++) lds128_if(hv[s], hfrag + s * 64, b == NB - 1);
            if (b == NB - 1) mbar_wait(sb + BAR_FW + warp * 8, 0);
            if (warp == 7) TSW(10);
            CK(12, lds32(sb + SM_W));
#pragma unroll
            for (int s = 0; s < 10; s++) {
#pragma unroll
                for (int mt = 0; mt < 2; mt++) ldsm4t(ga[s][mt], (f64b ^ (mt * 32)) + SM_W + (warp * 10 + s) * 1024);
            }
            const uint32_t gpart = sb + SM_RED + (warp >> 1) * 640 + j * 256 + ((g + 2 * j) & 7) * 16 + (warp & 1) * 8;
            mbar_wait(sb + BAR_H, b & 1);
#pragma unroll
            for (int s = 0; s < 5; s++) lds128_if(hv[s], hfrag + s * 64, g == b);
            CK(4, hv[0].x);
            float acc[2][2][4] = {};
#pragma unroll
            for (int s = 0; s < 10; s++) {
#pragma unroll
                for (int mt = 0; mt < 2; mt++)
                    mma16816(acc[mt][s & 1], ga[s][mt], (s & 1) ? hv[s >> 1].z : hv[s >> 1].x, (s & 1) ? hv[s >> 1].w : hv[s >> 1].y);
            }
#pragma unroll
            for (int mt = 0; mt < 2; mt++) {
                if (j < 3) sts64f(gpart + mt * 2560, acc[mt][0][0] + acc[mt][1][0], acc[mt][0][2] + acc[mt][1][2]);
                if (j < 2) sts64f(gpart + mt * 2560 + 128, acc[mt][0][1] + acc[mt][1][1], acc[mt][0][3] + acc[mt][1][3]);
            }
            CK(5, 0);
            asm volatile("bar.arrive 4, 320;" ::: "memory");
        } else if (is_g(cta)) {
            const uint32_t* asrc = &g_st.ax[0].w[(~b & 1) * 2 + near_side(sb)][warp * 128 + ((g >> 2) * 2 + (j >> 1)) * 32 + (g & 3) * 8 + (j & 1) * 4];
            const uint32_t ypart = sb + SM_RED2 + warp * 512 + j * 128 + ((g + 2 * j) & 7) * 16;
            uint32_t wb[12][4];
            uint4 va[3] = {};
            uint32_t lo[3] = {};
            auto ask = [&]() {
#pragma unroll
                for (int i = 0; i < 3; i++) ld_relaxed_v4_if(va[i], asrc + i * 4096, lo[i] == 0);
            };
            auto complete = [&]() {
#pragma unroll
                for (int i = 0; i < 3; i++) lo[i] = min(min(va[i].x, va[i].y), min(va[i].z, va[i].w));
                return all(min(lo[0], min(lo[1], lo[2])) != 0);
            };
            const int jj = (lane & 7) >> 1, q = jj >> 1, hi = lane >> 4;
            const uint32_t wsrc = sb + SM_W + warp * 6144 + q * 512 + ((hi ^ q) * 4 + (jj & 1) * 2 + (lane & 1)) * 32 + ((fcol ^ hi ^ q) << 4);
            mbar_wait(sb + BAR_H, b & 1);
            if (b == NB - 1) mbar_wait(sb + BAR_FW + warp * 8, 0);
            if (warp == 7) TSW(11);
            CK(13, lds32(sb + SM_W));
            ask();
#pragma unroll
            for (int s = 0; s < 12; s++) ldsm4t(wb[s], wsrc + (s >> 2) * 2048 + (s & 1) * 1024 + (s & 2) * 128);
            Warm warm;
            if (!complete()) {
#pragma unroll 1
                for (int it = 0; it < SPIN_MAX; it++) {
                    ask();
                    warm();
                    if (complete()) break;
                }
            }
            CK(8, va[0].x);
            if (va[0].x != 0x12345 && warp == 7) TSW(15);
            float acc[6][4] = {};
#pragma unroll
            for (int s = 0; s < 12; s++) {
                const uint4 v = va[s >> 2];
                mma16816(acc[s % 6], wb[s], (s & 2) ? v.z : v.x, (s & 2) ? v.w : v.y);
            }
            float y[4];
#pragma unroll
            for (int e = 0; e < 4; e++) y[e] = j < 2 ? (acc[0][e] + acc[2][e]) + acc[4][e] : (acc[1][e] + acc[3][e]) + acc[5][e];
            sts128f(ypart, y[0], y[1], y[2], y[3]);
            CK(9, 0);
            fin_arrive<6>();
            warm.done(sb + SM_SCRAP);
        }
    }
}

typedef CUresult (*EncodeFn)(CUtensorMap*, CUtensorMapDataType, cuuint32_t, void*, const cuuint64_t*, const cuuint64_t*,
                             const cuuint32_t*, const cuuint32_t*, CUtensorMapInterleave, CUtensorMapSwizzle,
                             CUtensorMapL2promotion, CUtensorMapFloatOOBfill);

CUtensorMap make_map(EncodeFn enc, void* ptr, uint64_t cols, uint64_t rows, uint32_t bcols, uint32_t brows,
                     CUtensorMapSwizzle sw, CUtensorMapL2promotion promo) {
    CUtensorMap m;
    const cuuint64_t dims[2] = {cols, rows};
    const cuuint64_t strides[1] = {cols * 2};
    const cuuint32_t box[2] = {bcols, brows};
    const cuuint32_t es[2] = {1, 1};
    enc(&m, CU_TENSOR_MAP_DATA_TYPE_BFLOAT16, 2, ptr, dims, strides, box, es, CU_TENSOR_MAP_INTERLEAVE_NONE, sw, promo,
        CU_TENSOR_MAP_FLOAT_OOB_FILL_NONE);
    return m;
}

}

extern "C" void kernel_launch(void* const* d_in, const int* in_sizes, int n_in, void* d_out, int out_size) {
    (void)in_sizes; (void)n_in; (void)out_size;
    static EncodeFn enc = nullptr;
    static int sms = 0;
    if (!enc) {
        cudaDriverEntryPointQueryResult qr;
        cudaGetDriverEntryPoint("cuTensorMapEncodeTiled", (void**)&enc, cudaEnableDefault, &qr);
        int dev = 0;
        cudaGetDevice(&dev);
        cudaDeviceGetAttribute(&sms, cudaDevAttrMultiProcessorCount, dev);
        cudaFuncSetAttribute(fused_decode_kernel, cudaFuncAttributeMaxDynamicSharedMemorySize, SM_TOTAL);
    }
    if (sms < NCTAS) return;
    const CUtensorMapL2promotion WPROMO = CU_TENSOR_MAP_L2_PROMOTION_L2_128B;
    Params p;
    p.k = make_map(enc, d_in[1], 64, (uint64_t)NBH * SK * 3, 64, TILE_ROWS, CU_TENSOR_MAP_SWIZZLE_128B, CU_TENSOR_MAP_L2_PROMOTION_NONE);
    p.v = make_map(enc, d_in[2], 64, (uint64_t)NBH * SK * 3, 64, TILE_ROWS, CU_TENSOR_MAP_SWIZZLE_128B, CU_TENSOR_MAP_L2_PROMOTION_NONE);
    p.wq = make_map(enc, d_in[3], NH * DH, DM, 48, 160, CU_TENSOR_MAP_SWIZZLE_NONE, WPROMO);
    p.wo = make_map(enc, d_in[4], DM, NH * DH, 32, DH, CU_TENSOR_MAP_SWIZZLE_64B, WPROMO);
    p.wg = make_map(enc, d_in[7], FF, DM, 32, 160, CU_TENSOR_MAP_SWIZZLE_64B, WPROMO);
    p.wu = make_map(enc, d_in[8], FF, DM, 32, 160, CU_TENSOR_MAP_SWIZZLE_64B, WPROMO);
    {
        const cuuint64_t dims[4] = {DM, 2, 8, FF / 16}, strides[3] = {8 * DM * 2, DM * 2, 16 * DM * 2};
        const cuuint32_t box[4] = {16, 2, 8, 12}, es[4] = {1, 1, 1, 1};
        enc(&p.wd, CU_TENSOR_MAP_DATA_TYPE_BFLOAT16, 4, d_in[9], dims, strides, box, es, CU_TENSOR_MAP_INTERLEAVE_NONE,
            CU_TENSOR_MAP_SWIZZLE_32B, WPROMO, CU_TENSOR_MAP_FLOAT_OOB_FILL_NONE);
    }
    p.x = (const __nv_bfloat16*)d_in[0];
    p.wr = (const __nv_bfloat16*)d_in[6];
    p.out = (__nv_bfloat16*)d_out;
    fused_decode_kernel<<<NCTAS, NTHREADS, SM_TOTAL, cudaStreamPerThread>>>(p);
}
```

```cpp
#include <cuda_runtime.h>
#include <cuda_bf16.h>
#include <cuda.h>
#include <stdint.h>

namespace {

constexpr int NB = 4, NH = 32, SK = 8192, DH = 192, DM = 640, FF = 1536;
constexpr int NBH = NB * NH;
constexpr int TILE = 64;
constexpr int UPB = SK / TILE;
constexpr int NUNITS = NBH * UPB;
constexpr int TILE_BYTES = TILE * DH * 2;
constexpr int TILE_ROWS = TILE * 3;
constexpr int NCTAS = 132;
constexpr int NQ_CTAS = 128;
constexpr int NE_CTAS = 112;
__host__ __device__ constexpr bool is_f(int cta) { return cta < NE_CTAS && cta % 14 < 11 && !(cta & 1); }
__host__ __device__ constexpr bool is_g(int cta) { return cta < NE_CTAS && cta % 14 < 11 && (cta & 1); }
__host__ __device__ constexpr int ffn_slice(int cta) { return cta / 14 * ((cta & 1) ? 5 : 6) + cta % 14 / 2; }

#define NWORK 2
#define LAG 2
#define NPOOL 768
#define RED0 116
#define RING 11
#define OREP 2
#define K0_AT_NS 1150
#define WO_AT_NS (K0_AT_NS + 2000)
#define K1_AT_NS (K0_AT_NS + 4400)
constexpr int KSWEEP_NS = 2000, WO_STEP_NS = 75;
#define FW_TICKET (NPOOL + 32)
#define FW_AT_NS 2090
#define FW_GAP 280
#define FW_MID 2100
#define FW_GAP2 200
#define HGATE_NS 700
#define SLOT_TICKS 9
#define SLOT_OPEN 3
#define PH_O 0
#define PH_H 8
#define PH_M 2
#define NPROBE 24
static_assert(FW_TICKET < NPOOL + NWORK * NCTAS, "every worker draws one ticket beyond the pool");
constexpr int NAUX = 8;
constexpr int NTHREADS = (NAUX + NWORK + 2) * 32;
constexpr int SPIN_MAX = 1 << 22;

constexpr int SM_KV = 0;
constexpr int SM_A = SM_KV + NWORK * TILE_BYTES;
constexpr int SM_W = SM_A + 61440;
constexpr int SM_X = SM_W + 81920;
constexpr int XPITCH = 648;
constexpr int HPITCH = 1344;
constexpr int SM_RED = SM_X + 5 * HPITCH + 64;
constexpr int SM_RED2 = SM_RED + 8 * 48 * 4 * 4;
constexpr int SM_MISC = SM_RED2 + 4096;
constexpr int BAR_WQ = SM_MISC, SM_SCRAP = SM_MISC + 32, BAR_WO = SM_MISC + 40, SM_SIDE = SM_MISC + 48, BAR_H = SM_MISC + 56, BAR_FW = SM_MISC + 64;
constexpr int BAR_KV = BAR_FW + 64;
constexpr int SM_TOTAL = BAR_KV + NWORK * 8;
static_assert(SM_W % 1024 == 0 && NB * XPITCH * 2 <= 4 * HPITCH && SM_RED % 128 == 0, "smem layout");

struct Params {
    CUtensorMap k, v;
    CUtensorMap wq;
    CUtensorMap wo;
    CUtensorMap wg, wu;
    CUtensorMap wd;
    const __nv_bfloat16 *x, *wr;
    __nv_bfloat16* out;
};

struct Early {
    uint32_t q[4][4][8];
    uint32_t umax[UPB];
};
struct Twin { uint32_t w[4][1024]; };
constexpr int PROBE = 1024 - 32;
#define LSTRIDE 16
struct State {
    Twin ax[3];
    Twin hx;
    Twin ox[(OREP + 1) / 2];
    Twin lx;
    float4 oacc[NBH * 64];
    float2 attn[NB][DM];
    uint32_t fw_time[32];
    float2 lsum[NBH][LSTRIDE];
    uint32_t score[NPOOL][32];
};
__host__ __device__ constexpr int oidx(int row, int grp) {
    return (row >> 2) * 256 + ((row & 1) * 2 + (grp >> 5)) * 64 + (row & 2) * 16 + (grp & 31);
}
constexpr int STATE_V4 = ((sizeof(State) / 32 + NQ_CTAS - 1) / NQ_CTAS) * 2;
static_assert(sizeof(State) % 32 == 0, "State is cleared in whole sectors");
static_assert(sizeof(Early) == 64 * 16, "an Early entry is cleared by 64 threads");
struct Scratch {
    State st;
    unsigned work[64];
    unsigned cnt_z[32];
    Early early[NBH];
    alignas(4096) float4 ring[RING][UPB][64];
};
constexpr size_t PAGE = 2u << 20;
static_assert(sizeof(Scratch) <= PAGE, "scratch must fit one page");
__device__ __align__(128) unsigned char g_raw[2 * PAGE];
__device__ __forceinline__ Scratch* scratch() {
    return reinterpret_cast<Scratch*>((reinterpret_cast<uintptr_t>(g_raw) + PAGE - 1) & ~(uintptr_t)(PAGE - 1));
}
#define g_early scratch()->early
#define g_st scratch()->st
#define g_ring scratch()->ring
#define g_cnt_z scratch()->cnt_z
#define g_work scratch()->work
#define ALL_LOADERS 0
#define TS(i)
#define TSW(i)
#define TS2(i)
#define TSI(n, i)
#define PH(i)
#define CK(i, dep)
#define ARR()
#define PROG(u)

__device__ __forceinline__ uint32_t s2u(const void* p) { return (uint32_t)__cvta_generic_to_shared(p); }
__device__ __forceinline__ void mbar_init(uint32_t bar, int cnt) {
    asm volatile("mbarrier.init.shared::cta.b64 [%0], %1;" :: "r"(bar), "r"(cnt) : "memory");
}
__device__ __forceinline__ void mbar_wait(uint32_t bar, uint32_t parity) {
    asm volatile("{\n.reg .pred p;\n.reg .u32 n;\nmov.u32 n, 0;\nWAIT_LOOP:\n"
                 "mbarrier.try_wait.parity.shared::cta.b64 p, [%0], %1;\n"
                 "@p bra WAIT_DONE;\nadd.u32 n, n, 1;\nsetp.lt.u32 p, n, %2;\n@p bra WAIT_LOOP;\nWAIT_DONE:\n}"
                 :: "r"(bar), "r"(parity), "n"(SPIN_MAX) : "memory");
}
__device__ __forceinline__ void request_tile(uint32_t dst, const CUtensorMap* tm, int unit, uint32_t bar, uint64_t pol) {
    asm volatile("{\n.reg .pred p;\nelect.sync _|p, 0xffffffff;\n"
                 "@p mbarrier.arrive.expect_tx.shared::cta.b64 _, [%2], %6;\n"
                 "@p cp.async.bulk.tensor.2d.shared::cluster.global.mbarrier::complete_tx::bytes.L2::cache_hint "
                 "[%0], [%1, {%3, %4}], [%2], %5;\n}"
                 :: "r"(dst), "l"(tm), "r"(bar), "r"(0), "r"(unit * TILE_ROWS), "l"(pol), "n"(TILE_BYTES) : "memory");
}
__device__ __forceinline__ void put_groups(void* dst, int mode, const float (&o)[6], float tag, float tag2) {
    asm volatile("{\n.reg .pred s, t;\n.reg .b128 u, v;\n.reg .b64 a, b;\n"
                 "setp.eq.s32 s, %1, 0;\nsetp.ne.s32 t, %1, 2;\nxor.b64 a, %0, 4096;\n"
                 "@t bra.uni SINGLE;\n"
                 "red.relaxed.gpu.global.add.v4.f32 [a], {%2,%3,%4,%8};\n"
                 "red.relaxed.gpu.global.add.v4.f32 [a+128], {%5,%6,%7,%9};\n"
                 "SINGLE:\n"
                 "@s bra.uni STORE;\n"
                 "red.relaxed.gpu.global.add.v4.f32 [%0], {%2,%3,%4,%8};\n"
                 "red.relaxed.gpu.global.add.v4.f32 [%0+128], {%5,%6,%7,%9};\n"
                 "STORE:\n"
                 "mov.b64 a, {%2, %3};\nmov.b64 b, {%4, %8};\nmov.b128 u, {a, b};\n"
                 "mov.b64 a, {%5, %6};\nmov.b64 b, {%7, %9};\nmov.b128 v, {a, b};\n"
                 "@s st.relaxed.gpu.global.b128 [%0], u;\n@s st.relaxed.gpu.global.b128 [%0+128], v;\n}"
                 :: "l"(dst), "r"(mode), "f"(o[0]), "f"(o[1]), "f"(o[2]), "f"(o[3]), "f"(o[4]), "f"(o[5]), "f"(tag), "f"(tag2) : "memory");
}
__device__ __forceinline__ void request_box(uint32_t dst, const CUtensorMap* tm, int col, int row, uint32_t bar, uint32_t bytes) {
    asm volatile("{\n.reg .pred p, q;\nelect.sync _|p, 0xffffffff;\nsetp.ne.and.u32 q, %5, 0, p;\n"
                 "@q mbarrier.arrive.expect_tx.shared::cta.b64 _, [%2], %5;\n"
                 "@p cp.async.bulk.tensor.2d.shared::cluster.global.mbarrier::complete_tx::bytes [%0], [%1, {%3, %4}], [%2];\n}"
                 :: "r"(dst), "l"(tm), "r"(bar), "r"(col), "r"(row), "r"(bytes) : "memory");
}
__device__ __forceinline__ uint32_t lds32(uint32_t addr) {
    uint32_t v;
    asm volatile("ld.shared.u32 %0, [%1];" : "=r"(v) : "r"(addr) : "memory");
    return v;
}
__device__ __forceinline__ void ldsm4(uint32_t (&r)[4], uint32_t addr) {
    asm volatile("ldmatrix.sync.aligned.m8n8.x4.shared.b16 {%0,%1,%2,%3}, [%4];"
                 : "=r"(r[0]), "=r"(r[1]), "=r"(r[2]), "=r"(r[3]) : "r"(addr) : "memory");
}
__device__ __forceinline__ void ldsm4t(uint32_t (&r)[4], uint32_t addr) {
    asm volatile("ldmatrix.sync.aligned.m8n8.x4.trans.shared.b16 {%0,%1,%2,%3}, [%4];"
                 : "=r"(r[0]), "=r"(r[1]), "=r"(r[2]), "=r"(r[3]) : "r"(addr) : "memory");
}
__device__ __forceinline__ void mma16816(float (&c)[4], const uint32_t (&a)[4], uint32_t b0, uint32_t b1) {
    asm volatile("mma.sync.aligned.m16n8k16.row.col.f32.bf16.bf16.f32 {%0,%1,%2,%3}, {%4,%5,%6,%7}, {%8,%9}, {%0,%1,%2,%3};"
                 : "+f"(c[0]), "+f"(c[1]), "+f"(c[2]), "+f"(c[3])
                 : "r"(a[0]), "r"(a[1]), "r"(a[2]), "r"(a[3]), "r"(b0), "r"(b1));
}
struct Warm {
    float c[4] = {};
    __device__ __forceinline__ void operator()() {
        asm volatile("mma.sync.aligned.m16n8k8.row.col.f32.bf16.bf16.f32 {%0,%1,%2,%3}, {%4,%4}, {%4}, {%0,%1,%2,%3};"
                     : "+f"(c[0]), "+f"(c[1]), "+f"(c[2]), "+f"(c[3]) : "r"(0));
    }
    __device__ __forceinline__ void done(uint32_t scrap) {
        asm volatile("{\n.reg .pred p;\nsetp.gt.f32 p, %1, 0f3f800000;\n@p st.shared.f32 [%0], %1;\n}" :: "r"(scrap), "f"(c[0]) : "memory");
    }
};
__device__ __forceinline__ uint4 ld_relaxed_v4(const void* p) {
    uint4 v;
    asm volatile("ld.relaxed.gpu.global.v4.u32 {%0,%1,%2,%3}, [%4];" : "=r"(v.x), "=r"(v.y), "=r"(v.z), "=r"(v.w) : "l"(p) : "memory");
    return v;
}
__device__ __forceinline__ float4 ld_relaxed_f4(const void* p) {
    float4 v;
    asm volatile("ld.relaxed.gpu.global.v4.f32 {%0,%1,%2,%3}, [%4];" : "=f"(v.x), "=f"(v.y), "=f"(v.z), "=f"(v.w) : "l"(p) : "memory");
    return v;
}
__device__ __forceinline__ float2 ld_relaxed_f2(const void* p) {
    float2 v;
    asm volatile("ld.relaxed.gpu.global.v2.f32 {%0,%1}, [%2];" : "=f"(v.x), "=f"(v.y) : "l"(p) : "memory");
    return v;
}
__device__ __forceinline__ float4 ld_relaxed_b128(const void* p) {
    float4 v;
    asm volatile("{\n.reg .b128 t;\n.reg .b64 a, b;\nld.relaxed.gpu.global.b128 t, [%4];\nmov.b128 {a, b}, t;\n"
                 "mov.b64 {%0, %1}, a;\nmov.b64 {%2, %3}, b;\n}" : "=f"(v.x), "=f"(v.y), "=f"(v.z), "=f"(v.w) : "l"(p) : "memory");
    return v;
}
__device__ __forceinline__ void st_relaxed_b128(void* p, float x, float y, float z, float w) {
    asm volatile("{\n.reg .b128 t;\n.reg .b64 a, b;\nmov.b64 a, {%1, %2};\nmov.b64 b, {%3, %4};\nmov.b128 t, {a, b};\n"
                 "st.relaxed.gpu.global.b128 [%0], t;\n}" :: "l"(p), "f"(x), "f"(y), "f"(z), "f"(w) : "memory");
}
__device__ __forceinline__ unsigned ld_acquire(const unsigned* p) {
    unsigned v;
    asm volatile("ld.acquire.gpu.global.u32 %0, [%1];" : "=r"(v) : "l"(p) : "memory");
    return v;
}
__device__ __forceinline__ void st_relaxed(void* p, uint32_t v) {
    asm volatile("st.relaxed.gpu.global.u32 [%0], %1;" :: "l"(p), "r"(v) : "memory");
}
__device__ __forceinline__ void red_f2(float* p, float a, float b) {
    asm volatile("red.relaxed.gpu.global.add.v2.f32 [%0], {%1,%2};" :: "l"(p), "f"(a), "f"(b) : "memory");
}
__device__ __forceinline__ void draw(int& ticket, unsigned* ctr, bool pred) {
    asm volatile("{\n.reg .pred p;\nsetp.ne.u32 p, %2, 0;\n@p atom.relaxed.gpu.global.inc.u32 %0, [%1], 0x7fffffff;\n}"
                 : "+r"(ticket) : "l"(ctr), "r"((uint32_t)pred) : "memory");
}
__device__ __forceinline__ void red_release(unsigned* p) {
    asm volatile("red.release.gpu.global.add.u32 [%0], 1;" :: "l"(p) : "memory");
}
__device__ __forceinline__ uint32_t ld_relaxed_u32(const void* p) {
    uint32_t v;
    asm volatile("ld.relaxed.gpu.global.u32 %0, [%1];" : "=r"(v) : "l"(p) : "memory");
    return v;
}
__device__ __forceinline__ float rcp_approx(float v) {
    float r;
    asm("rcp.approx.ftz.f32 %0, %1;" : "=f"(r) : "f"(v));
    return r;
}
__device__ __forceinline__ float ex2_approx(float v) {
    float e;
    asm("ex2.approx.ftz.f32 %0, %1;" : "=f"(e) : "f"(v));
    return e;
}
__device__ __forceinline__ float sigmoid_approx(float v) { return rcp_approx(1.0f + ex2_approx(v * -1.4426950408889634f)); }
__device__ __forceinline__ float sqrt_approx(float v) {
    float r;
    asm("sqrt.approx.ftz.f32 %0, %1;" : "=f"(r) : "f"(v));
    return r;
}
__device__ __forceinline__ bool all(bool v) { return __all_sync(0xffffffffu, v); }
__device__ __forceinline__ void wait_count(const unsigned* p, unsigned target) {
#pragma unroll 1
    for (int it = 0; it < SPIN_MAX; it++) {
        if (all(ld_acquire(p) >= target)) break;
        __nanosleep(400);
    }
}
__device__ __forceinline__ float wait_sum(const void* p, float n, int nap = 0) {
    float2 v;
#pragma unroll 1
    for (int it = 0; it < SPIN_MAX; it++) {
        v = ld_relaxed_f2(p);
        if (all(v.y >= n)) break;
        if (all(v.y == 0.f)) __nanosleep(600);
        else if (nap) __nanosleep(nap);
    }
    return v.x;
}
__device__ __forceinline__ void wait_row(int bh, float n) { wait_sum(g_st.lsum[bh], n); }
__device__ __forceinline__ void wait_row_o(int bh, float n) {
    wait_row(bh, n);
    if (bh >= RED0) return;
#pragma unroll 1
    for (int it = 0; it < SPIN_MAX; it++) {
        if (all(__uint_as_float(ld_relaxed_u32(&g_st.oacc[oidx(bh, 0)].w)) == UPB)) break;
        __nanosleep(300);
    }
}
constexpr uint32_t SLOT_K = (uint32_t)(((1ull << 32) + SLOT_TICKS - 1) / SLOT_TICKS);
#define SLOT_ASM(t, n, p, phase, k, open) \
    "mov.u32 " n ", 0;\nSLOT:\nmov.u32 " t ", %%globaltimer_lo;\nadd.u32 " n ", " n ", 1;\nsetp.lt.u32 " p ", " n ", 24;\nshr.u32 " t ", " t ", 5;\n" \
    "mad.lo.u32 " t ", " t ", " k ", " phase ";\nsetp.ge.and.u32 " p ", " t ", " open ", " p ";\n@" p " bra.uni SLOT;\n"
template <int PHASE> __host__ __device__ constexpr uint32_t slot_phase() { return SLOT_K / 2 - PHASE * SLOT_K; }
template <int PHASE> __device__ __forceinline__ void wait_slot() {
    if (PHASE < 0) return;
    asm volatile("{\n.reg .pred p;\n.reg .b32 t, n;\n" SLOT_ASM("t", "n", "p", "%0", "%1", "%2") "}"
                 :: "n"(slot_phase<PHASE>()), "n"(SLOT_K), "n"(SLOT_OPEN * SLOT_K) : "memory");
}
__device__ __forceinline__ void wait_time(uint32_t t) {
#pragma unroll 1
    for (int it = 0; it < SPIN_MAX; it++) {
        uint32_t now;
        asm volatile("mov.u32 %0, %%globaltimer_lo;" : "=r"(now));
        if (all((int)(now - t) >= 0)) break;
    }
}
__device__ __forceinline__ void wait_clock(uint32_t t, Warm& warm) { while (!all((int)(clock() - t) >= 0)) { warm(); } }
__device__ __forceinline__ uint32_t pack_bf16(float lo, float hi) {
    uint32_t r;
    asm("cvt.rn.bf16x2.f32 %0, %1, %2;" : "=r"(r) : "f"(hi), "f"(lo));
    return r;
}
__device__ __forceinline__ float bf16r(float v) { return __uint_as_float(pack_bf16(0.f, v)); }
__device__ __forceinline__ uint32_t nonzero(uint32_t w) { return w ? w : 0x80008000u; }
__device__ __forceinline__ uint32_t pack_neg(float lo, float hi) { return nonzero(pack_bf16(-lo, -hi)); }
__device__ __forceinline__ float lo_f(uint32_t v) { return __uint_as_float(v << 16); }
__device__ __forceinline__ float hi_f(uint32_t v) { return __uint_as_float(v & 0xffff0000u); }
__device__ __forceinline__ float warp_sum(float v) {
#pragma unroll
    for (int o = 16; o; o >>= 1) v += __shfl_xor_sync(0xffffffffu, v, o);
    return v;
}
__device__ __forceinline__ void layernorm20(float (&v)[20]) {
    float s = 0.f;
#pragma unroll
    for (int i = 0; i < 20; i++) s += v[i];
    const float mean = warp_sum(s) * (1.0f / DM);
    float q = 0.f;
#pragma unroll
    for (int i = 0; i < 20; i++) { const float d = v[i] - mean; q += d * d; }
    const float var = bf16r(warp_sum(q) * (1.0f / DM));
    const float m = bf16r(mean);
    const float rden = 1.0f / bf16r(sqrtf(bf16r(var + 1e-5f)));
#pragma unroll
    for (int i = 0; i < 20; i++) v[i] = bf16r(bf16r(v[i] - m) * rden);
}

__device__ __forceinline__ void moments(float m1, float m2, float& nmean, float& rden) {
    m1 *= 1.0f / DM;
    const float var = bf16r(fmaxf(fmaf(-m1, m1, m2 * (1.0f / DM)), 0.f));
    nmean = bf16r(m1);
    rden = rcp_approx(bf16r(sqrt_approx(bf16r(var + 1e-5f))));
}
__device__ __forceinline__ float sel4(int j, float a, float b, float c, float d) {
    float lo, hi, r;
    asm("{\n.reg .pred p;\nsetp.ne.s32 p, %3, 0;\nselp.f32 %0, %2, %1, p;\n}" : "=f"(lo) : "f"(a), "f"(b), "r"(j & 1));
    asm("{\n.reg .pred p;\nsetp.ne.s32 p, %3, 0;\nselp.f32 %0, %2, %1, p;\n}" : "=f"(hi) : "f"(c), "f"(d), "r"(j & 1));
    asm("{\n.reg .pred p;\nsetp.ne.s32 p, %3, 0;\nselp.f32 %0, %2, %1, p;\n}" : "=f"(r) : "f"(lo), "f"(hi), "r"(j & 2));
    return r;
}
template <typename T> __device__ __forceinline__ void pin(T*& p) { asm volatile("" : "+l"(p)); }
__device__ __forceinline__ void pin(uint32_t& v) { asm volatile("" : "+r"(v)); }
__device__ __forceinline__ void pin(float& v) { asm volatile("" : "+f"(v)); }
__device__ __forceinline__ uint32_t after(uint32_t n, float v) {
    asm volatile("{\n.reg .pred p;\nsetp.eq.u32 p, %1, 0x7fc1a5a5;\n@p add.u32 %0, %0, 32;\n}" : "+r"(n) : "r"(__float_as_uint(v)));
    return n;
}
__device__ __forceinline__ float2 lds64f(uint32_t addr) {
    float2 v;
    asm volatile("ld.shared.v2.f32 {%0,%1}, [%2];" : "=f"(v.x), "=f"(v.y) : "r"(addr) : "memory");
    return v;
}
__device__ __forceinline__ void sts32f(uint32_t addr, float v) { asm volatile("st.shared.f32 [%0], %1;" :: "r"(addr), "f"(v) : "memory"); }
template <int ID> __device__ __forceinline__ void fin_arrive() { asm volatile("bar.arrive %0, 288;" :: "n"(ID) : "memory"); }
template <int ID> __device__ __forceinline__ void fin_sync() { asm volatile("bar.sync %0, 288;" :: "n"(ID) : "memory"); }
template <int ID> __device__ __forceinline__ void fin_sync(uint32_t n) { asm volatile("bar.sync %0, %1;" :: "n"(ID), "r"(n) : "memory"); }
__device__ __forceinline__ float2 sum8(uint32_t addr, int pitch) {
    float2 t[8];
#pragma unroll
    for (int w = 0; w < 8; w++) t[w] = lds64f(addr + w * pitch);
    return make_float2(((t[0].x + t[1].x) + (t[2].x + t[3].x)) + ((t[4].x + t[5].x) + (t[6].x + t[7].x)),
                       ((t[0].y + t[1].y) + (t[2].y + t[3].y)) + ((t[4].y + t[5].y) + (t[6].y + t[7].y)));
}
__device__ __forceinline__ float4 sum4x4(uint32_t addr, int pitch) {
    float4 t[4];
#pragma unroll
    for (int w = 0; w < 4; w++)
        asm volatile("ld.shared.v4.f32 {%0,%1,%2,%3}, [%4];" : "=f"(t[w].x), "=f"(t[w].y), "=f"(t[w].z), "=f"(t[w].w) : "r"(addr + w * pitch) : "memory");
    return make_float4((t[0].x + t[1].x) + (t[2].x + t[3].x), (t[0].y + t[1].y) + (t[2].y + t[3].y),
                       (t[0].z + t[1].z) + (t[2].z + t[3].z), (t[0].w + t[1].w) + (t[2].w + t[3].w));
}
__device__ __forceinline__ void sts64f(uint32_t addr, float x, float y) {
    asm volatile("st.shared.v2.f32 [%0], {%1,%2};" :: "r"(addr), "f"(x), "f"(y) : "memory");
}
__device__ __forceinline__ uint4 lds128(uint32_t addr) {
    uint4 v;
    asm volatile("ld.shared.v4.u32 {%0,%1,%2,%3}, [%4];" : "=r"(v.x), "=r"(v.y), "=r"(v.z), "=r"(v.w) : "r"(addr) : "memory");
    return v;
}
__device__ __forceinline__ void ld_relaxed_v4_if(uint4& v, const void* p, bool pred) {
    asm volatile("{\n.reg .pred p;\nsetp.ne.u32 p, %5, 0;\n@p ld.relaxed.gpu.global.v4.u32 {%0,%1,%2,%3}, [%4];\n}"
                 : "+r"(v.x), "+r"(v.y), "+r"(v.z), "+r"(v.w) : "l"(p), "r"((uint32_t)pred) : "memory");
}
__device__ __forceinline__ void sts128f(uint32_t addr, float x, float y, float z, float w) {
    asm volatile("st.shared.v4.f32 [%0], {%1,%2,%3,%4};" :: "r"(addr), "f"(x), "f"(y), "f"(z), "f"(w) : "memory");
}
template <int NJ>
__device__ __forceinline__ void load_o(uint32_t (&ob)[3 * NJ][2], int bh, int J0, int j) {
    float4 v[NJ][4];
    float2 l;
#pragma unroll 1
    for (int it = 0; it < SPIN_MAX; it++) {
#pragma unroll
        for (int J = 0; J < NJ; J++) {
#pragma unroll
            for (int e = 0; e < 4; e++) v[J][e] = ld_relaxed_f4(&g_st.oacc[oidx(bh, j)] + oidx(0, (J0 + J) * 16 + e * 4));
        }
        l = ld_relaxed_f2(g_st.lsum[bh]);
        bool ok = l.y == UPB;
#pragma unroll
        for (int J = 0; J < NJ; J++) {
#pragma unroll
            for (int e = 0; e < 4; e++) ok &= v[J][e].w == UPB;
        }
        if (all(ok)) break;
    }
    const float rl = __fdividef(1.0f, l.x);
#pragma unroll
    for (int J = 0; J < NJ; J++) {
        ob[3 * J][0] = pack_bf16(v[J][0].x * rl, v[J][1].x * rl);     ob[3 * J][1] = pack_bf16(v[J][2].x * rl, v[J][3].x * rl);
        ob[3 * J + 1][0] = pack_bf16(v[J][0].y * rl, v[J][1].y * rl); ob[3 * J + 1][1] = pack_bf16(v[J][2].y * rl, v[J][3].y * rl);
        ob[3 * J + 2][0] = pack_bf16(v[J][0].z * rl, v[J][1].z * rl); ob[3 * J + 2][1] = pack_bf16(v[J][2].z * rl, v[J][3].z * rl);
    }
}
__device__ __forceinline__ int near_side(uint32_t sb) {
    uint32_t v;
    asm volatile("ld.volatile.shared.u32 %0, [%1];" : "=r"(v) : "r"(sb + SM_SIDE) : "memory");
    return v;
}
__device__ __forceinline__ void poll_row(uint4& a, uint4& b, uint2& c, const void* pa, const void* pb, const void* pc, uint32_t sa, uint32_t sc,
                                         bool arrive, bool nap, uint32_t bar, Warm& warm) {
    asm volatile("{\n.reg .pred p, q, r, s;\n.reg .b32 m, n, it;\n"
                 "setp.ne.u32 r, %19, 0;\nsetp.ne.u32 s, %20, 0;\nmov.u32 it, 0;\n"
                 "POLL:\n"
                 SLOT_ASM("m", "n", "p", "%23", "%24", "%25")
                 "ld.relaxed.gpu.global.v4.u32 {%0,%1,%2,%3}, [%14];\n"
                 "ld.relaxed.gpu.global.v4.u32 {%4,%5,%6,%7}, [%15];\n"
                 "ld.relaxed.gpu.global.v2.u32 {%8,%9}, [%16];\n"
                 "add.u32 it, it, 1;\nsetp.ge.u32 q, it, %21;\n"
                 "mov.u32 m, 0;\nmma.sync.aligned.m16n8k8.row.col.f32.bf16.bf16.f32 {%10,%11,%12,%13}, {m,m}, {m}, {%10,%11,%12,%13};\n"
                 "st.shared.v4.u32 [%17], {%0,%1,%2,%3};\n"
                 "st.shared.v4.u32 [%17+512], {%4,%5,%6,%7};\n"
                 "st.shared.v2.u32 [%18], {%8,%9};\n"
                 "min.u32 m, %0, %1;\nmin.u32 m, m, %2;\nmin.u32 n, %3, %4;\nmin.u32 n, n, %5;\nmin.u32 m, m, %6;\nmin.u32 m, m, %7;\n"
                 "min.u32 n, n, m;\nmin.u32 m, %8, %9;\nmin.u32 m, m, n;\n"
                 "setp.ne.or.u32 p, m, 0, q;\n"
                 "vote.sync.all.pred p, p, 0xffffffff;\n"
                 "and.pred q, p, r;\n"
                 "bar.warp.sync 0xffffffff;\n"
                 "@q mbarrier.arrive.shared::cta.b64 _, [%22];\n"
                 "@p bra.uni DONE;\n"
                 "@s nanosleep.u32 500;\n"
                 "bra.uni POLL;\n"
                 "DONE:\n}"
                 : "=&r"(a.x), "=&r"(a.y), "=&r"(a.z), "=&r"(a.w), "=&r"(b.x), "=&r"(b.y), "=&r"(b.z), "=&r"(b.w), "=&r"(c.x), "=&r"(c.y),
                   "+f"(warm.c[0]), "+f"(warm.c[1]), "+f"(warm.c[2]), "+f"(warm.c[3])
                 : "l"(pa), "l"(pb), "l"(pc), "r"(sa), "r"(sc), "r"((uint32_t)arrive), "r"((uint32_t)nap), "n"(SPIN_MAX), "r"(bar),
                   "n"(slot_phase<PH_H>()), "n"(SLOT_K), "n"(SLOT_OPEN * SLOT_K) : "memory");
}
__device__ __forceinline__ void aux_sync() { asm volatile("bar.sync 1, 256;" ::: "memory"); }

__global__ void __launch_bounds__(NTHREADS, 1)
fused_decode_kernel(const __grid_constant__ Params p) {
    extern __shared__ __align__(1024) unsigned char smem[];
    const uint32_t sb = s2u(smem);
    const int tid = threadIdx.x, cta = blockIdx.x;
    if (tid < 32 && cta < NQ_CTAS) {
        asm volatile("{\n.reg .pred p;\nelect.sync _|p, 0xffffffff;\n"
                     "@p mbarrier.init.shared::cta.b64 [%2], 1;\n"
                     "@p fence.mbarrier_init.release.cluster;\n"
                     "@p mbarrier.arrive.expect_tx.shared::cta.b64 _, [%2], 15360;\n"
                     "@p cp.async.bulk.tensor.2d.shared::cluster.global.mbarrier::complete_tx::bytes [%0], [%1, {%3, %4}], [%2];\n"
                     "@p mbarrier.init.shared::cta.b64 [%2+8], 1;\n@p mbarrier.init.shared::cta.b64 [%2+16], 1;\n"
                     "@p mbarrier.init.shared::cta.b64 [%2+24], 1;\n"
                     "@p fence.mbarrier_init.release.cluster;\n"
                     "@p mbarrier.arrive.expect_tx.shared::cta.b64 _, [%2+8], 15360;\n"
                     "@p cp.async.bulk.tensor.2d.shared::cluster.global.mbarrier::complete_tx::bytes [%0+15360], [%1, {%3, %5}], [%2+8];\n"
                     "@p mbarrier.arrive.expect_tx.shared::cta.b64 _, [%2+16], 15360;\n"
                     "@p cp.async.bulk.tensor.2d.shared::cluster.global.mbarrier::complete_tx::bytes [%0+30720], [%1, {%3, %6}], [%2+16];\n"
                     "@p mbarrier.arrive.expect_tx.shared::cta.b64 _, [%2+24], 15360;\n"
                     "@p cp.async.bulk.tensor.2d.shared::cluster.global.mbarrier::complete_tx::bytes [%0+46080], [%1, {%3, %7}], [%2+24];\n}"
                     :: "r"(sb + SM_W), "l"(&p.wq), "r"(sb + BAR_WQ), "r"(cta * 48), "r"(0), "r"(160), "r"(320), "r"(480) : "memory");
    }
    const int warp = __shfl_sync(0xffffffffu, tid >> 5, 0), lane = tid & 31;
    constexpr int grid = NCTAS;
    const int g = lane >> 2, j = lane & 3;
    uint32_t t_start;
    asm volatile("mov.u32 %0, %%globaltimer_lo;" : "=r"(t_start));
    TS(0);
    if (tid == 32) {
        mbar_init(sb + BAR_WO, 1);
        mbar_init(sb + BAR_H, 1);
#pragma unroll
        for (int i = 0; i < 8 + NWORK; i++) mbar_init(sb + BAR_FW + i * 8, 1);
        sts32f(sb + SM_SIDE, 0.f);
        asm volatile("fence.mbarrier_init.release.cluster;" ::: "memory");
        asm volatile("fence.proxy.async.shared::cta;" ::: "memory");
    }
    __syncthreads();
    if (warp >= NAUX + NWORK) {
        const int fw = warp - (NAUX + NWORK), fi = ffn_slice(cta);
        if (fw == 0) {
            if (cta < NQ_CTAS) {
#pragma unroll
                for (int i = lane; i < STATE_V4; i += 32)
                    if (cta * STATE_V4 + i < (int)(sizeof(State) / 16)) reinterpret_cast<uint4*>(&g_st)[cta * STATE_V4 + i] = make_uint4(0u, 0u, 0u, 0u);
                __syncwarp();
                if (lane == 0) red_release(g_cnt_z);
            }
            TSW(2); wait_count(g_cnt_z, NQ_CTAS); TSW(29);
            asm volatile("bar.arrive 2, %0;" :: "n"((NWORK + 2) * 32) : "memory");
            fin_arrive<3>();
        } else {
#pragma unroll 1
            for (int n = cta < NE_CTAS ? 5 : 4, i = n - 1; i >= 0; i--) {
                const int head = cta < NE_CTAS ? cta >> 2 : 28 + i;
                wait_time(t_start + WO_AT_NS + (NH - 1 - head) * WO_STEP_NS);
                request_box(sb + SM_A + i * 12288, &p.wo, cta < NE_CTAS ? (cta & 3) * 160 + i * 32 : (cta - NE_CTAS) * 32,
                            head * DH, sb + BAR_WO, i == n - 1 ? n * 12288 : 0);
            }
            asm volatile("bar.sync 2, %0;" :: "n"((NWORK + 2) * 32) : "memory");
            uint32_t best[2] = {~0u, ~0u};
#pragma unroll 1
            for (int i = 0; i < NPROBE; i++) {
#pragma unroll
                for (int c = 0; c < 2; c++) {
                    uint32_t t0 = clock(), t1 = t0;
                    int v = 0;
                    draw(v, &g_st.hx.w[c][PROBE], lane == 0);
                    asm volatile("{\n.reg .pred p;\nsetp.ne.u32 p, %1, 0xffffffff;\n@p mov.u32 %0, %%clock;\n}" : "+r"(t1) : "r"(v) : "memory");
                    best[c] = min(best[c], t1 - t0);
                }
                __nanosleep(1000);
            }
            if (lane == 0) sts32f(sb + SM_SIDE, __uint_as_float(best[1] < best[0]));
        }
        int job = cta;
        auto sum_rows = [&](int row_end) {
#pragma unroll 1
            for (; job < 8 * min(row_end, RED0); job += NCTAS) {
                const int row = job >> 3, grp = (job & 7) * 8 + (lane & 7);
                wait_row(row, UPB);
                const float4* src = &g_ring[row % RING][lane >> 3][grp];
                float sx = 0.f, sy = 0.f, sz = 0.f;
#pragma unroll 1
                for (int i = 0; i < 2; i++, src += 64 * 64) {
                    float4 v[16];
#pragma unroll 1
                    for (int it = 0; it < SPIN_MAX; it++) {
                        bool ok = true;
#pragma unroll
                        for (int k = 0; k < 16; k++) v[k] = ld_relaxed_b128(src + k * 4 * 64);
#pragma unroll
                        for (int k = 0; k < 16; k++) ok &= v[k].w == (float)(row + 1);
                        if (all(ok)) break;
                    }
#pragma unroll
                    for (int k = 0; k < 16; k++) { sx += v[k].x; sy += v[k].y; sz += v[k].z; }
                }
#pragma unroll
                for (int o = 8; o < 32; o <<= 1) {
                    sx += __shfl_xor_sync(0xffffffffu, sx, o); sy += __shfl_xor_sync(0xffffffffu, sy, o); sz += __shfl_xor_sync(0xffffffffu, sz, o);
                }
                if (lane < 8) st_relaxed_b128(&g_st.oacc[oidx(row, grp)], sx, sy, sz, UPB);
            }
        };
        const int ho0 = lane / 20 * 256 + lane % 20 * 4, ho1 = (lane + 32) / 20 * 256 + (lane + 32) % 20 * 4, ho2 = 3 * 256 + 16 + 2 * lane;
        uint32_t wr[10] = {};
        float wsum = 0.f;
        if (is_g(cta) && fw == 0) {
#pragma unroll
            for (int i = 0; i < 10; i++) {
                const int w = 4 * lane + 128 * (i >> 2) + (i & 3) - (i >= 8 ? 2 * lane : 0);
                wr[i] = *reinterpret_cast<const uint32_t*>(p.wr + (w >> 4) * 32 + (w & 3) * 8 + ((w >> 1) & 6));
                wsum += lo_f(wr[i]) + hi_f(wr[i]);
            }
            wsum = warp_sum(wsum);
        }
        const int fb = lane >> 3, fg = lane & 7;
        if (fw == 0) {
#pragma unroll
            for (int i = lane; i < DM / 2; i += 32) sts32f(sb + SM_X + 4 * HPITCH + i * 4, __uint_as_float(0x3f803f80u));
        }
        Warm warm;
        float nmean = 0.f, rden = 0.f, sig = 0.f;
#pragma unroll 1
        for (int b = 0; b < NB; b++) {
            const bool ffn = b >= NB - 2;
            if (fw == 0) {
                sum_rows((b + 1) * NH);
                if (ffn) asm volatile("bar.arrive 8, 64;" ::: "memory");
            } else if (ffn) {
                asm volatile("bar.sync 8, 64;" ::: "memory");
                if (b == NB - 1 && (is_f(cta) || is_g(cta) || ALL_LOADERS)) {
                    uint32_t t0 = 0;
#pragma unroll 1
                    for (int it = 0; it < SPIN_MAX; it++) {
                        t0 = ld_relaxed_u32(g_st.fw_time);
                        if (all(t0 != 0)) break;
                        __nanosleep(150);
                    }
                    asm volatile("fence.proxy.async.shared::cta;" ::: "memory");
                    wait_time(t0 + FW_AT_NS);
                    TSW(9);
                    uint32_t t = clock() + (is_f(cta) ? ((fi & 1) * 24 + (fi >> 1)) * FW_GAP / 48 : FW_MID + ((fi & 3) * 10 + (fi >> 2)) * FW_GAP2 / 40);
#pragma unroll 1
                    for (int i = 0; i < 8; i++) {
                        const uint32_t bar = sb + BAR_FW + i * 8;
                        if (is_f(cta)) {
                            wait_clock(t, warm);
                            request_box(sb + SM_W + i * 10240, (i & 1) ? &p.wu : &p.wg, fi * 32, (i >> 1) * 160, bar, 10240);
                            t += FW_GAP;
                        } else if (is_g(cta)) {
                            wait_clock(t, warm);
                            asm volatile("{\n.reg .pred p;\nelect.sync _|p, 0xffffffff;\n"
                                         "@p mbarrier.arrive.expect_tx.shared::cta.b64 _, [%2], 6144;\n"
                                         "@p cp.async.bulk.tensor.4d.shared::cluster.global.mbarrier::complete_tx::bytes [%0], [%1, {%3, %4, %4, %5}], [%2];\n}"
                                         :: "r"(sb + SM_W + i * 6144), "l"(&p.wd), "r"(bar), "r"(fi * 16), "r"(0), "r"(i * 12) : "memory");
                            t += FW_GAP2;
                        }
                    }
                }
                if (is_f(cta)) {
                    const uint32_t* src = &g_st.hx.w[near_side(sb)][min(fb, b) * 256 + 96];
                    float4 m;
#pragma unroll 1
                    for (int it = 0; it < SPIN_MAX; it++) {
                        wait_slot<PH_M>();
                        m = ld_relaxed_f4(src);
                        warm();
                        if (all(m.y + m.w == 2 * (NCTAS - NE_CTAS))) break;
                        if (b < NB - 1) __nanosleep(500);
                    }
                    moments(m.x, m.z, m.x, m.z);
                    sts64f(sb + SM_RED + 5120 + fb * 8, m.x, m.z);
                }
            }
            if (fw == 0 && cta >= NE_CTAS) {
                const int lc = cta - NE_CTAS, col = lc * 32 + 2 * (lane & 15);
                const uint32_t xv = *reinterpret_cast<const uint32_t*>(p.x + b * DM + col);
                uint32_t* dst = &(ffn ? g_st.hx.w : g_st.lx.w + 2)[lane >> 4][(b & 1) * 128 + lc / 5 * 256 + lc % 5 * 16 + (col & 6) * 2 + ((col >> 3) & 3)];
                uint32_t part = sb + SM_RED + (lane & 15) * 8;
                wait_row(b * NH + 28, 1);
                float4 early;
#pragma unroll 1
                for (int it = 0; it < SPIN_MAX; it++) {
                    early = ld_relaxed_f4(&g_st.attn[b][col]);
                    if (all(early.y == NE_CTAS / 4 && early.w == NE_CTAS / 4)) break;
                }
                if (early.x != 1.2345f && lane == 0) TS2(6);
                CK(1, __float_as_uint(early.x));
                const float x0 = -(lo_f(xv) + early.x), x1 = -(hi_f(xv) + early.z);
                fin_sync<4>(after(after(288, x0), x1));
                CK(2, lds32(sb + SM_RED));
                const float2 late = sum8(part, 128);
                const uint32_t hv = nonzero(pack_bf16(x0 - late.x, x1 - late.y));
                st_relaxed(dst, hv);
                if (ffn) st_relaxed(dst + 2048, hv);
                CK(3, 0);
                float m = lane < 16 ? lo_f(hv) + hi_f(hv) : fmaf(lo_f(hv), lo_f(hv), hi_f(hv) * hi_f(hv));
#pragma unroll
                for (int o = 1; o < 16; o <<= 1) m += __shfl_xor_sync(0xffffffffu, m, o);
                if ((lane & 14) == 0) red_f2(reinterpret_cast<float*>(&g_st.hx.w[lane & 1][b * 256 + 96 + (lane >> 4) * 2]), m, 1.f);
                fin_arrive<5>();
            }
            if (fw == 0 && (is_g(cta) || is_f(cta))) {
                const uint32_t* src = &(ffn ? g_st.hx.w : g_st.lx.w + 2)[near_side(sb) ^ (ffn && is_g(cta) ? 3 : 0)][(b & 1) * 128];
                const uint32_t hrow = sb + SM_X + b * HPITCH;
                wait_sum(b == NB - 1 ? (const void*)&g_st.lx.w[near_side(sb) ^ 1][3 * 256] : g_st.lsum[b * NH + NH - 1], UPB, 100);
                wait_clock(clock() + HGATE_NS * 2, warm);
                uint4 h0, h1;
                uint2 h2;
                poll_row(h0, h1, h2, src + ho0, src + ho1, src + ho2, hrow + lane * 16, hrow + 1024 + lane * 8, ffn && lane == 0, b < NB - 1, sb + BAR_H, warm);
                CK(4, h0.x);
                if (is_g(cta)) {
                    const uint32_t hw[10] = {h0.x, h0.y, h0.z, h0.w, h1.x, h1.y, h1.z, h1.w, h2.x, h2.y};
                    float m1 = 0.f, m2 = 0.f, rr = 0.f;
#pragma unroll
                    for (int i = 0; i < 10; i++) {
                        const float v0 = lo_f(hw[i]), v1 = hi_f(hw[i]);
                        m1 += v0 + v1;
                        m2 = fmaf(v0, v0, fmaf(v1, v1, m2));
                        rr = fmaf(v0, lo_f(wr[i]), fmaf(v1, hi_f(wr[i]), rr));
                    }
                    moments(warp_sum(m1), warp_sum(m2), m1, m2);
                    const float sg = bf16r(sigmoid_approx(bf16r((m1 * wsum - warp_sum(rr)) * m2)));
                    if (fb == b) { nmean = m1; rden = m2; sig = sg; }
                    __syncwarp();
                    if (ffn) {
                        const int yj = 2 * (fb & 1) + (fb >> 1);
                        uint32_t ypart = sb + SM_RED2 + yj * 128 + ((fg + 2 * yj) & 7) * 16;
                        __nv_bfloat16* out = p.out + fb * DM + fi * 16 + fg;
                        const float2 hw2 = lds64f(sb + SM_X + fb * HPITCH + ((fi >> 1) * 16 + (fg & 6) * 2 + (fi & 1) * 2) * 4);
                        const uint32_t w0 = __float_as_uint(hw2.x), w1 = __float_as_uint(hw2.y);
                        const float nh0 = (fg & 1) ? hi_f(w0) : lo_f(w0), nh1 = (fg & 1) ? hi_f(w1) : lo_f(w1);
                        const float ln0 = bf16r(bf16r(nmean - nh0) * rden) - nh0, ln1 = bf16r(bf16r(nmean - nh1) * rden) - nh1;
                        pin(ypart); pin(out);
                        fin_sync<6>(after(after(after(288, sig), ln0), ln1));
                        CK(10, lds32(ypart));
                        const float4 ya = sum4x4(ypart, 512), yb = sum4x4(ypart + 2048, 512);
                        const float4 y = make_float4(ya.x + yb.x, ya.y + yb.y, ya.z + yb.z, ya.w + yb.w);
                        const float y0 = -(((fb & 1) ? y.y : y.x) + __shfl_xor_sync(0xffffffffu, (fb & 1) ? y.x : y.y, 8));
                        const float y1 = -(((fb & 1) ? y.w : y.z) + __shfl_xor_sync(0xffffffffu, (fb & 1) ? y.z : y.w, 8));
                        const uint32_t ov = pack_bf16(fmaf(y0, sig, ln0), fmaf(y1, sig, ln1));
                        asm volatile("{\n.reg .pred p;\n.reg .b16 lo, hi;\nsetp.ne.u32 p, %2, 0;\nmov.b32 {lo, hi}, %1;\n"
                                     "@p st.global.u16 [%0], lo;\n@p st.global.u16 [%0+16], hi;\n"
                                     "@p exit;\n"
                                     "}" :: "l"(out), "r"(ov), "r"((uint32_t)(b == NB - 1)) : "memory");
                        CK(11, 0);
                        if (lane == 0) TS2(13);
                    }
                }
            }
            if (is_f(cta) && ffn) {
                const int ks = (2 * fi + fw) % 12;
                const int far = near_side(sb) ^ 1;
                uint32_t* dst = &g_st.ax[ks >> 2].w[(~b & 1) * 2 + far][(fi / 6) * 128 + (ks & 3) * 32 + fb * 8 + (fg & 1) * 4 + ((fg >> 1) ^ (ks & 1))];
                uint32_t* dst2 = dst + (far ? -1024 : 1024);
                uint32_t part = sb + SM_RED + fw * 2560 + fb * 128 + ((fg + (fb & 2)) & 7) * 16;
                uint32_t psum = sb + SM_RED + fw * 2560 + 4 * 128 + ((fg + 4) & 7) * 16;
                pin(dst); pin(part); pin(psum);
                asm volatile("bar.sync 4, 320;" ::: "memory");
                CK(6, lds32(part));
                const float4 d = sum4x4(part, 640), cs = sum4x4(psum, 640);
                const float2 mo = lds64f(sb + SM_RED + 5120 + fb * 8);
                nmean = mo.x; rden = mo.y;
                const float g0 = fmaf(nmean, cs.x, -d.x), g1 = fmaf(nmean, cs.y, -d.y), ke = rden * -1.4426950408889634f, r2 = rden * rden;
                const float p0 = g0 * fmaf(-nmean, cs.z, d.z) * r2, p1 = g1 * fmaf(-nmean, cs.w, d.w) * r2;
                const uint32_t av = nonzero(pack_bf16(p0 * rcp_approx(1.0f + ex2_approx(g0 * ke)), p1 * rcp_approx(1.0f + ex2_approx(g1 * ke))));
                st_relaxed(dst, av);
                st_relaxed(dst2, av);
                CK(7, 0);
            }
        }
        warm.done(sb + SM_SCRAP);
        if (cta == 0 && tid == (NAUX + NWORK) * 32) { g_work[0] = 0; g_work[32] = 0; g_cnt_z[0] = 0; }
        return;
    }
    if (warp >= NAUX) {
        const int wk = warp - NAUX;
        const uint32_t bar = sb + BAR_KV + wk * 8;
        const uint32_t buf = sb + SM_KV + wk * TILE_BYTES;
        uint64_t pol;
        asm volatile("createpolicy.fractional.L2::evict_first.b64 %0, 1.0;" : "=l"(pol));
        const int nstatic = NWORK * grid;
        constexpr int POOL0 = NUNITS - NPOOL;
        int uk = wk * grid + cta;
        wait_time(t_start + K0_AT_NS + uk * KSWEEP_NS / nstatic);
        request_tile(buf, &p.k, uk, bar, pol);
        uint32_t koff[3], voff[3];
        {
            const int r = lane & 7, hf = (lane >> 3) & 1;
            const int kkey = hf ? 8 + (r ^ 1) : r;
            const int vh = lane >> 4;
            const int vkey = ((r & 1) ? 8 : 0) + (vh ? (r ^ 1) : r);
#pragma unroll
            for (int b = 0; b < 3; b++) {
                const int rk = 3 * kkey + b, rv = 3 * vkey + b;
                koff[b] = buf + rk * 128 + (((lane >> 4) ^ (rk & 7)) << 4);
                voff[b] = buf + rv * 128 + ((hf ^ (rv & 7)) << 4);
            }
        }
        uint32_t phase = 0;
        uint32_t qf[12][2];
        auto load_q = [&](int u) {
            const uint32_t* q = g_early[u / UPB].q[0][j];
#pragma unroll
            for (int i = 0; i < 4; i++) {
                const uint4 a = ld_relaxed_v4(q + i * 32);
                const float2 c = ld_relaxed_f2(q + i * 32 + 4);
                qf[3 * i][0] = a.x; qf[3 * i][1] = a.y; qf[3 * i + 1][0] = a.z; qf[3 * i + 1][1] = a.w;
                qf[3 * i + 2][0] = __float_as_uint(c.x); qf[3 * i + 2][1] = __float_as_uint(c.y);
            }
        };
        load_q(uk);
        int uq[LAG];
        uint32_t sq[LAG];
#pragma unroll
        for (int i = 0; i < LAG; i++) { uq[i] = -1; sq[i] = 0; }
        uint4 mv = make_uint4(0u, 0u, 0u, 0u);
        float freed = UPB;
        while (true) {
            const int uv = uq[0];
            uint32_t sv = sq[0];
#pragma unroll
            for (int i = 0; i + 1 < LAG; i++) { uq[i] = uq[i + 1]; sq[i] = sq[i + 1]; }
            uq[LAG - 1] = uk;
            if (uk < NUNITS) {
                PH(7);
#pragma unroll 1
                for (int it = 0; it < SPIN_MAX; it++) {
                    uint32_t lo = 0xffffffffu;
#pragma unroll
                    for (int i = 0; i < 12; i++) lo = min(lo, min(qf[i][0], qf[i][1]));
                    if (all(lo != 0)) break;
                    __nanosleep(250);
                    load_q(uk);
                }
                mbar_wait(bar, phase); phase ^= 1;
                PH(0); ARR();
                TSI(0, 16); TSI(1, 18);
                float acc[2][4][4] = {};
#pragma unroll
                for (int ks = 0; ks < 12; ks++) {
#pragma unroll
                    for (int mt = 0; mt < 4; mt++) {
                        uint32_t a[4];
                        ldsm4(a, (koff[ks >> 2] ^ ((ks & 3) << 5)) + mt * 6144);
                        mma16816(acc[ks & 1][mt], a, qf[ks][0], qf[ks][1]);
                    }
                }
                PH(1);
                TSI(0, 17); TSI(1, 19);
                if (uk < nstatic) wait_time(t_start + K1_AT_NS + uk * KSWEEP_NS / nstatic);
                if (uv < NUNITS) request_tile(buf, uv >= 0 ? &p.v : &p.k, uv >= 0 ? uv : uk + nstatic, bar, pol);
                const float sa = sel4(j, acc[0][0][0], acc[0][1][0], acc[0][2][0], acc[0][3][0]) + sel4(j, acc[1][0][0], acc[1][1][0], acc[1][2][0], acc[1][3][0]);
                const float sc = sel4(j, acc[0][0][2], acc[0][1][2], acc[0][2][2], acc[0][3][2]) + sel4(j, acc[1][0][2], acc[1][1][2], acc[1][2][2], acc[1][3][2]);
                const uint32_t raw = pack_bf16(sa, sc);
                const float scale = -0.07216878364870322f;
                const uint32_t sk = pack_bf16(lo_f(raw) * scale, hi_f(raw) * scale);
                sq[LAG - 1] = sk;
                if (uk >= POOL0) st_relaxed(&g_st.score[uk - POOL0][lane], sk ? sk : 0x80008000u);
                int a = (int)(sk << 16), b = (int)(sk & 0xffff0000u);
                a ^= (a >> 31) & 0x7fff0000; b ^= (b >> 31) & 0x7fff0000;
                const int mx = __reduce_max_sync(0xffffffffu, max(a, b));
                if (lane == 0) st_relaxed(&g_early[uk / UPB].umax[uk % UPB], (uint32_t)mx | 1u);
            }
            if (uv < 0) {
                uk += nstatic;
                load_q(uk);
                continue;
            }
            if (uv >= NUNITS) break;
            const int bh = uv / UPB;
#pragma unroll 1
            for (int it = 0; it < SPIN_MAX; it++) {
                if (all((mv.x & mv.y & mv.z & mv.w & 1u) && (uv < POOL0 || sv != 0) && freed == UPB)) break;
                mv = ld_relaxed_v4(&g_early[bh].umax[lane * 4]);
                if (bh >= RING && bh < RED0) freed = __uint_as_float(ld_relaxed_u32(&g_st.oacc[oidx(bh - RING, (lane & 7) * 8)].w));
                if (uv >= POOL0) sv = ld_relaxed_u32(&g_st.score[uv - POOL0][lane]);
            }
            PH(2); CK(8, sv);
            int un = NUNITS, vn = 0;
            draw(un, g_work, uk < NUNITS && lane == 0);
            uint32_t tdraw;
            asm volatile("mov.u32 %0, %%globaltimer_lo;" : "=r"(tdraw));
            draw(vn, g_work + 32, uq[0] >= POOL0 && lane == 0);
            int mx = __reduce_max_sync(0xffffffffu, max(max((int)mv.x, (int)mv.y), max((int)mv.z, (int)mv.w))) & 0xffff0000;
            mx ^= (mx >> 31) & 0x7fff0000;
            const float m = __int_as_float(mx);
            const float l2e = 1.4426950408889634f;
            const uint32_t pp = pack_bf16(exp2f((lo_f(sv) - m) * l2e), exp2f((hi_f(sv) - m) * l2e));
            uint32_t pb[8];
#pragma unroll
            for (int t = 0; t < 4; t++) {
                pb[2 * t] = __shfl_sync(0xffffffffu, pp, 8 * j + t);
                pb[2 * t + 1] = __shfl_sync(0xffffffffu, pp, 8 * j + 4 + t);
            }
            float lacc[4] = {};
            const uint32_t ones[4] = {0x3f803f80u, 0x3f803f80u, 0x3f803f80u, 0x3f803f80u};
#pragma unroll
            for (int t = 0; t < 4; t++) mma16816(lacc, ones, pb[2 * t], pb[2 * t + 1]);
            if (uv < nstatic) {
                asm volatile("bar.sync 2, %0;" :: "n"((NWORK + 2) * 32) : "memory");
                TSW(3);
            }
            const int grp = 16 * j + 4 * (g & 1) + (g >> 1);
            uint32_t mode = (bh >= RED0) + (bh >= NBH - 4);
            float tag = mode ? 1.f : (float)(bh + 1), tag2 = fmaf(__uint_as_float(voff[0]), 0.f, tag);
            void* dst = mode == 0 ? (void*)&g_ring[bh % RING][uv % UPB][grp] :
                        mode == 1 ? (void*)&g_st.oacc[oidx(bh, grp)] : (void*)&g_st.ox[0].w[uv % OREP * 2 + (~(near_side(sb) ^ uv % OREP) & 1)][oidx(bh & 3, grp) * 4];
            if (mode == 2 && lane < 2) red_f2(reinterpret_cast<float*>(&g_st.lx.w[lane][(bh & 3) * 256]), lacc[0], 1.f);
            CK(10, __float_as_uint(lacc[0]));
            un = __shfl_sync(0xffffffffu, un, 0) + (LAG + 1) * nstatic;
            vn = __shfl_sync(0xffffffffu, vn, 0);
            if (uq[0] >= POOL0) uq[0] = POOL0 + vn;
            if (vn == FW_TICKET && lane == 0) st_relaxed(g_st.fw_time, tdraw | 1u);
            if (uq[0] < NUNITS && un >= NUNITS) {
                mv = ld_relaxed_v4(&g_early[uq[0] / UPB].umax[lane * 4]);
                if (uq[0] < RED0 * UPB) freed = 0.f;
                if (uq[0] >= POOL0) sq[0] = ld_relaxed_u32(&g_st.score[uq[0] - POOL0][lane]);
            }
            pin(dst); pin(mode); pin(tag); pin(tag2); pin(voff[0]); pin(voff[1]); pin(voff[2]);
            PH(3); CK(9, vn);
            mbar_wait(bar, phase); phase ^= 1;
            PH(4); ARR(); CK(12, lds32(buf));
            float acc[12][4] = {};
#pragma unroll
            for (int t = 0; t < 4; t++) {
#pragma unroll
                for (int mt = 0; mt < 12; mt++) {
                    uint32_t a[4];
                    ldsm4t(a, (voff[mt >> 2] ^ ((mt & 3) << 5)) + t * 6144);
                    mma16816(acc[mt], a, pb[2 * t], pb[2 * t + 1]);
                }
            }
            PH(5);
            if (lane == 0) PROG(un);
            if (un < NUNITS || uq[0] < NUNITS) request_tile(buf, un < NUNITS ? &p.k : &p.v, un < NUNITS ? un : uq[0], bar, pol);
            if (un < NUNITS || uq[0] < NUNITS) CK(11, 0);
            float o[6];
#pragma unroll
            for (int e = 0; e < 6; e++) {
                const int q = e % 3, c = (e / 3) * 2;
                o[e] = sel4(j, acc[q][c], acc[3 + q][c], acc[6 + q][c], acc[9 + q][c]);
            }
            put_groups(dst, mode, o, tag, tag2);
            CK(13, 0);
            if (un < NUNITS) load_q(un);
            if (lane == 0) red_f2(&g_st.lsum[bh][0].x, lacc[0], 1.f);
            PH(6);
            if (uq[0] >= NUNITS && un >= NUNITS) break;
            uk = un;
            if (uq[0] < NUNITS && un < NUNITS) {
                const int nb = uq[0] / UPB;
                mv = ld_relaxed_v4(&g_early[nb].umax[lane * 4]);
                freed = nb >= RING && nb < RED0 ? __uint_as_float(ld_relaxed_u32(&g_st.oacc[oidx(nb - RING, (lane & 7) * 8)].w)) : UPB;
                if (uq[0] >= POOL0) sq[0] = ld_relaxed_u32(&g_st.score[uq[0] - POOL0][lane]);
            }
        }
        TSW(4 + wk);
        return;
    }

    __nv_bfloat16* xs = reinterpret_cast<__nv_bfloat16*>(smem + SM_X);
    float* red = reinterpret_cast<float*>(smem + SM_RED);
    const int frow = (lane & 7) + ((lane >> 4) << 3), fcol = (lane >> 3) & 1;
    const uint32_t f64b = sb + (frow * 4 + (fcol ^ ((frow >> 1) & 3))) * 16;
    if (cta < NQ_CTAS) {
        TS(26);
        if (warp >= 4) {
            uint2 xr[5];
#pragma unroll
            for (int i = 0; i < 5; i++) xr[i] = *reinterpret_cast<const uint2*>(p.x + (warp - 4) * DM + i * 128 + lane * 4);
            float v[20];
#pragma unroll
            for (int i = 0; i < 5; i++) {
                v[4 * i] = lo_f(xr[i].x); v[4 * i + 1] = hi_f(xr[i].x); v[4 * i + 2] = lo_f(xr[i].y); v[4 * i + 3] = hi_f(xr[i].y);
            }
            layernorm20(v);
#pragma unroll
            for (int i = 0; i < 5; i++)
                *reinterpret_cast<uint2*>(xs + (warp - 4) * XPITCH + i * 128 + lane * 4) =
                    make_uint2(pack_bf16(v[4 * i], v[4 * i + 1]), pack_bf16(v[4 * i + 2], v[4 * i + 3]));
        }
        aux_sync();
        TS(27);
        mbar_wait(sb + BAR_WQ + (warp >> 1) * 8, 0);
        TS(1);
        const uint32_t xfrag = sb + SM_X + ((g & 3) * XPITCH + 2 * j) * 2;
        float acc[3][4] = {};
#pragma unroll
        for (int s = 0; s < 5; s++) {
            const int ks = warp * 5 + s;
            const uint32_t b0 = lds32(xfrag + ks * 32), b1 = lds32(xfrag + ks * 32 + 16);
            const int row = ks * 16 + frow;
#pragma unroll
            for (int mt = 0; mt < 3; mt++) {
                uint32_t a[4];
                ldsm4t(a, sb + SM_W + (row * 6 + 2 * mt + fcol) * 16);
                mma16816(acc[mt], a, b0, b1);
            }
        }
        if (j < 2) {
#pragma unroll
            for (int mt = 0; mt < 3; mt++) {
                *reinterpret_cast<float2*>(red + warp * 216 + mt * 72 + g * 4 + 2 * j) = make_float2(acc[mt][0], acc[mt][1]);
                *reinterpret_cast<float2*>(red + warp * 216 + mt * 72 + 36 + g * 4 + 2 * j) = make_float2(acc[mt][2], acc[mt][3]);
            }
        }
        aux_sync();
        if (warp < 4) {
            const float* src = red + min(g, 5) * 36 + warp * 8 + j;
            float s0 = 0.f, s1 = 0.f;
#pragma unroll
            for (int w = 0; w < 8; w++) { s0 += src[w * 216]; s1 += src[w * 216 + 4]; }
            st_relaxed(&g_early[j * NH + (cta >> 2)].q[cta & 3][warp][g], pack_neg(s0, s1));
        }
        TS(28);
    }
    fin_sync<3>();
    mbar_wait(sb + BAR_WO, 0);
    TS(7);
    uint32_t part = sb + SM_RED + (warp * 32 + 8 * j + g) * 4;

#pragma unroll 1
    for (int b = 0; b < NB; b++) {
        if (cta >= NE_CTAS) {
            uint32_t a[6][2][4];
#pragma unroll
            for (int s = 0; s < 6; s++) {
#pragma unroll
                for (int mt = 0; mt < 2; mt++) ldsm4t(a[s][mt], (f64b ^ (mt * 32)) + SM_A + (warp * 6 + s) * 1024);
            }
            const int bh = b * NH + 28 + (warp >> 1);
            const int side = near_side(sb) ^ 1;
            const void* osrc[OREP];
#pragma unroll
            for (int c = 0; c < OREP; c++)
                osrc[c] = b == NB - 1 ? (const void*)&g_st.ox[c >> 1].w[side ^ (c & 1) * 3][oidx(bh & 3, (warp & 1) * 32 + lane) * 4] : &g_st.oacc[oidx(bh, (warp & 1) * 32 + lane)];
            const void* lsrc = b == NB - 1 ? (const void*)&g_st.lx.w[side][(bh & 3) * 256] : g_st.lsum[bh];
            wait_row_o(bh, 1);
            const float rl = rcp_approx(wait_sum(lsrc, UPB)) * (b == NB - 1 ? 1.f : 1.f / OREP), full = b == NB - 1 ? UPB : UPB * OREP;
            float4 ov;
            float px, py, pz;
            Warm warm;
#pragma unroll 1
            for (int it = 0; it < SPIN_MAX; it++) {
                wait_slot<PH_O>();
                float4 oc[OREP];
#pragma unroll
                for (int c = 0; c < OREP; c++) oc[c] = ld_relaxed_f4(osrc[c]);
                warm();
                ov = oc[0];
#pragma unroll
                for (int c = 1; c < OREP; c++) { ov.x += oc[c].x; ov.y += oc[c].y; ov.z += oc[c].z; ov.w += oc[c].w; }
                ov.x *= rl; ov.y *= rl; ov.z *= rl;
                px = __shfl_xor_sync(0xffffffffu, ov.x, 4); py = __shfl_xor_sync(0xffffffffu, ov.y, 4); pz = __shfl_xor_sync(0xffffffffu, ov.z, 4);
                if (all(ov.w == full)) break;
            }
            CK(0, __float_as_uint(ov.x));
            if (ov.x != 1.2345f && warp == 7) TSW(14);
            const uint32_t w[3] = {pack_bf16(ov.x, px), pack_bf16(ov.y, py), pack_bf16(ov.z, pz)};
            float acc[2][2][4] = {};
#pragma unroll
            for (int s = 0; s < 6; s++) {
                const uint32_t b0 = __shfl_sync(0xffffffffu, w[s % 3], (s / 3) * 16 + j);
                const uint32_t b1 = __shfl_sync(0xffffffffu, w[s % 3], (s / 3) * 16 + 8 + j);
#pragma unroll
                for (int mt = 0; mt < 2; mt++) mma16816(acc[mt][s & 1], a[s][mt], b0, b1);
            }
            sts32f(part, sel4(j, acc[0][0][0] + acc[0][1][0], acc[0][0][2] + acc[0][1][2], acc[1][0][0] + acc[1][1][0], acc[1][0][2] + acc[1][1][2]));
            CK(1, 0);
            fin_arrive<4>();
            warm.done(sb + SM_SCRAP);
            fin_sync<5>();
            if (cta < NE_CTAS + 4 && tid < 64) reinterpret_cast<uint4*>(&g_early[b * NH + 28 + cta - NE_CTAS])[tid] = make_uint4(0u, 0u, 0u, 0u);
        } else {
            const int bh = b * NH + (cta >> 2);
            if (warp == 0) wait_row_o(bh, UPB);
            aux_sync();
            if (warp < 5) {
                uint32_t ob[12][2];
                load_o<4>(ob, bh, 0, j);
                float acc[2][2][4] = {};
#pragma unroll
                for (int ks = 0; ks < 12; ks++) {
#pragma unroll
                    for (int mt = 0; mt < 2; mt++) {
                        uint32_t a[4];
                        ldsm4t(a, (f64b ^ (mt * 32)) + SM_A + warp * 12288 + ks * 1024);
                        mma16816(acc[mt][ks & 1], a, ob[ks][0], ob[ks][1]);
                    }
                }
                red_f2(&g_st.attn[b][(cta & 3) * 160 + warp * 32 + 8 * j + g].x,
                       sel4(j, acc[0][0][0] + acc[0][1][0], acc[0][0][2] + acc[0][1][2], acc[1][0][0] + acc[1][1][0], acc[1][0][2] + acc[1][1][2]), 1.f);
                TS(8);
            } else if (warp > 5 && (cta & 3) == 0) {
                reinterpret_cast<uint4*>(&g_early[bh])[tid - 192] = make_uint4(0u, 0u, 0u, 0u);
            }
        }
        if (b < NB - 2) continue;

        if (is_f(cta)) {
            uint32_t ga[10][2][4];
            uint4 hv[5];
            const uint32_t hfrag = sb + SM_X + min(g, 4) * HPITCH + ((warp >> 1) * 80 + 4 * j) * 4;
            if (b == NB - 1) mbar_wait(sb + BAR_FW + warp * 8, 0);
            if (warp == 7) TSW(10);
            CK(12, lds32(sb + SM_W));
#pragma unroll
            for (int s = 0; s < 10; s++) {
#pragma unroll
                for (int mt = 0; mt < 2; mt++) ldsm4t(ga[s][mt], (f64b ^ (mt * 32)) + SM_W + (warp * 10 + s) * 1024);
            }
            const uint32_t gpart = sb + SM_RED + (warp >> 1) * 640 + j * 256 + ((g + 2 * j) & 7) * 16 + (warp & 1) * 8;
            mbar_wait(sb + BAR_H, b & 1);
#pragma unroll
            for (int s = 0; s < 5; s++) hv[s] = lds128(hfrag + s * 64);
            CK(4, hv[0].x);
            float acc[2][2][4] = {};
#pragma unroll
            for (int s = 0; s < 10; s++) {
#pragma unroll
                for (int mt = 0; mt < 2; mt++)
                    mma16816(acc[mt][s & 1], ga[s][mt], (s & 1) ? hv[s >> 1].z : hv[s >> 1].x, (s & 1) ? hv[s >> 1].w : hv[s >> 1].y);
            }
#pragma unroll
            for (int mt = 0; mt < 2; mt++) {
                if (j < 3) sts64f(gpart + mt * 2560, acc[mt][0][0] + acc[mt][1][0], acc[mt][0][2] + acc[mt][1][2]);
                if (j < 2) sts64f(gpart + mt * 2560 + 128, acc[mt][0][1] + acc[mt][1][1], acc[mt][0][3] + acc[mt][1][3]);
            }
            CK(5, 0);
            asm volatile("bar.arrive 4, 320;" ::: "memory");
        } else if (is_g(cta)) {
            const uint32_t* asrc = &g_st.ax[0].w[(~b & 1) * 2 + near_side(sb)][warp * 128 + ((g >> 2) * 2 + (j >> 1)) * 32 + (g & 3) * 8 + (j & 1) * 4];
            const uint32_t ypart = sb + SM_RED2 + warp * 512 + j * 128 + ((g + 2 * j) & 7) * 16;
            uint32_t wb[12][4];
            uint4 va[3] = {};
            uint32_t lo[3] = {};
            auto ask = [&]() {
#pragma unroll
                for (int i = 0; i < 3; i++) ld_relaxed_v4_if(va[i], asrc + i * 4096, lo[i] == 0);
            };
            auto complete = [&]() {
#pragma unroll
                for (int i = 0; i < 3; i++) lo[i] = min(min(va[i].x, va[i].y), min(va[i].z, va[i].w));
                return all(min(lo[0], min(lo[1], lo[2])) != 0);
            };
            const int jj = (lane & 7) >> 1, q = jj >> 1, hi = lane >> 4;
            const uint32_t wsrc = sb + SM_W + warp * 6144 + q * 512 + ((hi ^ q) * 4 + (jj & 1) * 2 + (lane & 1)) * 32 + ((fcol ^ hi ^ q) << 4);
            mbar_wait(sb + BAR_H, b & 1);
            if (b == NB - 1) mbar_wait(sb + BAR_FW + warp * 8, 0);
            if (warp == 7) TSW(11);
            CK(13, lds32(sb + SM_W));
            ask();
#pragma unroll
            for (int s = 0; s < 12; s++) ldsm4t(wb[s], wsrc + (s >> 2) * 2048 + (s & 1) * 1024 + (s & 2) * 128);
            Warm warm;
            if (!complete()) {
#pragma unroll 1
                for (int it = 0; it < SPIN_MAX; it++) {
                    ask();
                    warm();
                    if (complete()) break;
                }
            }
            CK(8, va[0].x);
            if (va[0].x != 0x12345 && warp == 7) TSW(15);
            float acc[6][4] = {};
#pragma unroll
            for (int s = 0; s < 12; s++) {
                const uint4 v = va[s >> 2];
                mma16816(acc[s % 6], wb[s], (s & 2) ? v.z : v.x, (s & 2) ? v.w : v.y);
            }
            float y[4];
#pragma unroll
            for (int e = 0; e < 4; e++) y[e] = j < 2 ? (acc[0][e] + acc[2][e]) + acc[4][e] : (acc[1][e] + acc[3][e]) + acc[5][e];
            sts128f(ypart, y[0], y[1], y[2], y[3]);
            CK(9, 0);
            fin_arrive<6>();
            warm.done(sb + SM_SCRAP);
        }
    }
}

typedef CUresult (*EncodeFn)(CUtensorMap*, CUtensorMapDataType, cuuint32_t, void*, const cuuint64_t*, const cuuint64_t*,
                             const cuuint32_t*, const cuuint32_t*, CUtensorMapInterleave, CUtensorMapSwizzle,
                             CUtensorMapL2promotion, CUtensorMapFloatOOBfill);

CUtensorMap make_map(EncodeFn enc, void* ptr, uint64_t cols, uint64_t rows, uint32_t bcols, uint32_t brows,
                     CUtensorMapSwizzle sw, CUtensorMapL2promotion promo) {
    CUtensorMap m;
    const cuuint64_t dims[2] = {cols, rows};
    const cuuint64_t strides[1] = {cols * 2};
    const cuuint32_t box[2] = {bcols, brows};
    const cuuint32_t es[2] = {1, 1};
    enc(&m, CU_TENSOR_MAP_DATA_TYPE_BFLOAT16, 2, ptr, dims, strides, box, es, CU_TENSOR_MAP_INTERLEAVE_NONE, sw, promo,
        CU_TENSOR_MAP_FLOAT_OOB_FILL_NONE);
    return m;
}

}

extern "C" void kernel_launch(void* const* d_in, const int* in_sizes, int n_in, void* d_out, int out_size) {
    (void)in_sizes; (void)n_in; (void)out_size;
    static EncodeFn enc = nullptr;
    static int sms = 0;
    if (!enc) {
        cudaDriverEntryPointQueryResult qr;
        cudaGetDriverEntryPoint("cuTensorMapEncodeTiled", (void**)&enc, cudaEnableDefault, &qr);
        int dev = 0;
        cudaGetDevice(&dev);
        cudaDeviceGetAttribute(&sms, cudaDevAttrMultiProcessorCount, dev);
        cudaFuncSetAttribute(fused_decode_kernel, cudaFuncAttributeMaxDynamicSharedMemorySize, SM_TOTAL);
    }
    if (sms < NCTAS) return;
    const CUtensorMapL2promotion WPROMO = CU_TENSOR_MAP_L2_PROMOTION_L2_128B;
    Params p;
    p.k = make_map(enc, d_in[1], 64, (uint64_t)NBH * SK * 3, 64, TILE_ROWS, CU_TENSOR_MAP_SWIZZLE_128B, CU_TENSOR_MAP_L2_PROMOTION_NONE);
    p.v = make_map(enc, d_in[2], 64, (uint64_t)NBH * SK * 3, 64, TILE_ROWS, CU_TENSOR_MAP_SWIZZLE_128B, CU_TENSOR_MAP_L2_PROMOTION_NONE);
    p.wq = make_map(enc, d_in[3], NH * DH, DM, 48, 160, CU_TENSOR_MAP_SWIZZLE_NONE, WPROMO);
    p.wo = make_map(enc, d_in[4], DM, NH * DH, 32, DH, CU_TENSOR_MAP_SWIZZLE_64B, WPROMO);
    p.wg = make_map(enc, d_in[7], FF, DM, 32, 160, CU_TENSOR_MAP_SWIZZLE_64B, WPROMO);
    p.wu = make_map(enc, d_in[8], FF, DM, 32, 160, CU_TENSOR_MAP_SWIZZLE_64B, WPROMO);
    {
        const cuuint64_t dims[4] = {DM, 2, 8, FF / 16}, strides[3] = {8 * DM * 2, DM * 2, 16 * DM * 2};
        const cuuint32_t box[4] = {16, 2, 8, 12}, es[4] = {1, 1, 1, 1};
        enc(&p.wd, CU_TENSOR_MAP_DATA_TYPE_BFLOAT16, 4, d_in[9], dims, strides, box, es, CU_TENSOR_MAP_INTERLEAVE_NONE,
            CU_TENSOR_MAP_SWIZZLE_32B, WPROMO, CU_TENSOR_MAP_FLOAT_OOB_FILL_NONE);
    }
    p.x = (const __nv_bfloat16*)d_in[0];
    p.wr = (const __nv_bfloat16*)d_in[6];
    p.out = (__nv_bfloat16*)d_out;
    fused_decode_kernel<<<NCTAS, NTHREADS, SM_TOTAL, cudaStreamPerThread>>>(p);
}
```

```cpp
#include <cuda_runtime.h>
#include <cuda_bf16.h>
#include <cuda.h>
#include <stdint.h>

namespace {

constexpr int NB = 4, NH = 32, SK = 8192, DH = 192, DM = 640, FF = 1536;
constexpr int NBH = NB * NH;
constexpr int TILE = 64;
constexpr int UPB = SK / TILE;
constexpr int NUNITS = NBH * UPB;
constexpr int TILE_BYTES = TILE * DH * 2;
constexpr int TILE_ROWS = TILE * 3;
constexpr int NCTAS = 132;
constexpr int NQ_CTAS = 128;
constexpr int NE_CTAS = 112;
__host__ __device__ constexpr bool is_f(int cta) { return cta < NE_CTAS && cta % 14 < 11 && !(cta & 1); }
__host__ __device__ constexpr bool is_g(int cta) { return cta < NE_CTAS && cta % 14 < 11 && (cta & 1); }
__host__ __device__ constexpr int ffn_slice(int cta) { return cta / 14 * ((cta & 1) ? 5 : 6) + cta % 14 / 2; }

#define NWORK 2
#define LAG 2
#define NPOOL 768
#define RED0 116
#define RING 11
#define OREP 2
#define K0_AT_NS 1150
#define WO_AT_NS (K0_AT_NS + 2000)
#define K1_AT_NS (K0_AT_NS + 4400)
#define K1SWEEP_NS 2000
#define WO_STEP_NS 75
constexpr int KSWEEP_NS = 2000;
#define FW_TICKET (NPOOL + 32)
#define FW_AT_NS 2090
#define FW_GAP 280
#define FW_MID 2100
#define FW_GAP2 200
#define HGATE_NS 700
#define SLOT_TICKS 9
#define SLOT_OPEN 3
#define PH_O 0
#define PH_H 8
#define PH_M 2
#define NPROBE 24
static_assert(FW_TICKET < NPOOL + NWORK * NCTAS, "every worker draws one ticket beyond the pool");
constexpr int NAUX = 8;
constexpr int NTHREADS = (NAUX + NWORK + 2) * 32;
constexpr int SPIN_MAX = 1 << 22;

constexpr int SM_KV = 0;
constexpr int SM_A = SM_KV + NWORK * TILE_BYTES;
constexpr int SM_W = SM_A + 61440;
constexpr int SM_X = SM_W + 81920;
constexpr int XPITCH = 648;
constexpr int HPITCH = 1344;
constexpr int SM_RED = SM_X + 5 * HPITCH + 64;
constexpr int SM_RED2 = SM_RED + 8 * 48 * 4 * 4;
constexpr int SM_MISC = SM_RED2 + 4096;
constexpr int BAR_WQ = SM_MISC, SM_SCRAP = SM_MISC + 32, BAR_WO = SM_MISC + 40, SM_SIDE = SM_MISC + 48, BAR_H = SM_MISC + 56, BAR_FW = SM_MISC + 64;
constexpr int BAR_KV = BAR_FW + 64;
constexpr int SM_TOTAL = BAR_KV + NWORK * 8;
static_assert(SM_W % 1024 == 0 && NB * XPITCH * 2 <= 4 * HPITCH && SM_RED % 128 == 0, "smem layout");

struct Params {
    CUtensorMap k, v;
    CUtensorMap wq;
    CUtensorMap wo;
    CUtensorMap wg, wu;
    CUtensorMap wd;
    const __nv_bfloat16 *x, *wr;
    __nv_bfloat16* out;
};

struct Early {
    uint32_t q[4][4][8];
    uint32_t umax[UPB];
};
struct Twin { uint32_t w[4][1024]; };
constexpr int PROBE = 1024 - 32;
#define LSTRIDE 16
struct State {
    Twin ax[3];
    Twin hx;
    Twin ox[(OREP + 1) / 2];
    Twin lx;
    float4 oacc[NBH * 64];
    float2 attn[NB][DM];
    uint32_t fw_time[32];
    float2 lsum[NBH][LSTRIDE];
    uint32_t score[NPOOL][32];
};
__host__ __device__ constexpr int oidx(int row, int grp) {
    return (row >> 2) * 256 + ((row & 1) * 2 + (grp >> 5)) * 64 + (row & 2) * 16 + (grp & 31);
}
constexpr int STATE_V4 = ((sizeof(State) / 32 + NQ_CTAS - 1) / NQ_CTAS) * 2;
static_assert(sizeof(State) % 32 == 0, "State is cleared in whole sectors");
static_assert(sizeof(Early) == 64 * 16, "an Early entry is cleared by 64 threads");
struct Scratch {
    State st;
    unsigned work[64];
    unsigned cnt_z[32];
    Early early[NBH];
    alignas(4096) float4 ring[RING][UPB][64];
};
constexpr size_t PAGE = 2u << 20;
static_assert(sizeof(Scratch) <= PAGE, "scratch must fit one page");
__device__ __align__(128) unsigned char g_raw[2 * PAGE];
__device__ __forceinline__ Scratch* scratch() {
    return reinterpret_cast<Scratch*>((reinterpret_cast<uintptr_t>(g_raw) + PAGE - 1) & ~(uintptr_t)(PAGE - 1));
}
#define g_early scratch()->early
#define g_st scratch()->st
#define g_ring scratch()->ring
#define g_cnt_z scratch()->cnt_z
#define g_work scratch()->work
#define ALL_LOADERS 0
#define TS(i)
#define TSW(i)
#define TS2(i)
#define TSI(n, i)
#define PH(i)
#define CK(i, dep)
#define ARR()
#define PROG(u)

__device__ __forceinline__ uint32_t s2u(const void* p) { return (uint32_t)__cvta_generic_to_shared(p); }
__device__ __forceinline__ void mbar_init(uint32_t bar, int cnt) {
    asm volatile("mbarrier.init.shared::cta.b64 [%0], %1;" :: "r"(bar), "r"(cnt) : "memory");
}
__device__ __forceinline__ void mbar_wait(uint32_t bar, uint32_t parity) {
    asm volatile("{\n.reg .pred p;\n.reg .u32 n;\nmov.u32 n, 0;\nWAIT_LOOP:\n"
                 "mbarrier.try_wait.parity.shared::cta.b64 p, [%0], %1;\n"
                 "@p bra WAIT_DONE;\nadd.u32 n, n, 1;\nsetp.lt.u32 p, n, %2;\n@p bra WAIT_LOOP;\nWAIT_DONE:\n}"
                 :: "r"(bar), "r"(parity), "n"(SPIN_MAX) : "memory");
}
__device__ __forceinline__ void request_tile(uint32_t dst, const CUtensorMap* tm, int unit, uint32_t bar, uint64_t pol) {
    asm volatile("{\n.reg .pred p;\nelect.sync _|p, 0xffffffff;\n"
                 "@p mbarrier.arrive.expect_tx.shared::cta.b64 _, [%2], %6;\n"
                 "@p cp.async.bulk.tensor.2d.shared::cluster.global.mbarrier::complete_tx::bytes.L2::cache_hint "
                 "[%0], [%1, {%3, %4}], [%2], %5;\n}"
                 :: "r"(dst), "l"(tm), "r"(bar), "r"(0), "r"(unit * TILE_ROWS), "l"(pol), "n"(TILE_BYTES) : "memory");
}
__device__ __forceinline__ void put_groups(void* dst, int mode, const float (&o)[6], float tag, float tag2) {
    asm volatile("{\n.reg .pred s, t;\n.reg .b128 u, v;\n.reg .b64 a, b;\n"
                 "setp.eq.s32 s, %1, 0;\nsetp.ne.s32 t, %1, 2;\nxor.b64 a, %0, 4096;\n"
                 "@t bra.uni SINGLE;\n"
                 "red.relaxed.gpu.global.add.v4.f32 [a], {%2,%3,%4,%8};\n"
                 "red.relaxed.gpu.global.add.v4.f32 [a+128], {%5,%6,%7,%9};\n"
                 "SINGLE:\n"
                 "@s bra.uni STORE;\n"
                 "red.relaxed.gpu.global.add.v4.f32 [%0], {%2,%3,%4,%8};\n"
                 "red.relaxed.gpu.global.add.v4.f32 [%0+128], {%5,%6,%7,%9};\n"
                 "STORE:\n"
                 "mov.b64 a, {%2, %3};\nmov.b64 b, {%4, %8};\nmov.b128 u, {a, b};\n"
                 "mov.b64 a, {%5, %6};\nmov.b64 b, {%7, %9};\nmov.b128 v, {a, b};\n"
                 "@s st.relaxed.gpu.global.b128 [%0], u;\n@s st.relaxed.gpu.global.b128 [%0+128], v;\n}"
                 :: "l"(dst), "r"(mode), "f"(o[0]), "f"(o[1]), "f"(o[2]), "f"(o[3]), "f"(o[4]), "f"(o[5]), "f"(tag), "f"(tag2) : "memory");
}
__device__ __forceinline__ void request_box(uint32_t dst, const CUtensorMap* tm, int col, int row, uint32_t bar, uint32_t bytes) {
    asm volatile("{\n.reg .pred p, q;\nelect.sync _|p, 0xffffffff;\nsetp.ne.and.u32 q, %5, 0, p;\n"
                 "@q mbarrier.arrive.expect_tx.shared::cta.b64 _, [%2], %5;\n"
                 "@p cp.async.bulk.tensor.2d.shared::cluster.global.mbarrier::complete_tx::bytes [%0], [%1, {%3, %4}], [%2];\n}"
                 :: "r"(dst), "l"(tm), "r"(bar), "r"(col), "r"(row), "r"(bytes) : "memory");
}
__device__ __forceinline__ uint32_t lds32(uint32_t addr) {
    uint32_t v;
    asm volatile("ld.shared.u32 %0, [%1];" : "=r"(v) : "r"(addr) : "memory");
    return v;
}
__device__ __forceinline__ void ldsm4(uint32_t (&r)[4], uint32_t addr) {
    asm volatile("ldmatrix.sync.aligned.m8n8.x4.shared.b16 {%0,%1,%2,%3}, [%4];"
                 : "=r"(r[0]), "=r"(r[1]), "=r"(r[2]), "=r"(r[3]) : "r"(addr) : "memory");
}
__device__ __forceinline__ void ldsm4t(uint32_t (&r)[4], uint32_t addr) {
    asm volatile("ldmatrix.sync.aligned.m8n8.x4.trans.shared.b16 {%0,%1,%2,%3}, [%4];"
                 : "=r"(r[0]), "=r"(r[1]), "=r"(r[2]), "=r"(r[3]) : "r"(addr) : "memory");
}
__device__ __forceinline__ void mma16816(float (&c)[4], const uint32_t (&a)[4], uint32_t b0, uint32_t b1) {
    asm volatile("mma.sync.aligned.m16n8k16.row.col.f32.bf16.bf16.f32 {%0,%1,%2,%3}, {%4,%5,%6,%7}, {%8,%9}, {%0,%1,%2,%3};"
                 : "+f"(c[0]), "+f"(c[1]), "+f"(c[2]), "+f"(c[3])
                 : "r"(a[0]), "r"(a[1]), "r"(a[2]), "r"(a[3]), "r"(b0), "r"(b1));
}
struct Warm {
    float c[4] = {};
    __device__ __forceinline__ void operator()() {
        asm volatile("mma.sync.aligned.m16n8k8.row.col.f32.bf16.bf16.f32 {%0,%1,%2,%3}, {%4,%4}, {%4}, {%0,%1,%2,%3};"
                     : "+f"(c[0]), "+f"(c[1]), "+f"(c[2]), "+f"(c[3]) : "r"(0));
    }
    __device__ __forceinline__ void done(uint32_t scrap) {
        asm volatile("{\n.reg .pred p;\nsetp.gt.f32 p, %1, 0f3f800000;\n@p st.shared.f32 [%0], %1;\n}" :: "r"(scrap), "f"(c[0]) : "memory");
    }
};
__device__ __forceinline__ uint4 ld_relaxed_v4(const void* p) {
    uint4 v;
    asm volatile("ld.relaxed.gpu.global.v4.u32 {%0,%1,%2,%3}, [%4];" : "=r"(v.x), "=r"(v.y), "=r"(v.z), "=r"(v.w) : "l"(p) : "memory");
    return v;
}
__device__ __forceinline__ float4 ld_relaxed_f4(const void* p) {
    float4 v;
    asm volatile("ld.relaxed.gpu.global.v4.f32 {%0,%1,%2,%3}, [%4];" : "=f"(v.x), "=f"(v.y), "=f"(v.z), "=f"(v.w) : "l"(p) : "memory");
    return v;
}
__device__ __forceinline__ float2 ld_relaxed_f2(const void* p) {
    float2 v;
    asm volatile("ld.relaxed.gpu.global.v2.f32 {%0,%1}, [%2];" : "=f"(v.x), "=f"(v.y) : "l"(p) : "memory");
    return v;
}
__device__ __forceinline__ float4 ld_relaxed_b128(const void* p) {
    float4 v;
    asm volatile("{\n.reg .b128 t;\n.reg .b64 a, b;\nld.relaxed.gpu.global.b128 t, [%4];\nmov.b128 {a, b}, t;\n"
                 "mov.b64 {%0, %1}, a;\nmov.b64 {%2, %3}, b;\n}" : "=f"(v.x), "=f"(v.y), "=f"(v.z), "=f"(v.w) : "l"(p) : "memory");
    return v;
}
__device__ __forceinline__ void st_relaxed_b128(void* p, float x, float y, float z, float w) {
    asm volatile("{\n.reg .b128 t;\n.reg .b64 a, b;\nmov.b64 a, {%1, %2};\nmov.b64 b, {%3, %4};\nmov.b128 t, {a, b};\n"
                 "st.relaxed.gpu.global.b128 [%0], t;\n}" :: "l"(p), "f"(x), "f"(y), "f"(z), "f"(w) : "memory");
}
__device__ __forceinline__ unsigned ld_acquire(const unsigned* p) {
    unsigned v;
    asm volatile("ld.acquire.gpu.global.u32 %0, [%1];" : "=r"(v) : "l"(p) : "memory");
    return v;
}
__device__ __forceinline__ void st_relaxed(void* p, uint32_t v) {
    asm volatile("st.relaxed.gpu.global.u32 [%0], %1;" :: "l"(p), "r"(v) : "memory");
}
__device__ __forceinline__ void red_f2(float* p, float a, float b) {
    asm volatile("red.relaxed.gpu.global.add.v2.f32 [%0], {%1,%2};" :: "l"(p), "f"(a), "f"(b) : "memory");
}
__device__ __forceinline__ void draw(int& ticket, unsigned* ctr, bool pred) {
    asm volatile("{\n.reg .pred p;\nsetp.ne.u32 p, %2, 0;\n@p atom.relaxed.gpu.global.inc.u32 %0, [%1], 0x7fffffff;\n}"
                 : "+r"(ticket) : "l"(ctr), "r"((uint32_t)pred) : "memory");
}
__device__ __forceinline__ void red_release(unsigned* p) {
    asm volatile("red.release.gpu.global.add.u32 [%0], 1;" :: "l"(p) : "memory");
}
__device__ __forceinline__ uint32_t ld_relaxed_u32(const void* p) {
    uint32_t v;
    asm volatile("ld.relaxed.gpu.global.u32 %0, [%1];" : "=r"(v) : "l"(p) : "memory");
    return v;
}
__device__ __forceinline__ float rcp_approx(float v) {
    float r;
    asm("rcp.approx.ftz.f32 %0, %1;" : "=f"(r) : "f"(v));
    return r;
}
__device__ __forceinline__ float ex2_approx(float v) {
    float e;
    asm("ex2.approx.ftz.f32 %0, %1;" : "=f"(e) : "f"(v));
    return e;
}
__device__ __forceinline__ float sigmoid_approx(float v) { return rcp_approx(1.0f + ex2_approx(v * -1.4426950408889634f)); }
__device__ __forceinline__ float sqrt_approx(float v) {
    float r;
    asm("sqrt.approx.ftz.f32 %0, %1;" : "=f"(r) : "f"(v));
    return r;
}
__device__ __forceinline__ bool all(bool v) { return __all_sync(0xffffffffu, v); }
__device__ __forceinline__ void wait_count(const unsigned* p, unsigned target) {
#pragma unroll 1
    for (int it = 0; it < SPIN_MAX; it++) {
        if (all(ld_acquire(p) >= target)) break;
        __nanosleep(400);
    }
}
__device__ __forceinline__ float wait_sum(const void* p, float n, int nap = 0) {
    float2 v;
#pragma unroll 1
    for (int it = 0; it < SPIN_MAX; it++) {
        v = ld_relaxed_f2(p);
        if (all(v.y >= n)) break;
        if (all(v.y == 0.f)) __nanosleep(600);
        else if (nap) __nanosleep(nap);
    }
    return v.x;
}
__device__ __forceinline__ void wait_row(int bh, float n) { wait_sum(g_st.lsum[bh], n); }
__device__ __forceinline__ void wait_row_o(int bh, float n) {
    wait_row(bh, n);
    if (bh >= RED0) return;
#pragma unroll 1
    for (int it = 0; it < SPIN_MAX; it++) {
        if (all(__uint_as_float(ld_relaxed_u32(&g_st.oacc[oidx(bh, 0)].w)) == UPB)) break;
        __nanosleep(300);
    }
}
constexpr uint32_t SLOT_K = (uint32_t)(((1ull << 32) + SLOT_TICKS - 1) / SLOT_TICKS);
#define SLOT_ASM(t, n, p, phase, k, open) \
    "mov.u32 " n ", 0;\nSLOT:\nmov.u32 " t ", %%globaltimer_lo;\nadd.u32 " n ", " n ", 1;\nsetp.lt.u32 " p ", " n ", 24;\nshr.u32 " t ", " t ", 5;\n" \
    "mad.lo.u32 " t ", " t ", " k ", " phase ";\nsetp.ge.and.u32 " p ", " t ", " open ", " p ";\n@" p " bra.uni SLOT;\n"
template <int PHASE> __host__ __device__ constexpr uint32_t slot_phase() { return SLOT_K / 2 - PHASE * SLOT_K; }
template <int PHASE> __device__ __forceinline__ void wait_slot() {
    if (PHASE < 0) return;
    asm volatile("{\n.reg .pred p;\n.reg .b32 t, n;\n" SLOT_ASM("t", "n", "p", "%0", "%1", "%2") "}"
                 :: "n"(slot_phase<PHASE>()), "n"(SLOT_K), "n"(SLOT_OPEN * SLOT_K) : "memory");
}
__device__ __forceinline__ void wait_time(uint32_t t) {
#pragma unroll 1
    for (int it = 0; it < SPIN_MAX; it++) {
        uint32_t now;
        asm volatile("mov.u32 %0, %%globaltimer_lo;" : "=r"(now));
        if (all((int)(now - t) >= 0)) break;
    }
}
__device__ __forceinline__ void wait_clock(uint32_t t, Warm& warm) { while (!all((int)(clock() - t) >= 0)) { warm(); } }
__device__ __forceinline__ uint32_t pack_bf16(float lo, float hi) {
    uint32_t r;
    asm("cvt.rn.bf16x2.f32 %0, %1, %2;" : "=r"(r) : "f"(hi), "f"(lo));
    return r;
}
__device__ __forceinline__ float bf16r(float v) { return __uint_as_float(pack_bf16(0.f, v)); }
__device__ __forceinline__ uint32_t nonzero(uint32_t w) { return w ? w : 0x80008000u; }
__device__ __forceinline__ uint32_t pack_neg(float lo, float hi) { return nonzero(pack_bf16(-lo, -hi)); }
__device__ __forceinline__ float lo_f(uint32_t v) { return __uint_as_float(v << 16); }
__device__ __forceinline__ float hi_f(uint32_t v) { return __uint_as_float(v & 0xffff0000u); }
__device__ __forceinline__ float warp_sum(float v) {
#pragma unroll
    for (int o = 16; o; o >>= 1) v += __shfl_xor_sync(0xffffffffu, v, o);
    return v;
}
__device__ __forceinline__ void layernorm20(float (&v)[20]) {
    float s = 0.f;
#pragma unroll
    for (int i = 0; i < 20; i++) s += v[i];
    const float mean = warp_sum(s) * (1.0f / DM);
    float q = 0.f;
#pragma unroll
    for (int i = 0; i < 20; i++) { const float d = v[i] - mean; q += d * d; }
    const float var = bf16r(warp_sum(q) * (1.0f / DM));
    const float m = bf16r(mean);
    const float rden = 1.0f / bf16r(sqrtf(bf16r(var + 1e-5f)));
#pragma unroll
    for (int i = 0; i < 20; i++) v[i] = bf16r(bf16r(v[i] - m) * rden);
}

__device__ __forceinline__ void moments(float m1, float m2, float& nmean, float& rden) {
    m1 *= 1.0f / DM;
    const float var = bf16r(fmaxf(fmaf(-m1, m1, m2 * (1.0f / DM)), 0.f));
    nmean = bf16r(m1);
    rden = rcp_approx(bf16r(sqrt_approx(bf16r(var + 1e-5f))));
}
__device__ __forceinline__ float sel4(int j, float a, float b, float c, float d) {
    float lo, hi, r;
    asm("{\n.reg .pred p;\nsetp.ne.s32 p, %3, 0;\nselp.f32 %0, %2, %1, p;\n}" : "=f"(lo) : "f"(a), "f"(b), "r"(j & 1));
    asm("{\n.reg .pred p;\nsetp.ne.s32 p, %3, 0;\nselp.f32 %0, %2, %1, p;\n}" : "=f"(hi) : "f"(c), "f"(d), "r"(j & 1));
    asm("{\n.reg .pred p;\nsetp.ne.s32 p, %3, 0;\nselp.f32 %0, %2, %1, p;\n}" : "=f"(r) : "f"(lo), "f"(hi), "r"(j & 2));
    return r;
}
template <typename T> __device__ __forceinline__ void pin(T*& p) { asm volatile("" : "+l"(p)); }
__device__ __forceinline__ void pin(uint32_t& v) { asm volatile("" : "+r"(v)); }
__device__ __forceinline__ void pin(float& v) { asm volatile("" : "+f"(v)); }
__device__ __forceinline__ uint32_t after(uint32_t n, float v) {
    asm volatile("{\n.reg .pred p;\nsetp.eq.u32 p, %1, 0x7fc1a5a5;\n@p add.u32 %0, %0, 32;\n}" : "+r"(n) : "r"(__float_as_uint(v)));
    return n;
}
__device__ __forceinline__ float2 lds64f(uint32_t addr) {
    float2 v;
    asm volatile("ld.shared.v2.f32 {%0,%1}, [%2];" : "=f"(v.x), "=f"(v.y) : "r"(addr) : "memory");
    return v;
}
__device__ __forceinline__ void sts32f(uint32_t addr, float v) { asm volatile("st.shared.f32 [%0], %1;" :: "r"(addr), "f"(v) : "memory"); }
template <int ID> __device__ __forceinline__ void fin_arrive() { asm volatile("bar.arrive %0, 288;" :: "n"(ID) : "memory"); }
template <int ID> __device__ __forceinline__ void fin_sync() { asm volatile("bar.sync %0, 288;" :: "n"(ID) : "memory"); }
template <int ID> __device__ __forceinline__ void fin_sync(uint32_t n) { asm volatile("bar.sync %0, %1;" :: "n"(ID), "r"(n) : "memory"); }
__device__ __forceinline__ float2 sum8(uint32_t addr, int pitch) {
    float2 t[8];
#pragma unroll
    for (int w = 0; w < 8; w++) t[w] = lds64f(addr + w * pitch);
    return make_float2(((t[0].x + t[1].x) + (t[2].x + t[3].x)) + ((t[4].x + t[5].x) + (t[6].x + t[7].x)),
                       ((t[0].y + t[1].y) + (t[2].y + t[3].y)) + ((t[4].y + t[5].y) + (t[6].y + t[7].y)));
}
__device__ __forceinline__ float4 sum4x4(uint32_t addr, int pitch) {
    float4 t[4];
#pragma unroll
    for (int w = 0; w < 4; w++)
        asm volatile("ld.shared.v4.f32 {%0,%1,%2,%3}, [%4];" : "=f"(t[w].x), "=f"(t[w].y), "=f"(t[w].z), "=f"(t[w].w) : "r"(addr + w * pitch) : "memory");
    return make_float4((t[0].x + t[1].x) + (t[2].x + t[3].x), (t[0].y + t[1].y) + (t[2].y + t[3].y),
                       (t[0].z + t[1].z) + (t[2].z + t[3].z), (t[0].w + t[1].w) + (t[2].w + t[3].w));
}
__device__ __forceinline__ void sts64f(uint32_t addr, float x, float y) {
    asm volatile("st.shared.v2.f32 [%0], {%1,%2};" :: "r"(addr), "f"(x), "f"(y) : "memory");
}
__device__ __forceinline__ uint4 lds128(uint32_t addr) {
    uint4 v;
    asm volatile("ld.shared.v4.u32 {%0,%1,%2,%3}, [%4];" : "=r"(v.x), "=r"(v.y), "=r"(v.z), "=r"(v.w) : "r"(addr) : "memory");
    return v;
}
__device__ __forceinline__ void ld_relaxed_v4_if(uint4& v, const void* p, bool pred) {
    asm volatile("{\n.reg .pred p;\nsetp.ne.u32 p, %5, 0;\n@p ld.relaxed.gpu.global.v4.u32 {%0,%1,%2,%3}, [%4];\n}"
                 : "+r"(v.x), "+r"(v.y), "+r"(v.z), "+r"(v.w) : "l"(p), "r"((uint32_t)pred) : "memory");
}
__device__ __forceinline__ void sts128f(uint32_t addr, float x, float y, float z, float w) {
    asm volatile("st.shared.v4.f32 [%0], {%1,%2,%3,%4};" :: "r"(addr), "f"(x), "f"(y), "f"(z), "f"(w) : "memory");
}
template <int NJ>
__device__ __forceinline__ void load_o(uint32_t (&ob)[3 * NJ][2], int bh, int J0, int j) {
    float4 v[NJ][4];
    float2 l;
#pragma unroll 1
    for (int it = 0; it < SPIN_MAX; it++) {
#pragma unroll
        for (int J = 0; J < NJ; J++) {
#pragma unroll
            for (int e = 0; e < 4; e++) v[J][e] = ld_relaxed_f4(&g_st.oacc[oidx(bh, j)] + oidx(0, (J0 + J) * 16 + e * 4));
        }
        l = ld_relaxed_f2(g_st.lsum[bh]);
        bool ok = l.y == UPB;
#pragma unroll
        for (int J = 0; J < NJ; J++) {
#pragma unroll
            for (int e = 0; e < 4; e++) ok &= v[J][e].w == UPB;
        }
        if (all(ok)) break;
    }
    const float rl = __fdividef(1.0f, l.x);
#pragma unroll
    for (int J = 0; J < NJ; J++) {
        ob[3 * J][0] = pack_bf16(v[J][0].x * rl, v[J][1].x * rl);     ob[3 * J][1] = pack_bf16(v[J][2].x * rl, v[J][3].x * rl);
        ob[3 * J + 1][0] = pack_bf16(v[J][0].y * rl, v[J][1].y * rl); ob[3 * J + 1][1] = pack_bf16(v[J][2].y * rl, v[J][3].y * rl);
        ob[3 * J + 2][0] = pack_bf16(v[J][0].z * rl, v[J][1].z * rl); ob[3 * J + 2][1] = pack_bf16(v[J][2].z * rl, v[J][3].z * rl);
    }
}
__device__ __forceinline__ int near_side(uint32_t sb) {
    uint32_t v;
    asm volatile("ld.volatile.shared.u32 %0, [%1];" : "=r"(v) : "r"(sb + SM_SIDE) : "memory");
    return v;
}
__device__ __forceinline__ void poll_row(uint4& a, uint4& b, uint2& c, const void* pa, const void* pb, const void* pc, uint32_t sa, uint32_t sc,
                                         bool arrive, bool nap, uint32_t bar, Warm& warm) {
    asm volatile("{\n.reg .pred p, q, r, s;\n.reg .b32 m, n, it;\n"
                 "setp.ne.u32 r, %19, 0;\nsetp.ne.u32 s, %20, 0;\nmov.u32 it, 0;\n"
                 "POLL:\n"
                 SLOT_ASM("m", "n", "p", "%23", "%24", "%25")
                 "ld.relaxed.gpu.global.v4.u32 {%0,%1,%2,%3}, [%14];\n"
                 "ld.relaxed.gpu.global.v4.u32 {%4,%5,%6,%7}, [%15];\n"
                 "ld.relaxed.gpu.global.v2.u32 {%8,%9}, [%16];\n"
                 "add.u32 it, it, 1;\nsetp.ge.u32 q, it, %21;\n"
                 "mov.u32 m, 0;\nmma.sync.aligned.m16n8k8.row.col.f32.bf16.bf16.f32 {%10,%11,%12,%13}, {m,m}, {m}, {%10,%11,%12,%13};\n"
                 "st.shared.v4.u32 [%17], {%0,%1,%2,%3};\n"
                 "st.shared.v4.u32 [%17+512], {%4,%5,%6,%7};\n"
                 "st.shared.v2.u32 [%18], {%8,%9};\n"
                 "min.u32 m, %0, %1;\nmin.u32 m, m, %2;\nmin.u32 n, %3, %4;\nmin.u32 n, n, %5;\nmin.u32 m, m, %6;\nmin.u32 m, m, %7;\n"
                 "min.u32 n, n, m;\nmin.u32 m, %8, %9;\nmin.u32 m, m, n;\n"
                 "setp.ne.or.u32 p, m, 0, q;\n"
                 "vote.sync.all.pred p, p, 0xffffffff;\n"
                 "and.pred q, p, r;\n"
                 "bar.warp.sync 0xffffffff;\n"
                 "@q mbarrier.arrive.shared::cta.b64 _, [%22];\n"
                 "@p bra.uni DONE;\n"
                 "@s nanosleep.u32 500;\n"
                 "bra.uni POLL;\n"
                 "DONE:\n}"
                 : "=&r"(a.x), "=&r"(a.y), "=&r"(a.z), "=&r"(a.w), "=&r"(b.x), "=&r"(b.y), "=&r"(b.z), "=&r"(b.w), "=&r"(c.x), "=&r"(c.y),
                   "+f"(warm.c[0]), "+f"(warm.c[1]), "+f"(warm.c[2]), "+f"(warm.c[3])
                 : "l"(pa), "l"(pb), "l"(pc), "r"(sa), "r"(sc), "r"((uint32_t)arrive), "r"((uint32_t)nap), "n"(SPIN_MAX), "r"(bar),
                   "n"(slot_phase<PH_H>()), "n"(SLOT_K), "n"(SLOT_OPEN * SLOT_K) : "memory");
}
__device__ __forceinline__ void aux_sync() { asm volatile("bar.sync 1, 256;" ::: "memory"); }

__global__ void __launch_bounds__(NTHREADS, 1)
fused_decode_kernel(const __grid_constant__ Params p) {
    extern __shared__ __align__(1024) unsigned char smem[];
    const uint32_t sb = s2u(smem);
    const int tid = threadIdx.x, cta = blockIdx.x;
    if (tid < 32 && cta < NQ_CTAS) {
        asm volatile("{\n.reg .pred p;\nelect.sync _|p, 0xffffffff;\n"
                     "@p mbarrier.init.shared::cta.b64 [%2], 1;\n"
                     "@p fence.mbarrier_init.release.cluster;\n"
                     "@p mbarrier.arrive.expect_tx.shared::cta.b64 _, [%2], 15360;\n"
                     "@p cp.async.bulk.tensor.2d.shared::cluster.global.mbarrier::complete_tx::bytes [%0], [%1, {%3, %4}], [%2];\n"
                     "@p mbarrier.init.shared::cta.b64 [%2+8], 1;\n@p mbarrier.init.shared::cta.b64 [%2+16], 1;\n"
                     "@p mbarrier.init.shared::cta.b64 [%2+24], 1;\n"
                     "@p fence.mbarrier_init.release.cluster;\n"
                     "@p mbarrier.arrive.expect_tx.shared::cta.b64 _, [%2+8], 15360;\n"
                     "@p cp.async.bulk.tensor.2d.shared::cluster.global.mbarrier::complete_tx::bytes [%0+15360], [%1, {%3, %5}], [%2+8];\n"
                     "@p mbarrier.arrive.expect_tx.shared::cta.b64 _, [%2+16], 15360;\n"
                     "@p cp.async.bulk.tensor.2d.shared::cluster.global.mbarrier::complete_tx::bytes [%0+30720], [%1, {%3, %6}], [%2+16];\n"
                     "@p mbarrier.arrive.expect_tx.shared::cta.b64 _, [%2+24], 15360;\n"
                     "@p cp.async.bulk.tensor.2d.shared::cluster.global.mbarrier::complete_tx::bytes [%0+46080], [%1, {%3, %7}], [%2+24];\n}"
                     :: "r"(sb + SM_W), "l"(&p.wq), "r"(sb + BAR_WQ), "r"(cta * 48), "r"(0), "r"(160), "r"(320), "r"(480) : "memory");
    }
    const int warp = __shfl_sync(0xffffffffu, tid >> 5, 0), lane = tid & 31;
    constexpr int grid = NCTAS;
    const int g = lane >> 2, j = lane & 3;
    uint32_t t_start;
    asm volatile("mov.u32 %0, %%globaltimer_lo;" : "=r"(t_start));
    TS(0);
    if (tid == 32) {
        mbar_init(sb + BAR_WO, 1);
        mbar_init(sb + BAR_H, 1);
#pragma unroll
        for (int i = 0; i < 8 + NWORK; i++) mbar_init(sb + BAR_FW + i * 8, 1);
        sts32f(sb + SM_SIDE, 0.f);
        asm volatile("fence.mbarrier_init.release.cluster;" ::: "memory");
        asm volatile("fence.proxy.async.shared::cta;" ::: "memory");
    }
    __syncthreads();
    if (warp >= NAUX + NWORK) {
        const int fw = warp - (NAUX + NWORK), fi = ffn_slice(cta);
        if (fw == 0) {
            if (cta < NQ_CTAS) {
#pragma unroll
                for (int i = lane; i < STATE_V4; i += 32)
                    if (cta * STATE_V4 + i < (int)(sizeof(State) / 16)) reinterpret_cast<uint4*>(&g_st)[cta * STATE_V4 + i] = make_uint4(0u, 0u, 0u, 0u);
                __syncwarp();
                if (lane == 0) red_release(g_cnt_z);
            }
            TSW(2); wait_count(g_cnt_z, NQ_CTAS); TSW(29);
            asm volatile("bar.arrive 2, %0;" :: "n"((NWORK + 2) * 32) : "memory");
            fin_arrive<3>();
        } else {
#pragma unroll 1
            for (int n = cta < NE_CTAS ? 5 : 4, i = n - 1; i >= 0; i--) {
                const int head = cta < NE_CTAS ? cta >> 2 : 28 + i;
                wait_time(t_start + WO_AT_NS + (NH - 1 - head) * WO_STEP_NS);
                request_box(sb + SM_A + i * 12288, &p.wo, cta < NE_CTAS ? (cta & 3) * 160 + i * 32 : (cta - NE_CTAS) * 32,
                            head * DH, sb + BAR_WO, i == n - 1 ? n * 12288 : 0);
            }
            asm volatile("bar.sync 2, %0;" :: "n"((NWORK + 2) * 32) : "memory");
            uint32_t best[2] = {~0u, ~0u};
#pragma unroll 1
            for (int i = 0; i < NPROBE; i++) {
#pragma unroll
                for (int c = 0; c < 2; c++) {
                    uint32_t t0 = clock(), t1 = t0;
                    int v = 0;
                    draw(v, &g_st.hx.w[c][PROBE], lane == 0);
                    asm volatile("{\n.reg .pred p;\nsetp.ne.u32 p, %1, 0xffffffff;\n@p mov.u32 %0, %%clock;\n}" : "+r"(t1) : "r"(v) : "memory");
                    best[c] = min(best[c], t1 - t0);
                }
                __nanosleep(1000);
            }
            if (lane == 0) sts32f(sb + SM_SIDE, __uint_as_float(best[1] < best[0]));
        }
        int job = cta;
        auto sum_rows = [&](int row_end) {
#pragma unroll 1
            for (; job < 8 * min(row_end, RED0); job += NCTAS) {
                const int row = job >> 3, grp = (job & 7) * 8 + (lane & 7);
                wait_row(row, UPB);
                const float4* src = &g_ring[row % RING][lane >> 3][grp];
                float sx = 0.f, sy = 0.f, sz = 0.f;
#pragma unroll 1
                for (int i = 0; i < 2; i++, src += 64 * 64) {
                    float4 v[16];
#pragma unroll 1
                    for (int it = 0; it < SPIN_MAX; it++) {
                        bool ok = true;
#pragma unroll
                        for (int k = 0; k < 16; k++) v[k] = ld_relaxed_b128(src + k * 4 * 64);
#pragma unroll
                        for (int k = 0; k < 16; k++) ok &= v[k].w == (float)(row + 1);
                        if (all(ok)) break;
                    }
#pragma unroll
                    for (int k = 0; k < 16; k++) { sx += v[k].x; sy += v[k].y; sz += v[k].z; }
                }
#pragma unroll
                for (int o = 8; o < 32; o <<= 1) {
                    sx += __shfl_xor_sync(0xffffffffu, sx, o); sy += __shfl_xor_sync(0xffffffffu, sy, o); sz += __shfl_xor_sync(0xffffffffu, sz, o);
                }
                if (lane < 8) st_relaxed_b128(&g_st.oacc[oidx(row, grp)], sx, sy, sz, UPB);
            }
        };
        const int ho0 = lane / 20 * 256 + lane % 20 * 4, ho1 = (lane + 32) / 20 * 256 + (lane + 32) % 20 * 4, ho2 = 3 * 256 + 16 + 2 * lane;
        uint32_t wr[10] = {};
        float wsum = 0.f;
        if (is_g(cta) && fw == 0) {
#pragma unroll
            for (int i = 0; i < 10; i++) {
                const int w = 4 * lane + 128 * (i >> 2) + (i & 3) - (i >= 8 ? 2 * lane : 0);
                wr[i] = *reinterpret_cast<const uint32_t*>(p.wr + (w >> 4) * 32 + (w & 3) * 8 + ((w >> 1) & 6));
                wsum += lo_f(wr[i]) + hi_f(wr[i]);
            }
            wsum = warp_sum(wsum);
        }
        const int fb = lane >> 3, fg = lane & 7;
        if (fw == 0) {
#pragma unroll
            for (int i = lane; i < DM / 2; i += 32) sts32f(sb + SM_X + 4 * HPITCH + i * 4, __uint_as_float(0x3f803f80u));
        }
        Warm warm;
        float nmean = 0.f, rden = 0.f, sig = 0.f;
#pragma unroll 1
        for (int b = 0; b < NB; b++) {
            const bool ffn = b >= NB - 2;
            if (fw == 0) {
                sum_rows((b + 1) * NH);
                if (ffn) asm volatile("bar.arrive 8, 64;" ::: "memory");
            } else if (ffn) {
                asm volatile("bar.sync 8, 64;" ::: "memory");
                if (b == NB - 1 && (is_f(cta) || is_g(cta) || ALL_LOADERS)) {
                    uint32_t t0 = 0;
#pragma unroll 1
                    for (int it = 0; it < SPIN_MAX; it++) {
                        t0 = ld_relaxed_u32(g_st.fw_time);
                        if (all(t0 != 0)) break;
                        __nanosleep(150);
                    }
                    asm volatile("fence.proxy.async.shared::cta;" ::: "memory");
                    wait_time(t0 + FW_AT_NS);
                    TSW(9);
                    uint32_t t = clock() + (is_f(cta) ? ((fi & 1) * 24 + (fi >> 1)) * FW_GAP / 48 : FW_MID + ((fi & 3) * 10 + (fi >> 2)) * FW_GAP2 / 40);
#pragma unroll 1
                    for (int i = 0; i < 8; i++) {
                        const uint32_t bar = sb + BAR_FW + i * 8;
                        if (is_f(cta)) {
                            wait_clock(t, warm);
                            request_box(sb + SM_W + i * 10240, (i & 1) ? &p.wu : &p.wg, fi * 32, (i >> 1) * 160, bar, 10240);
                            t += FW_GAP;
                        } else if (is_g(cta)) {
                            wait_clock(t, warm);
                            asm volatile("{\n.reg .pred p;\nelect.sync _|p, 0xffffffff;\n"
                                         "@p mbarrier.arrive.expect_tx.shared::cta.b64 _, [%2], 6144;\n"
                                         "@p cp.async.bulk.tensor.4d.shared::cluster.global.mbarrier::complete_tx::bytes [%0], [%1, {%3, %4, %4, %5}], [%2];\n}"
                                         :: "r"(sb + SM_W + i * 6144), "l"(&p.wd), "r"(bar), "r"(fi * 16), "r"(0), "r"(i * 12) : "memory");
                            t += FW_GAP2;
                        }
                    }
                }
                if (is_f(cta)) {
                    const uint32_t* src = &g_st.hx.w[near_side(sb)][min(fb, b) * 256 + 96];
                    float4 m;
#pragma unroll 1
                    for (int it = 0; it < SPIN_MAX; it++) {
                        wait_slot<PH_M>();
                        m = ld_relaxed_f4(src);
                        warm();
                        if (all(m.y + m.w == 2 * (NCTAS - NE_CTAS))) break;
                        if (b < NB - 1) __nanosleep(500);
                    }
                    moments(m.x, m.z, m.x, m.z);
                    sts64f(sb + SM_RED + 5120 + fb * 8, m.x, m.z);
                }
            }
            if (fw == 0 && cta >= NE_CTAS) {
                const int lc = cta - NE_CTAS, col = lc * 32 + 2 * (lane & 15);
                const uint32_t xv = *reinterpret_cast<const uint32_t*>(p.x + b * DM + col);
                uint32_t* dst = &(ffn ? g_st.hx.w : g_st.lx.w + 2)[lane >> 4][(b & 1) * 128 + lc / 5 * 256 + lc % 5 * 16 + (col & 6) * 2 + ((col >> 3) & 3)];
                uint32_t part = sb + SM_RED + (lane & 15) * 8;
                wait_row(b * NH + 28, 1);
                float4 early;
#pragma unroll 1
                for (int it = 0; it < SPIN_MAX; it++) {
                    early = ld_relaxed_f4(&g_st.attn[b][col]);
                    if (all(early.y == NE_CTAS / 4 && early.w == NE_CTAS / 4)) break;
                }
                if (early.x != 1.2345f && lane == 0) TS2(6);
                CK(1, __float_as_uint(early.x));
                const float x0 = -(lo_f(xv) + early.x), x1 = -(hi_f(xv) + early.z);
                fin_sync<4>(after(after(288, x0), x1));
                CK(2, lds32(sb + SM_RED));
                const float2 late = sum8(part, 128);
                const uint32_t hv = nonzero(pack_bf16(x0 - late.x, x1 - late.y));
                st_relaxed(dst, hv);
                if (ffn) st_relaxed(dst + 2048, hv);
                CK(3, 0);
                float m = lane < 16 ? lo_f(hv) + hi_f(hv) : fmaf(lo_f(hv), lo_f(hv), hi_f(hv) * hi_f(hv));
#pragma unroll
                for (int o = 1; o < 16; o <<= 1) m += __shfl_xor_sync(0xffffffffu, m, o);
                if ((lane & 14) == 0) red_f2(reinterpret_cast<float*>(&g_st.hx.w[lane & 1][b * 256 + 96 + (lane >> 4) * 2]), m, 1.f);
                fin_arrive<5>();
            }
            if (fw == 0 && (is_g(cta) || is_f(cta))) {
                const uint32_t* src = &(ffn ? g_st.hx.w : g_st.lx.w + 2)[near_side(sb) ^ (ffn && is_g(cta) ? 3 : 0)][(b & 1) * 128];
                const uint32_t hrow = sb + SM_X + b * HPITCH;
                wait_sum(b == NB - 1 ? (const void*)&g_st.lx.w[near_side(sb) ^ 1][3 * 256] : g_st.lsum[b * NH + NH - 1], UPB, 100);
                wait_clock(clock() + HGATE_NS * 2, warm);
                uint4 h0, h1;
                uint2 h2;
                poll_row(h0, h1, h2, src + ho0, src + ho1, src + ho2, hrow + lane * 16, hrow + 1024 + lane * 8, ffn && lane == 0, b < NB - 1, sb + BAR_H, warm);
                CK(4, h0.x);
                if (is_g(cta)) {
                    const uint32_t hw[10] = {h0.x, h0.y, h0.z, h0.w, h1.x, h1.y, h1.z, h1.w, h2.x, h2.y};
                    float m1 = 0.f, m2 = 0.f, rr = 0.f;
#pragma unroll
                    for (int i = 0; i < 10; i++) {
                        const float v0 = lo_f(hw[i]), v1 = hi_f(hw[i]);
                        m1 += v0 + v1;
                        m2 = fmaf(v0, v0, fmaf(v1, v1, m2));
                        rr = fmaf(v0, lo_f(wr[i]), fmaf(v1, hi_f(wr[i]), rr));
                    }
                    moments(warp_sum(m1), warp_sum(m2), m1, m2);
                    const float sg = bf16r(sigmoid_approx(bf16r((m1 * wsum - warp_sum(rr)) * m2)));
                    if (fb == b) { nmean = m1; rden = m2; sig = sg; }
                    __syncwarp();
                    if (ffn) {
                        const int yj = 2 * (fb & 1) + (fb >> 1);
                        uint32_t ypart = sb + SM_RED2 + yj * 128 + ((fg + 2 * yj) & 7) * 16;
                        __nv_bfloat16* out = p.out + fb * DM + fi * 16 + fg;
                        const float2 hw2 = lds64f(sb + SM_X + fb * HPITCH + ((fi >> 1) * 16 + (fg & 6) * 2 + (fi & 1) * 2) * 4);
                        const uint32_t w0 = __float_as_uint(hw2.x), w1 = __float_as_uint(hw2.y);
                        const float nh0 = (fg & 1) ? hi_f(w0) : lo_f(w0), nh1 = (fg & 1) ? hi_f(w1) : lo_f(w1);
                        const float ln0 = bf16r(bf16r(nmean - nh0) * rden) - nh0, ln1 = bf16r(bf16r(nmean - nh1) * rden) - nh1;
                        pin(ypart); pin(out);
                        fin_sync<6>(after(after(after(288, sig), ln0), ln1));
                        CK(10, lds32(ypart));
                        const float4 ya = sum4x4(ypart, 512), yb = sum4x4(ypart + 2048, 512);
                        const float4 y = make_float4(ya.x + yb.x, ya.y + yb.y, ya.z + yb.z, ya.w + yb.w);
                        const float y0 = -(((fb & 1) ? y.y : y.x) + __shfl_xor_sync(0xffffffffu, (fb & 1) ? y.x : y.y, 8));
                        const float y1 = -(((fb & 1) ? y.w : y.z) + __shfl_xor_sync(0xffffffffu, (fb & 1) ? y.z : y.w, 8));
                        const uint32_t ov = pack_bf16(fmaf(y0, sig, ln0), fmaf(y1, sig, ln1));
                        asm volatile("{\n.reg .pred p;\n.reg .b16 lo, hi;\nsetp.ne.u32 p, %2, 0;\nmov.b32 {lo, hi}, %1;\n"
                                     "@p st.global.u16 [%0], lo;\n@p st.global.u16 [%0+16], hi;\n"
                                     "@p exit;\n"
                                     "}" :: "l"(out), "r"(ov), "r"((uint32_t)(b == NB - 1)) : "memory");
                        CK(11, 0);
                        if (lane == 0) TS2(13);
                    }
                }
            }
            if (is_f(cta) && ffn) {
                const int ks = (2 * fi + fw) % 12;
                const int far = near_side(sb) ^ 1;
                uint32_t* dst = &g_st.ax[ks >> 2].w[(~b & 1) * 2 + far][(fi / 6) * 128 + (ks & 3) * 32 + fb * 8 + (fg & 1) * 4 + ((fg >> 1) ^ (ks & 1))];
                uint32_t* dst2 = dst + (far ? -1024 : 1024);
                uint32_t part = sb + SM_RED + fw * 2560 + fb * 128 + ((fg + (fb & 2)) & 7) * 16;
                uint32_t psum = sb + SM_RED + fw * 2560 + 4 * 128 + ((fg + 4) & 7) * 16;
                pin(dst); pin(part); pin(psum);
                asm volatile("bar.sync 4, 320;" ::: "memory");
                CK(6, lds32(part));
                const float4 d = sum4x4(part, 640), cs = sum4x4(psum, 640);
                const float2 mo = lds64f(sb + SM_RED + 5120 + fb * 8);
                nmean = mo.x; rden = mo.y;
                const float g0 = fmaf(nmean, cs.x, -d.x), g1 = fmaf(nmean, cs.y, -d.y), ke = rden * -1.4426950408889634f, r2 = rden * rden;
                const float p0 = g0 * fmaf(-nmean, cs.z, d.z) * r2, p1 = g1 * fmaf(-nmean, cs.w, d.w) * r2;
                const uint32_t av = nonzero(pack_bf16(p0 * rcp_approx(1.0f + ex2_approx(g0 * ke)), p1 * rcp_approx(1.0f + ex2_approx(g1 * ke))));
                st_relaxed(dst, av);
                st_relaxed(dst2, av);
                CK(7, 0);
            }
        }
        warm.done(sb + SM_SCRAP);
        if (cta == 0 && tid == (NAUX + NWORK) * 32) { g_work[0] = 0; g_work[32] = 0; g_cnt_z[0] = 0; }
        return;
    }
    if (warp >= NAUX) {
        const int wk = warp - NAUX;
        const uint32_t bar = sb + BAR_KV + wk * 8;
        const uint32_t buf = sb + SM_KV + wk * TILE_BYTES;
        uint64_t pol;
        asm volatile("createpolicy.fractional.L2::evict_first.b64 %0, 1.0;" : "=l"(pol));
        const int nstatic = NWORK * grid;
        constexpr int POOL0 = NUNITS - NPOOL;
        int uk = wk * grid + cta;
        wait_time(t_start + K0_AT_NS + uk * KSWEEP_NS / nstatic);
        request_tile(buf, &p.k, uk, bar, pol);
        uint32_t koff[3], voff[3];
        {
            const int r = lane & 7, hf = (lane >> 3) & 1;
            const int kkey = hf ? 8 + (r ^ 1) : r;
            const int vh = lane >> 4;
            const int vkey = ((r & 1) ? 8 : 0) + (vh ? (r ^ 1) : r);
#pragma unroll
            for (int b = 0; b < 3; b++) {
                const int rk = 3 * kkey + b, rv = 3 * vkey + b;
                koff[b] = buf + rk * 128 + (((lane >> 4) ^ (rk & 7)) << 4);
                voff[b] = buf + rv * 128 + ((hf ^ (rv & 7)) << 4);
            }
        }
        uint32_t phase = 0;
        uint32_t qf[12][2];
        auto load_q = [&](int u) {
            const uint32_t* q = g_early[u / UPB].q[0][j];
#pragma unroll
            for (int i = 0; i < 4; i++) {
                const uint4 a = ld_relaxed_v4(q + i * 32);
                const float2 c = ld_relaxed_f2(q + i * 32 + 4);
                qf[3 * i][0] = a.x; qf[3 * i][1] = a.y; qf[3 * i + 1][0] = a.z; qf[3 * i + 1][1] = a.w;
                qf[3 * i + 2][0] = __float_as_uint(c.x); qf[3 * i + 2][1] = __float_as_uint(c.y);
            }
        };
        load_q(uk);
        int uq[LAG];
        uint32_t sq[LAG];
#pragma unroll
        for (int i = 0; i < LAG; i++) { uq[i] = -1; sq[i] = 0; }
        uint4 mv = make_uint4(0u, 0u, 0u, 0u);
        float freed = UPB;
        while (true) {
            const int uv = uq[0];
            uint32_t sv = sq[0];
#pragma unroll
            for (int i = 0; i + 1 < LAG; i++) { uq[i] = uq[i + 1]; sq[i] = sq[i + 1]; }
            uq[LAG - 1] = uk;
            if (uk < NUNITS) {
                PH(7);
#pragma unroll 1
                for (int it = 0; it < SPIN_MAX; it++) {
                    uint32_t lo = 0xffffffffu;
#pragma unroll
                    for (int i = 0; i < 12; i++) lo = min(lo, min(qf[i][0], qf[i][1]));
                    if (all(lo != 0)) break;
                    __nanosleep(250);
                    load_q(uk);
                }
                mbar_wait(bar, phase); phase ^= 1;
                PH(0); ARR();
                TSI(0, 16); TSI(1, 18);
                float acc[2][4][4] = {};
#pragma unroll
                for (int ks = 0; ks < 12; ks++) {
#pragma unroll
                    for (int mt = 0; mt < 4; mt++) {
                        uint32_t a[4];
                        ldsm4(a, (koff[ks >> 2] ^ ((ks & 3) << 5)) + mt * 6144);
                        mma16816(acc[ks & 1][mt], a, qf[ks][0], qf[ks][1]);
                    }
                }
                PH(1);
                TSI(0, 17); TSI(1, 19);
                if (uk < nstatic) wait_time(t_start + K1_AT_NS + uk * K1SWEEP_NS / nstatic);
                if (uv < NUNITS) request_tile(buf, uv >= 0 ? &p.v : &p.k, uv >= 0 ? uv : uk + nstatic, bar, pol);
                const float sa = sel4(j, acc[0][0][0], acc[0][1][0], acc[0][2][0], acc[0][3][0]) + sel4(j, acc[1][0][0], acc[1][1][0], acc[1][2][0], acc[1][3][0]);
                const float sc = sel4(j, acc[0][0][2], acc[0][1][2], acc[0][2][2], acc[0][3][2]) + sel4(j, acc[1][0][2], acc[1][1][2], acc[1][2][2], acc[1][3][2]);
                const uint32_t raw = pack_bf16(sa, sc);
                const float scale = -0.07216878364870322f;
                const uint32_t sk = pack_bf16(lo_f(raw) * scale, hi_f(raw) * scale);
                sq[LAG - 1] = sk;
                if (uk >= POOL0) st_relaxed(&g_st.score[uk - POOL0][lane], sk ? sk : 0x80008000u);
                int a = (int)(sk << 16), b = (int)(sk & 0xffff0000u);
                a ^= (a >> 31) & 0x7fff0000; b ^= (b >> 31) & 0x7fff0000;
                const int mx = __reduce_max_sync(0xffffffffu, max(a, b));
                if (lane == 0) st_relaxed(&g_early[uk / UPB].umax[uk % UPB], (uint32_t)mx | 1u);
            }
            if (uv < 0) {
                uk += nstatic;
                load_q(uk);
                continue;
            }
            if (uv >= NUNITS) break;
            const int bh = uv / UPB;
#pragma unroll 1
            for (int it = 0; it < SPIN_MAX; it++) {
                if (all((mv.x & mv.y & mv.z & mv.w & 1u) && (uv < POOL0 || sv != 0) && freed == UPB)) break;
                mv = ld_relaxed_v4(&g_early[bh].umax[lane * 4]);
                if (bh >= RING && bh < RED0) freed = __uint_as_float(ld_relaxed_u32(&g_st.oacc[oidx(bh - RING, (lane & 7) * 8)].w));
                if (uv >= POOL0) sv = ld_relaxed_u32(&g_st.score[uv - POOL0][lane]);
            }
            PH(2); CK(8, sv);
            int un = NUNITS, vn = 0;
            draw(un, g_work, uk < NUNITS && lane == 0);
            uint32_t tdraw;
            asm volatile("mov.u32 %0, %%globaltimer_lo;" : "=r"(tdraw));
            draw(vn, g_work + 32, uq[0] >= POOL0 && lane == 0);
            int mx = __reduce_max_sync(0xffffffffu, max(max((int)mv.x, (int)mv.y), max((int)mv.z, (int)mv.w))) & 0xffff0000;
            mx ^= (mx >> 31) & 0x7fff0000;
            const float m = __int_as_float(mx);
            const float l2e = 1.4426950408889634f;
            const uint32_t pp = pack_bf16(exp2f((lo_f(sv) - m) * l2e), exp2f((hi_f(sv) - m) * l2e));
            uint32_t pb[8];
#pragma unroll
            for (int t = 0; t < 4; t++) {
                pb[2 * t] = __shfl_sync(0xffffffffu, pp, 8 * j + t);
                pb[2 * t + 1] = __shfl_sync(0xffffffffu, pp, 8 * j + 4 + t);
            }
            float lacc[4] = {};
            const uint32_t ones[4] = {0x3f803f80u, 0x3f803f80u, 0x3f803f80u, 0x3f803f80u};
#pragma unroll
            for (int t = 0; t < 4; t++) mma16816(lacc, ones, pb[2 * t], pb[2 * t + 1]);
            if (uv < nstatic) {
                asm volatile("bar.sync 2, %0;" :: "n"((NWORK + 2) * 32) : "memory");
                TSW(3);
            }
            const int grp = 16 * j + 4 * (g & 1) + (g >> 1);
            uint32_t mode = (bh >= RED0) + (bh >= NBH - 4);
            float tag = mode ? 1.f : (float)(bh + 1), tag2 = fmaf(__uint_as_float(voff[0]), 0.f, tag);
            void* dst = mode == 0 ? (void*)&g_ring[bh % RING][uv % UPB][grp] :
                        mode == 1 ? (void*)&g_st.oacc[oidx(bh, grp)] : (void*)&g_st.ox[0].w[uv % OREP * 2 + (~(near_side(sb) ^ uv % OREP) & 1)][oidx(bh & 3, grp) * 4];
            if (mode == 2 && lane < 2) red_f2(reinterpret_cast<float*>(&g_st.lx.w[lane][(bh & 3) * 256]), lacc[0], 1.f);
            CK(10, __float_as_uint(lacc[0]));
            un = __shfl_sync(0xffffffffu, un, 0) + (LAG + 1) * nstatic;
            vn = __shfl_sync(0xffffffffu, vn, 0);
            if (uq[0] >= POOL0) uq[0] = POOL0 + vn;
            if (vn == FW_TICKET && lane == 0) st_relaxed(g_st.fw_time, tdraw | 1u);
            if (uq[0] < NUNITS && un >= NUNITS) {
                mv = ld_relaxed_v4(&g_early[uq[0] / UPB].umax[lane * 4]);
                if (uq[0] < RED0 * UPB) freed = 0.f;
                if (uq[0] >= POOL0) sq[0] = ld_relaxed_u32(&g_st.score[uq[0] - POOL0][lane]);
            }
            pin(dst); pin(mode); pin(tag); pin(tag2); pin(voff[0]); pin(voff[1]); pin(voff[2]);
            PH(3); CK(9, vn);
            mbar_wait(bar, phase); phase ^= 1;
            PH(4); ARR(); CK(12, lds32(buf));
            float acc[12][4] = {};
#pragma unroll
            for (int t = 0; t < 4; t++) {
#pragma unroll
                for (int mt = 0; mt < 12; mt++) {
                    uint32_t a[4];
                    ldsm4t(a, (voff[mt >> 2] ^ ((mt & 3) << 5)) + t * 6144);
                    mma16816(acc[mt], a, pb[2 * t], pb[2 * t + 1]);
                }
            }
            PH(5);
            if (lane == 0) PROG(un);
            if (un < NUNITS || uq[0] < NUNITS) request_tile(buf, un < NUNITS ? &p.k : &p.v, un < NUNITS ? un : uq[0], bar, pol);
            if (un < NUNITS || uq[0] < NUNITS) CK(11, 0);
            float o[6];
#pragma unroll
            for (int e = 0; e < 6; e++) {
                const int q = e % 3, c = (e / 3) * 2;
                o[e] = sel4(j, acc[q][c], acc[3 + q][c], acc[6 + q][c], acc[9 + q][c]);
            }
            put_groups(dst, mode, o, tag, tag2);
            CK(13, 0);
            if (un < NUNITS) load_q(un);
            if (lane == 0) red_f2(&g_st.lsum[bh][0].x, lacc[0], 1.f);
            PH(6);
            if (uq[0] >= NUNITS && un >= NUNITS) break;
            uk = un;
            if (uq[0] < NUNITS && un < NUNITS) {
                const int nb = uq[0] / UPB;
                mv = ld_relaxed_v4(&g_early[nb].umax[lane * 4]);
                freed = nb >= RING && nb < RED0 ? __uint_as_float(ld_relaxed_u32(&g_st.oacc[oidx(nb - RING, (lane & 7) * 8)].w)) : UPB;
                if (uq[0] >= POOL0) sq[0] = ld_relaxed_u32(&g_st.score[uq[0] - POOL0][lane]);
            }
        }
        TSW(4 + wk);
        return;
    }

    __nv_bfloat16* xs = reinterpret_cast<__nv_bfloat16*>(smem + SM_X);
    float* red = reinterpret_cast<float*>(smem + SM_RED);
    const int frow = (lane & 7) + ((lane >> 4) << 3), fcol = (lane >> 3) & 1;
    const uint32_t f64b = sb + (frow * 4 + (fcol ^ ((frow >> 1) & 3))) * 16;
    if (cta < NQ_CTAS) {
        TS(26);
        if (warp >= 4) {
            uint2 xr[5];
#pragma unroll
            for (int i = 0; i < 5; i++) xr[i] = *reinterpret_cast<const uint2*>(p.x + (warp - 4) * DM + i * 128 + lane * 4);
            float v[20];
#pragma unroll
            for (int i = 0; i < 5; i++) {
                v[4 * i] = lo_f(xr[i].x); v[4 * i + 1] = hi_f(xr[i].x); v[4 * i + 2] = lo_f(xr[i].y); v[4 * i + 3] = hi_f(xr[i].y);
            }
            layernorm20(v);
#pragma unroll
            for (int i = 0; i < 5; i++)
                *reinterpret_cast<uint2*>(xs + (warp - 4) * XPITCH + i * 128 + lane * 4) =
                    make_uint2(pack_bf16(v[4 * i], v[4 * i + 1]), pack_bf16(v[4 * i + 2], v[4 * i + 3]));
        }
        aux_sync();
        TS(27);
        mbar_wait(sb + BAR_WQ + (warp >> 1) * 8, 0);
        TS(1);
        const uint32_t xfrag = sb + SM_X + ((g & 3) * XPITCH + 2 * j) * 2;
        float acc[3][4] = {};
#pragma unroll
        for (int s = 0; s < 5; s++) {
            const int ks = warp * 5 + s;
            const uint32_t b0 = lds32(xfrag + ks * 32), b1 = lds32(xfrag + ks * 32 + 16);
            const int row = ks * 16 + frow;
#pragma unroll
            for (int mt = 0; mt < 3; mt++) {
                uint32_t a[4];
                ldsm4t(a, sb + SM_W + (row * 6 + 2 * mt + fcol) * 16);
                mma16816(acc[mt], a, b0, b1);
            }
        }
        if (j < 2) {
#pragma unroll
            for (int mt = 0; mt < 3; mt++) {
                *reinterpret_cast<float2*>(red + warp * 216 + mt * 72 + g * 4 + 2 * j) = make_float2(acc[mt][0], acc[mt][1]);
                *reinterpret_cast<float2*>(red + warp * 216 + mt * 72 + 36 + g * 4 + 2 * j) = make_float2(acc[mt][2], acc[mt][3]);
            }
        }
        aux_sync();
        if (warp < 4) {
            const float* src = red + min(g, 5) * 36 + warp * 8 + j;
            float s0 = 0.f, s1 = 0.f;
#pragma unroll
            for (int w = 0; w < 8; w++) { s0 += src[w * 216]; s1 += src[w * 216 + 4]; }
            st_relaxed(&g_early[j * NH + (cta >> 2)].q[cta & 3][warp][g], pack_neg(s0, s1));
        }
        TS(28);
    }
    fin_sync<3>();
    mbar_wait(sb + BAR_WO, 0);
    TS(7);
    uint32_t part = sb + SM_RED + (warp * 32 + 8 * j + g) * 4;

#pragma unroll 1
    for (int b = 0; b < NB; b++) {
        if (cta >= NE_CTAS) {
            uint32_t a[6][2][4];
#pragma unroll
            for (int s = 0; s < 6; s++) {
#pragma unroll
                for (int mt = 0; mt < 2; mt++) ldsm4t(a[s][mt], (f64b ^ (mt * 32)) + SM_A + (warp * 6 + s) * 1024);
            }
            const int bh = b * NH + 28 + (warp >> 1);
            const int side = near_side(sb) ^ 1;
            const void* osrc[OREP];
#pragma unroll
            for (int c = 0; c < OREP; c++)
                osrc[c] = b == NB - 1 ? (const void*)&g_st.ox[c >> 1].w[side ^ (c & 1) * 3][oidx(bh & 3, (warp & 1) * 32 + lane) * 4] : &g_st.oacc[oidx(bh, (warp & 1) * 32 + lane)];
            const void* lsrc = b == NB - 1 ? (const void*)&g_st.lx.w[side][(bh & 3) * 256] : g_st.lsum[bh];
            wait_row_o(bh, 1);
            const float rl = rcp_approx(wait_sum(lsrc, UPB)) * (b == NB - 1 ? 1.f : 1.f / OREP), full = b == NB - 1 ? UPB : UPB * OREP;
            float4 ov;
            float px, py, pz;
            Warm warm;
#pragma unroll 1
            for (int it = 0; it < SPIN_MAX; it++) {
                wait_slot<PH_O>();
                float4 oc[OREP];
#pragma unroll
                for (int c = 0; c < OREP; c++) oc[c] = ld_relaxed_f4(osrc[c]);
                warm();
                ov = oc[0];
#pragma unroll
                for (int c = 1; c < OREP; c++) { ov.x += oc[c].x; ov.y += oc[c].y; ov.z += oc[c].z; ov.w += oc[c].w; }
                ov.x *= rl; ov.y *= rl; ov.z *= rl;
                px = __shfl_xor_sync(0xffffffffu, ov.x, 4); py = __shfl_xor_sync(0xffffffffu, ov.y, 4); pz = __shfl_xor_sync(0xffffffffu, ov.z, 4);
                if (all(ov.w == full)) break;
            }
            CK(0, __float_as_uint(ov.x));
            if (ov.x != 1.2345f && warp == 7) TSW(14);
            const uint32_t w[3] = {pack_bf16(ov.x, px), pack_bf16(ov.y, py), pack_bf16(ov.z, pz)};
            float acc[2][2][4] = {};
#pragma unroll
            for (int s = 0; s < 6; s++) {
                const uint32_t b0 = __shfl_sync(0xffffffffu, w[s % 3], (s / 3) * 16 + j);
                const uint32_t b1 = __shfl_sync(0xffffffffu, w[s % 3], (s / 3) * 16 + 8 + j);
#pragma unroll
                for (int mt = 0; mt < 2; mt++) mma16816(acc[mt][s & 1], a[s][mt], b0, b1);
            }
            sts32f(part, sel4(j, acc[0][0][0] + acc[0][1][0], acc[0][0][2] + acc[0][1][2], acc[1][0][0] + acc[1][1][0], acc[1][0][2] + acc[1][1][2]));
            CK(1, 0);
            fin_arrive<4>();
            warm.done(sb + SM_SCRAP);
            fin_sync<5>();
            if (cta < NE_CTAS + 4 && tid < 64) reinterpret_cast<uint4*>(&g_early[b * NH + 28 + cta - NE_CTAS])[tid] = make_uint4(0u, 0u, 0u, 0u);
        } else {
            const int bh = b * NH + (cta >> 2);
            if (warp == 0) wait_row_o(bh, UPB);
            aux_sync();
            if (warp < 5) {
                uint32_t ob[12][2];
                load_o<4>(ob, bh, 0, j);
                float acc[2][2][4] = {};
#pragma unroll
                for (int ks = 0; ks < 12; ks++) {
#pragma unroll
                    for (int mt = 0; mt < 2; mt++) {
                        uint32_t a[4];
                        ldsm4t(a, (f64b ^ (mt * 32)) + SM_A + warp * 12288 + ks * 1024);
                        mma16816(acc[mt][ks & 1], a, ob[ks][0], ob[ks][1]);
                    }
                }
                red_f2(&g_st.attn[b][(cta & 3) * 160 + warp * 32 + 8 * j + g].x,
                       sel4(j, acc[0][0][0] + acc[0][1][0], acc[0][0][2] + acc[0][1][2], acc[1][0][0] + acc[1][1][0], acc[1][0][2] + acc[1][1][2]), 1.f);
                TS(8);
            } else if (warp > 5 && (cta & 3) == 0) {
                reinterpret_cast<uint4*>(&g_early[bh])[tid - 192] = make_uint4(0u, 0u, 0u, 0u);
            }
        }
        if (b < NB - 2) continue;

        if (is_f(cta)) {
            uint32_t ga[10][2][4];
            uint4 hv[5];
            const uint32_t hfrag = sb + SM_X + min(g, 4) * HPITCH + ((warp >> 1) * 80 + 4 * j) * 4;
            if (b == NB - 1) mbar_wait(sb + BAR_FW + warp * 8, 0);
            if (warp == 7) TSW(10);
            CK(12, lds32(sb + SM_W));
#pragma unroll
            for (int s = 0; s < 10; s++) {
#pragma unroll
                for (int mt = 0; mt < 2; mt++) ldsm4t(ga[s][mt], (f64b ^ (mt * 32)) + SM_W + (warp * 10 + s) * 1024);
            }
            const uint32_t gpart = sb + SM_RED + (warp >> 1) * 640 + j * 256 + ((g + 2 * j) & 7) * 16 + (warp & 1) * 8;
            mbar_wait(sb + BAR_H, b & 1);
#pragma unroll
            for (int s = 0; s < 5; s++) hv[s] = lds128(hfrag + s * 64);
            CK(4, hv[0].x);
            float acc[2][2][4] = {};
#pragma unroll
            for (int s = 0; s < 10; s++) {
#pragma unroll
                for (int mt = 0; mt < 2; mt++)
                    mma16816(acc[mt][s & 1], ga[s][mt], (s & 1) ? hv[s >> 1].z : hv[s >> 1].x, (s & 1) ? hv[s >> 1].w : hv[s >> 1].y);
            }
#pragma unroll
            for (int mt = 0; mt < 2; mt++) {
                if (j < 3) sts64f(gpart + mt * 2560, acc[mt][0][0] + acc[mt][1][0], acc[mt][0][2] + acc[mt][1][2]);
                if (j < 2) sts64f(gpart + mt * 2560 + 128, acc[mt][0][1] + acc[mt][1][1], acc[mt][0][3] + acc[mt][1][3]);
            }
            CK(5, 0);
            asm volatile("bar.arrive 4, 320;" ::: "memory");
        } else if (is_g(cta)) {
            const uint32_t* asrc = &g_st.ax[0].w[(~b & 1) * 2 + near_side(sb)][warp * 128 + ((g >> 2) * 2 + (j >> 1)) * 32 + (g & 3) * 8 + (j & 1) * 4];
            const uint32_t ypart = sb + SM_RED2 + warp * 512 + j * 128 + ((g + 2 * j) & 7) * 16;
            uint32_t wb[12][4];
            uint4 va[3] = {};
            uint32_t lo[3] = {};
            auto ask = [&]() {
#pragma unroll
                for (int i = 0; i < 3; i++) ld_relaxed_v4_if(va[i], asrc + i * 4096, lo[i] == 0);
            };
            auto complete = [&]() {
#pragma unroll
                for (int i = 0; i < 3; i++) lo[i] = min(min(va[i].x, va[i].y), min(va[i].z, va[i].w));
                return all(min(lo[0], min(lo[1], lo[2])) != 0);
            };
            const int jj = (lane & 7) >> 1, q = jj >> 1, hi = lane >> 4;
            const uint32_t wsrc = sb + SM_W + warp * 6144 + q * 512 + ((hi ^ q) * 4 + (jj & 1) * 2 + (lane & 1)) * 32 + ((fcol ^ hi ^ q) << 4);
            mbar_wait(sb + BAR_H, b & 1);
            if (b == NB - 1) mbar_wait(sb + BAR_FW + warp * 8, 0);
            if (warp == 7) TSW(11);
            CK(13, lds32(sb + SM_W));
            ask();
#pragma unroll
            for (int s = 0; s < 12; s++) ldsm4t(wb[s], wsrc + (s >> 2) * 2048 + (s & 1) * 1024 + (s & 2) * 128);
            Warm warm;
            if (!complete()) {
#pragma unroll 1
                for (int it = 0; it < SPIN_MAX; it++) {
                    ask();
                    warm();
                    if (complete()) break;
                }
            }
            CK(8, va[0].x);
            if (va[0].x != 0x12345 && warp == 7) TSW(15);
            float acc[6][4] = {};
#pragma unroll
            for (int s = 0; s < 12; s++) {
                const uint4 v = va[s >> 2];
                mma16816(acc[s % 6], wb[s], (s & 2) ? v.z : v.x, (s & 2) ? v.w : v.y);
            }
            float y[4];
#pragma unroll
            for (int e = 0; e < 4; e++) y[e] = j < 2 ? (acc[0][e] + acc[2][e]) + acc[4][e] : (acc[1][e] + acc[3][e]) + acc[5][e];
            sts128f(ypart, y[0], y[1], y[2], y[3]);
            CK(9, 0);
            fin_arrive<6>();
            warm.done(sb + SM_SCRAP);
        }
    }
}

typedef CUresult (*EncodeFn)(CUtensorMap*, CUtensorMapDataType, cuuint32_t, void*, const cuuint64_t*, const cuuint64_t*,
                             const cuuint32_t*, const cuuint32_t*, CUtensorMapInterleave, CUtensorMapSwizzle,
                             CUtensorMapL2promotion, CUtensorMapFloatOOBfill);

CUtensorMap make_map(EncodeFn enc, void* ptr, uint64_t cols, uint64_t rows, uint32_t bcols, uint32_t brows,
                     CUtensorMapSwizzle sw, CUtensorMapL2promotion promo) {
    CUtensorMap m;
    const cuuint64_t dims[2] = {cols, rows};
    const cuuint64_t strides[1] = {cols * 2};
    const cuuint32_t box[2] = {bcols, brows};
    const cuuint32_t es[2] = {1, 1};
    enc(&m, CU_TENSOR_MAP_DATA_TYPE_BFLOAT16, 2, ptr, dims, strides, box, es, CU_TENSOR_MAP_INTERLEAVE_NONE, sw, promo,
        CU_TENSOR_MAP_FLOAT_OOB_FILL_NONE);
    return m;
}

}

extern "C" void kernel_launch(void* const* d_in, const int* in_sizes, int n_in, void* d_out, int out_size) {
    (void)in_sizes; (void)n_in; (void)out_size;
    static EncodeFn enc = nullptr;
    static int sms = 0;
    if (!enc) {
        cudaDriverEntryPointQueryResult qr;
        cudaGetDriverEntryPoint("cuTensorMapEncodeTiled", (void**)&enc, cudaEnableDefault, &qr);
        int dev = 0;
        cudaGetDevice(&dev);
        cudaDeviceGetAttribute(&sms, cudaDevAttrMultiProcessorCount, dev);
        cudaFuncSetAttribute(fused_decode_kernel, cudaFuncAttributeMaxDynamicSharedMemorySize, SM_TOTAL);
    }
    if (sms < NCTAS) return;
    const CUtensorMapL2promotion WPROMO = CU_TENSOR_MAP_L2_PROMOTION_L2_128B;
    Params p;
    p.k = make_map(enc, d_in[1], 64, (uint64_t)NBH * SK * 3, 64, TILE_ROWS, CU_TENSOR_MAP_SWIZZLE_128B, CU_TENSOR_MAP_L2_PROMOTION_NONE);
    p.v = make_map(enc, d_in[2], 64, (uint64_t)NBH * SK * 3, 64, TILE_ROWS, CU_TENSOR_MAP_SWIZZLE_128B, CU_TENSOR_MAP_L2_PROMOTION_NONE);
    p.wq = make_map(enc, d_in[3], NH * DH, DM, 48, 160, CU_TENSOR_MAP_SWIZZLE_NONE, WPROMO);
    p.wo = make_map(enc, d_in[4], DM, NH * DH, 32, DH, CU_TENSOR_MAP_SWIZZLE_64B, WPROMO);
    p.wg = make_map(enc, d_in[7], FF, DM, 32, 160, CU_TENSOR_MAP_SWIZZLE_64B, WPROMO);
    p.wu = make_map(enc, d_in[8], FF, DM, 32, 160, CU_TENSOR_MAP_SWIZZLE_64B, WPROMO);
    {
        const cuuint64_t dims[4] = {DM, 2, 8, FF / 16}, strides[3] = {8 * DM * 2, DM * 2, 16 * DM * 2};
        const cuuint32_t box[4] = {16, 2, 8, 12}, es[4] = {1, 1, 1, 1};
        enc(&p.wd, CU_TENSOR_MAP_DATA_TYPE_BFLOAT16, 4, d_in[9], dims, strides, box, es, CU_TENSOR_MAP_INTERLEAVE_NONE,
            CU_TENSOR_MAP_SWIZZLE_32B, WPROMO, CU_TENSOR_MAP_FLOAT_OOB_FILL_NONE);
    }
    p.x = (const __nv_bfloat16*)d_in[0];
    p.wr = (const __nv_bfloat16*)d_in[6];
    p.out = (__nv_bfloat16*)d_out;
    fused_decode_kernel<<<NCTAS, NTHREADS, SM_TOTAL, cudaStreamPerThread>>>(p);
}
```

```cpp
#include <cuda_runtime.h>
#include <cuda_bf16.h>
#include <cuda.h>
#include <stdint.h>

namespace {

constexpr int NB = 4, NH = 32, SK = 8192, DH = 192, DM = 640, FF = 1536;
constexpr int NBH = NB * NH;
constexpr int TILE = 64;
constexpr int UPB = SK / TILE;
constexpr int NUNITS = NBH * UPB;
constexpr int TILE_BYTES = TILE * DH * 2;
constexpr int TILE_ROWS = TILE * 3;
constexpr int NCTAS = 132;
constexpr int NQ_CTAS = 128;
constexpr int NE_CTAS = 112;
__host__ __device__ constexpr bool is_f(int cta) { return cta < NE_CTAS && cta % 14 < 11 && !(cta & 1); }
__host__ __device__ constexpr bool is_g(int cta) { return cta < NE_CTAS && cta % 14 < 11 && (cta & 1); }
__host__ __device__ constexpr int ffn_slice(int cta) { return cta / 14 * ((cta & 1) ? 5 : 6) + cta % 14 / 2; }

#define NWORK 2
#define LAG 3
#define NPOOL 896
#define RED0 116
#define RING 12
#define OREP 2
#define K0_AT_NS 1150
#define WO_AT_NS (K0_AT_NS + 2000)
#define K1_AT_NS (K0_AT_NS + 4400)
#define WO_STEP_NS 75
constexpr int KSWEEP_NS = 2000;
#define FW_TICKET (NPOOL + 32)
#define FW_AT_NS 2090
#define FW_GAP 280
#define FW_MID 2100
#define FW_GAP2 200
#define HGATE_NS 700
#define SLOT_TICKS 9
#define SLOT_OPEN 3
#define PH_O 0
#define PH_H 8
#define PH_M 2
#define NPROBE 24
#define MIX_R 6
#define MIX_ROWS 3
constexpr int MIX = MIX_ROWS * UPB, MIX1 = (NBH - 4) * UPB, MIX0 = MIX1 - (MIX1 - (LAG + 1) * NWORK * NCTAS) / MIX * MIX;
static_assert((MIX1 - (NUNITS - NPOOL)) % MIX == 0, "the pool starts with a group of rows");
__device__ __forceinline__ int unit_of(int t) {
    const unsigned r = (unsigned)(t - MIX0) % MIX, e = t - MIX1;
    if (e < 4 * UPB) return MIX1 + (e & 256) + (e & 3) * 64 + (e & 255) / 4;
    return t < MIX0 || t >= MIX1 ? t : t - r + r % MIX_R * (MIX / MIX_R) + r / MIX_R;
}
static_assert(FW_TICKET < NPOOL + NWORK * NCTAS, "every worker draws one ticket beyond the pool");
constexpr int NAUX = 8;
constexpr int NTHREADS = (NAUX + NWORK + 2) * 32;
constexpr int SPIN_MAX = 1 << 22;

constexpr int SM_KV = 0;
constexpr int SM_A = SM_KV + NWORK * TILE_BYTES;
constexpr int SM_W = SM_A + 61440;
constexpr int SM_X = SM_W + 81920;
constexpr int XPITCH = 648;
constexpr int HPITCH = 1344;
constexpr int SM_RED = SM_X + 5 * HPITCH + 64;
constexpr int SM_RED2 = SM_RED + 8 * 48 * 4 * 4;
constexpr int SM_MISC = SM_RED2 + 4096;
constexpr int BAR_WQ = SM_MISC, SM_SCRAP = SM_MISC + 32, BAR_WO = SM_MISC + 40, SM_SIDE = SM_MISC + 48, BAR_H = SM_MISC + 56, BAR_FW = SM_MISC + 64;
constexpr int BAR_KV = BAR_FW + 64;
constexpr int SM_TOTAL = BAR_KV + NWORK * 8;
static_assert(SM_W % 1024 == 0 && NB * XPITCH * 2 <= 4 * HPITCH && SM_RED % 128 == 0, "smem layout");

struct Params {
    CUtensorMap k, v;
    CUtensorMap wq;
    CUtensorMap wo;
    CUtensorMap wg, wu;
    CUtensorMap wd;
    const __nv_bfloat16 *x, *wr;
    __nv_bfloat16* out;
};

struct Early {
    uint32_t q[4][4][8];
    uint32_t umax[UPB];
};
struct Twin { uint32_t w[4][1024]; };
constexpr int PROBE = 1024 - 32;
#define LSTRIDE 16
struct State {
    Twin ax[3];
    Twin hx;
    Twin ox[(OREP + 1) / 2];
    Twin lx;
    float4 oacc[NBH * 64];
    float2 attn[NB][DM];
    uint32_t fw_time[32];
    float2 lsum[NBH][LSTRIDE];
    uint32_t score[NPOOL][32];
};
__host__ __device__ constexpr int oidx(int row, int grp) {
    return (row >> 2) * 256 + ((row & 1) * 2 + (grp >> 5)) * 64 + (row & 2) * 16 + (grp & 31);
}
constexpr int STATE_V4 = ((sizeof(State) / 32 + NQ_CTAS - 1) / NQ_CTAS) * 2;
static_assert(sizeof(State) % 32 == 0, "State is cleared in whole sectors");
static_assert(sizeof(Early) == 64 * 16, "an Early entry is cleared by 64 threads");
struct Scratch {
    State st;
    unsigned work[64];
    unsigned cnt_z[32];
    Early early[NBH];
    alignas(4096) float4 ring[RING][UPB][64];
};
constexpr size_t PAGE = 2u << 20;
static_assert(sizeof(Scratch) <= PAGE, "scratch must fit one page");
__device__ __align__(128) unsigned char g_raw[2 * PAGE];
__device__ __forceinline__ Scratch* scratch() {
    return reinterpret_cast<Scratch*>((reinterpret_cast<uintptr_t>(g_raw) + PAGE - 1) & ~(uintptr_t)(PAGE - 1));
}
#define g_early scratch()->early
#define g_st scratch()->st
#define g_ring scratch()->ring
#define g_cnt_z scratch()->cnt_z
#define g_work scratch()->work
#define ALL_LOADERS 0
#define TS(i)
#define TSW(i)
#define TS2(i)
#define TSI(n, i)
#define PH(i)
#define CK(i, dep)
#define ARR()
#define PROG(u)

__device__ __forceinline__ uint32_t s2u(const void* p) { return (uint32_t)__cvta_generic_to_shared(p); }
__device__ __forceinline__ void mbar_init(uint32_t bar, int cnt) {
    asm volatile("mbarrier.init.shared::cta.b64 [%0], %1;" :: "r"(bar), "r"(cnt) : "memory");
}
__device__ __forceinline__ void mbar_wait(uint32_t bar, uint32_t parity) {
    asm volatile("{\n.reg .pred p;\n.reg .u32 n;\nmov.u32 n, 0;\nWAIT_LOOP:\n"
                 "mbarrier.try_wait.parity.shared::cta.b64 p, [%0], %1;\n"
                 "@p bra WAIT_DONE;\nadd.u32 n, n, 1;\nsetp.lt.u32 p, n, %2;\n@p bra WAIT_LOOP;\nWAIT_DONE:\n}"
                 :: "r"(bar), "r"(parity), "n"(SPIN_MAX) : "memory");
}
__device__ __forceinline__ void request_tile(uint32_t dst, const CUtensorMap* tm, int unit, uint32_t bar, uint64_t pol) {
    asm volatile("{\n.reg .pred p;\nelect.sync _|p, 0xffffffff;\n"
                 "@p mbarrier.arrive.expect_tx.shared::cta.b64 _, [%2], %6;\n"
                 "@p cp.async.bulk.tensor.2d.shared::cluster.global.mbarrier::complete_tx::bytes.L2::cache_hint "
                 "[%0], [%1, {%3, %4}], [%2], %5;\n}"
                 :: "r"(dst), "l"(tm), "r"(bar), "r"(0), "r"(unit * TILE_ROWS), "l"(pol), "n"(TILE_BYTES) : "memory");
}
__device__ __forceinline__ void put_groups(void* dst, int mode, const float (&o)[6], float tag, float tag2) {
    asm volatile("{\n.reg .pred s, t;\n.reg .b128 u, v;\n.reg .b64 a, b;\n"
                 "setp.eq.s32 s, %1, 0;\nsetp.ne.s32 t, %1, 2;\nxor.b64 a, %0, 4096;\n"
                 "@t bra.uni SINGLE;\n"
                 "red.relaxed.gpu.global.add.v4.f32 [a], {%2,%3,%4,%8};\n"
                 "red.relaxed.gpu.global.add.v4.f32 [a+128], {%5,%6,%7,%9};\n"
                 "SINGLE:\n"
                 "@s bra.uni STORE;\n"
                 "red.relaxed.gpu.global.add.v4.f32 [%0], {%2,%3,%4,%8};\n"
                 "red.relaxed.gpu.global.add.v4.f32 [%0+128], {%5,%6,%7,%9};\n"
                 "STORE:\n"
                 "mov.b64 a, {%2, %3};\nmov.b64 b, {%4, %8};\nmov.b128 u, {a, b};\n"
                 "mov.b64 a, {%5, %6};\nmov.b64 b, {%7, %9};\nmov.b128 v, {a, b};\n"
                 "@s st.relaxed.gpu.global.b128 [%0], u;\n@s st.relaxed.gpu.global.b128 [%0+128], v;\n}"
                 :: "l"(dst), "r"(mode), "f"(o[0]), "f"(o[1]), "f"(o[2]), "f"(o[3]), "f"(o[4]), "f"(o[5]), "f"(tag), "f"(tag2) : "memory");
}
__device__ __forceinline__ void request_box(uint32_t dst, const CUtensorMap* tm, int col, int row, uint32_t bar, uint32_t bytes) {
    asm volatile("{\n.reg .pred p, q;\nelect.sync _|p, 0xffffffff;\nsetp.ne.and.u32 q, %5, 0, p;\n"
                 "@q mbarrier.arrive.expect_tx.shared::cta.b64 _, [%2], %5;\n"
                 "@p cp.async.bulk.tensor.2d.shared::cluster.global.mbarrier::complete_tx::bytes [%0], [%1, {%3, %4}], [%2];\n}"
                 :: "r"(dst), "l"(tm), "r"(bar), "r"(col), "r"(row), "r"(bytes) : "memory");
}
__device__ __forceinline__ uint32_t lds32(uint32_t addr) {
    uint32_t v;
    asm volatile("ld.shared.u32 %0, [%1];" : "=r"(v) : "r"(addr) : "memory");
    return v;
}
__device__ __forceinline__ void ldsm4(uint32_t (&r)[4], uint32_t addr) {
    asm volatile("ldmatrix.sync.aligned.m8n8.x4.shared.b16 {%0,%1,%2,%3}, [%4];"
                 : "=r"(r[0]), "=r"(r[1]), "=r"(r[2]), "=r"(r[3]) : "r"(addr) : "memory");
}
__device__ __forceinline__ void ldsm4t(uint32_t (&r)[4], uint32_t addr) {
    asm volatile("ldmatrix.sync.aligned.m8n8.x4.trans.shared.b16 {%0,%1,%2,%3}, [%4];"
                 : "=r"(r[0]), "=r"(r[1]), "=r"(r[2]), "=r"(r[3]) : "r"(addr) : "memory");
}
__device__ __forceinline__ void mma16816(float (&c)[4], const uint32_t (&a)[4], uint32_t b0, uint32_t b1) {
    asm volatile("mma.sync.aligned.m16n8k16.row.col.f32.bf16.bf16.f32 {%0,%1,%2,%3}, {%4,%5,%6,%7}, {%8,%9}, {%0,%1,%2,%3};"
                 : "+f"(c[0]), "+f"(c[1]), "+f"(c[2]), "+f"(c[3])
                 : "r"(a[0]), "r"(a[1]), "r"(a[2]), "r"(a[3]), "r"(b0), "r"(b1));
}
struct Warm {
    float c[4] = {};
    __device__ __forceinline__ void operator()() {
        asm volatile("mma.sync.aligned.m16n8k8.row.col.f32.bf16.bf16.f32 {%0,%1,%2,%3}, {%4,%4}, {%4}, {%0,%1,%2,%3};"
                     : "+f"(c[0]), "+f"(c[1]), "+f"(c[2]), "+f"(c[3]) : "r"(0));
    }
    __device__ __forceinline__ void done(uint32_t scrap) {
        asm volatile("{\n.reg .pred p;\nsetp.gt.f32 p, %1, 0f3f800000;\n@p st.shared.f32 [%0], %1;\n}" :: "r"(scrap), "f"(c[0]) : "memory");
    }
};
__device__ __forceinline__ uint4 ld_relaxed_v4(const void* p) {
    uint4 v;
    asm volatile("ld.relaxed.gpu.global.v4.u32 {%0,%1,%2,%3}, [%4];" : "=r"(v.x), "=r"(v.y), "=r"(v.z), "=r"(v.w) : "l"(p) : "memory");
    return v;
}
__device__ __forceinline__ float4 ld_relaxed_f4(const void* p) {
    float4 v;
    asm volatile("ld.relaxed.gpu.global.v4.f32 {%0,%1,%2,%3}, [%4];" : "=f"(v.x), "=f"(v.y), "=f"(v.z), "=f"(v.w) : "l"(p) : "memory");
    return v;
}
__device__ __forceinline__ float2 ld_relaxed_f2(const void* p) {
    float2 v;
    asm volatile("ld.relaxed.gpu.global.v2.f32 {%0,%1}, [%2];" : "=f"(v.x), "=f"(v.y) : "l"(p) : "memory");
    return v;
}
__device__ __forceinline__ float4 ld_relaxed_b128(const void* p) {
    float4 v;
    asm volatile("{\n.reg .b128 t;\n.reg .b64 a, b;\nld.relaxed.gpu.global.b128 t, [%4];\nmov.b128 {a, b}, t;\n"
                 "mov.b64 {%0, %1}, a;\nmov.b64 {%2, %3}, b;\n}" : "=f"(v.x), "=f"(v.y), "=f"(v.z), "=f"(v.w) : "l"(p) : "memory");
    return v;
}
__device__ __forceinline__ void st_relaxed_b128(void* p, float x, float y, float z, float w) {
    asm volatile("{\n.reg .b128 t;\n.reg .b64 a, b;\nmov.b64 a, {%1, %2};\nmov.b64 b, {%3, %4};\nmov.b128 t, {a, b};\n"
                 "st.relaxed.gpu.global.b128 [%0], t;\n}" :: "l"(p), "f"(x), "f"(y), "f"(z), "f"(w) : "memory");
}
__device__ __forceinline__ unsigned ld_acquire(const unsigned* p) {
    unsigned v;
    asm volatile("ld.acquire.gpu.global.u32 %0, [%1];" : "=r"(v) : "l"(p) : "memory");
    return v;
}
__device__ __forceinline__ void st_relaxed(void* p, uint32_t v) {
    asm volatile("st.relaxed.gpu.global.u32 [%0], %1;" :: "l"(p), "r"(v) : "memory");
}
__device__ __forceinline__ void red_f2(float* p, float a, float b) {
    asm volatile("red.relaxed.gpu.global.add.v2.f32 [%0], {%1,%2};" :: "l"(p), "f"(a), "f"(b) : "memory");
}
__device__ __forceinline__ void draw(int& ticket, unsigned* ctr, bool pred) {
    asm volatile("{\n.reg .pred p;\nsetp.ne.u32 p, %2, 0;\n@p atom.relaxed.gpu.global.inc.u32 %0, [%1], 0x7fffffff;\n}"
                 : "+r"(ticket) : "l"(ctr), "r"((uint32_t)pred) : "memory");
}
__device__ __forceinline__ void red_release(unsigned* p) {
    asm volatile("red.release.gpu.global.add.u32 [%0], 1;" :: "l"(p) : "memory");
}
__device__ __forceinline__ uint32_t ld_relaxed_u32(const void* p) {
    uint32_t v;
    asm volatile("ld.relaxed.gpu.global.u32 %0, [%1];" : "=r"(v) : "l"(p) : "memory");
    return v;
}
__device__ __forceinline__ float rcp_approx(float v) {
    float r;
    asm("rcp.approx.ftz.f32 %0, %1;" : "=f"(r) : "f"(v));
    return r;
}
__device__ __forceinline__ float ex2_approx(float v) {
    float e;
    asm("ex2.approx.ftz.f32 %0, %1;" : "=f"(e) : "f"(v));
    return e;
}
__device__ __forceinline__ float sigmoid_approx(float v) { return rcp_approx(1.0f + ex2_approx(v * -1.4426950408889634f)); }
__device__ __forceinline__ float sqrt_approx(float v) {
    float r;
    asm("sqrt.approx.ftz.f32 %0, %1;" : "=f"(r) : "f"(v));
    return r;
}
__device__ __forceinline__ bool all(bool v) { return __all_sync(0xffffffffu, v); }
__device__ __forceinline__ void wait_count(const unsigned* p, unsigned target) {
#pragma unroll 1
    for (int it = 0; it < SPIN_MAX; it++) {
        if (all(ld_acquire(p) >= target)) break;
        __nanosleep(400);
    }
}
__device__ __forceinline__ float wait_sum(const void* p, float n, int nap = 0) {
    float2 v;
#pragma unroll 1
    for (int it = 0; it < SPIN_MAX; it++) {
        v = ld_relaxed_f2(p);
        if (all(v.y >= n)) break;
        if (all(v.y == 0.f)) __nanosleep(600);
        else if (nap) __nanosleep(nap);
    }
    return v.x;
}
__device__ __forceinline__ void wait_row(int bh, float n) { wait_sum(g_st.lsum[bh], n); }
__device__ __forceinline__ void wait_row_o(int bh, float n) {
    wait_row(bh, n);
    if (bh >= RED0) return;
#pragma unroll 1
    for (int it = 0; it < SPIN_MAX; it++) {
        if (all(__uint_as_float(ld_relaxed_u32(&g_st.oacc[oidx(bh, 0)].w)) == UPB)) break;
        __nanosleep(300);
    }
}
constexpr uint32_t SLOT_K = (uint32_t)(((1ull << 32) + SLOT_TICKS - 1) / SLOT_TICKS);
#define SLOT_ASM(t, n, p, phase, k, open) \
    "mov.u32 " n ", 0;\nSLOT:\nmov.u32 " t ", %%globaltimer_lo;\nadd.u32 " n ", " n ", 1;\nsetp.lt.u32 " p ", " n ", 24;\nshr.u32 " t ", " t ", 5;\n" \
    "mad.lo.u32 " t ", " t ", " k ", " phase ";\nsetp.ge.and.u32 " p ", " t ", " open ", " p ";\n@" p " bra.uni SLOT;\n"
template <int PHASE> __host__ __device__ constexpr uint32_t slot_phase() { return SLOT_K / 2 - PHASE * SLOT_K; }
template <int PHASE> __device__ __forceinline__ void wait_slot() {
    if (PHASE < 0) return;
    asm volatile("{\n.reg .pred p;\n.reg .b32 t, n;\n" SLOT_ASM("t", "n", "p", "%0", "%1", "%2") "}"
                 :: "n"(slot_phase<PHASE>()), "n"(SLOT_K), "n"(SLOT_OPEN * SLOT_K) : "memory");
}
__device__ __forceinline__ void wait_time(uint32_t t) {
#pragma unroll 1
    for (int it = 0; it < SPIN_MAX; it++) {
        uint32_t now;
        asm volatile("mov.u32 %0, %%globaltimer_lo;" : "=r"(now));
        if (all((int)(now - t) >= 0)) break;
    }
}
__device__ __forceinline__ void wait_clock(uint32_t t, Warm& warm) { while (!all((int)(clock() - t) >= 0)) { warm(); } }
__device__ __forceinline__ uint32_t pack_bf16(float lo, float hi) {
    uint32_t r;
    asm("cvt.rn.bf16x2.f32 %0, %1, %2;" : "=r"(r) : "f"(hi), "f"(lo));
    return r;
}
__device__ __forceinline__ float bf16r(float v) { return __uint_as_float(pack_bf16(0.f, v)); }
__device__ __forceinline__ uint32_t nonzero(uint32_t w) { return w ? w : 0x80008000u; }
__device__ __forceinline__ uint32_t pack_neg(float lo, float hi) { return nonzero(pack_bf16(-lo, -hi)); }
__device__ __forceinline__ float lo_f(uint32_t v) { return __uint_as_float(v << 16); }
__device__ __forceinline__ float hi_f(uint32_t v) { return __uint_as_float(v & 0xffff0000u); }
__device__ __forceinline__ float warp_sum(float v) {
#pragma unroll
    for (int o = 16; o; o >>= 1) v += __shfl_xor_sync(0xffffffffu, v, o);
    return v;
}
__device__ __forceinline__ void layernorm20(float (&v)[20]) {
    float s = 0.f;
#pragma unroll
    for (int i = 0; i < 20; i++) s += v[i];
    const float mean = warp_sum(s) * (1.0f / DM);
    float q = 0.f;
#pragma unroll
    for (int i = 0; i < 20; i++) { const float d = v[i] - mean; q += d * d; }
    const float var = bf16r(warp_sum(q) * (1.0f / DM));
    const float m = bf16r(mean);
    const float rden = 1.0f / bf16r(sqrtf(bf16r(var + 1e-5f)));
#pragma unroll
    for (int i = 0; i < 20; i++) v[i] = bf16r(bf16r(v[i] - m) * rden);
}

__device__ __forceinline__ void moments(float m1, float m2, float& nmean, float& rden) {
    m1 *= 1.0f / DM;
    const float var = bf16r(fmaxf(fmaf(-m1, m1, m2 * (1.0f / DM)), 0.f));
    nmean = bf16r(m1);
    rden = rcp_approx(bf16r(sqrt_approx(bf16r(var + 1e-5f))));
}
__device__ __forceinline__ float sel4(int j, float a, float b, float c, float d) {
    float lo, hi, r;
    asm("{\n.reg .pred p;\nsetp.ne.s32 p, %3, 0;\nselp.f32 %0, %2, %1, p;\n}" : "=f"(lo) : "f"(a), "f"(b), "r"(j & 1));
    asm("{\n.reg .pred p;\nsetp.ne.s32 p, %3, 0;\nselp.f32 %0, %2, %1, p;\n}" : "=f"(hi) : "f"(c), "f"(d), "r"(j & 1));
    asm("{\n.reg .pred p;\nsetp.ne.s32 p, %3, 0;\nselp.f32 %0, %2, %1, p;\n}" : "=f"(r) : "f"(lo), "f"(hi), "r"(j & 2));
    return r;
}
template <typename T> __device__ __forceinline__ void pin(T*& p) { asm volatile("" : "+l"(p)); }
__device__ __forceinline__ void pin(uint32_t& v) { asm volatile("" : "+r"(v)); }
__device__ __forceinline__ void pin(float& v) { asm volatile("" : "+f"(v)); }
__device__ __forceinline__ uint32_t after(uint32_t n, float v) {
    asm volatile("{\n.reg .pred p;\nsetp.eq.u32 p, %1, 0x7fc1a5a5;\n@p add.u32 %0, %0, 32;\n}" : "+r"(n) : "r"(__float_as_uint(v)));
    return n;
}
__device__ __forceinline__ float2 lds64f(uint32_t addr) {
    float2 v;
    asm volatile("ld.shared.v2.f32 {%0,%1}, [%2];" : "=f"(v.x), "=f"(v.y) : "r"(addr) : "memory");
    return v;
}
__device__ __forceinline__ void sts32f(uint32_t addr, float v) { asm volatile("st.shared.f32 [%0], %1;" :: "r"(addr), "f"(v) : "memory"); }
template <int ID> __device__ __forceinline__ void fin_arrive() { asm volatile("bar.arrive %0, 288;" :: "n"(ID) : "memory"); }
template <int ID> __device__ __forceinline__ void fin_sync() { asm volatile("bar.sync %0, 288;" :: "n"(ID) : "memory"); }
template <int ID> __device__ __forceinline__ void fin_sync(uint32_t n) { asm volatile("bar.sync %0, %1;" :: "n"(ID), "r"(n) : "memory"); }
__device__ __forceinline__ float2 sum8(uint32_t addr, int pitch) {
    float2 t[8];
#pragma unroll
    for (int w = 0; w < 8; w++) t[w] = lds64f(addr + w * pitch);
    return make_float2(((t[0].x + t[1].x) + (t[2].x + t[3].x)) + ((t[4].x + t[5].x) + (t[6].x + t[7].x)),
                       ((t[0].y + t[1].y) + (t[2].y + t[3].y)) + ((t[4].y + t[5].y) + (t[6].y + t[7].y)));
}
__device__ __forceinline__ float4 sum4x4(uint32_t addr, int pitch) {
    float4 t[4];
#pragma unroll
    for (int w = 0; w < 4; w++)
        asm volatile("ld.shared.v4.f32 {%0,%1,%2,%3}, [%4];" : "=f"(t[w].x), "=f"(t[w].y), "=f"(t[w].z), "=f"(t[w].w) : "r"(addr + w * pitch) : "memory");
    return make_float4((t[0].x + t[1].x) + (t[2].x + t[3].x), (t[0].y + t[1].y) + (t[2].y + t[3].y),
                       (t[0].z + t[1].z) + (t[2].z + t[3].z), (t[0].w + t[1].w) + (t[2].w + t[3].w));
}
__device__ __forceinline__ void sts64f(uint32_t addr, float x, float y) {
    asm volatile("st.shared.v2.f32 [%0], {%1,%2};" :: "r"(addr), "f"(x), "f"(y) : "memory");
}
__device__ __forceinline__ uint4 lds128(uint32_t addr) {
    uint4 v;
    asm volatile("ld.shared.v4.u32 {%0,%1,%2,%3}, [%4];" : "=r"(v.x), "=r"(v.y), "=r"(v.z), "=r"(v.w) : "r"(addr) : "memory");
    return v;
}
__device__ __forceinline__ void ld_relaxed_v4_if(uint4& v, const void* p, bool pred) {
    asm volatile("{\n.reg .pred p;\nsetp.ne.u32 p, %5, 0;\n@p ld.relaxed.gpu.global.v4.u32 {%0,%1,%2,%3}, [%4];\n}"
                 : "+r"(v.x), "+r"(v.y), "+r"(v.z), "+r"(v.w) : "l"(p), "r"((uint32_t)pred) : "memory");
}
__device__ __forceinline__ void sts128f(uint32_t addr, float x, float y, float z, float w) {
    asm volatile("st.shared.v4.f32 [%0], {%1,%2,%3,%4};" :: "r"(addr), "f"(x), "f"(y), "f"(z), "f"(w) : "memory");
}
template <int NJ>
__device__ __forceinline__ void load_o(uint32_t (&ob)[3 * NJ][2], int bh, int J0, int j) {
    float4 v[NJ][4];
    float2 l;
#pragma unroll 1
    for (int it = 0; it < SPIN_MAX; it++) {
#pragma unroll
        for (int J = 0; J < NJ; J++) {
#pragma unroll
            for (int e = 0; e < 4; e++) v[J][e] = ld_relaxed_f4(&g_st.oacc[oidx(bh, j)] + oidx(0, (J0 + J) * 16 + e * 4));
        }
        l = ld_relaxed_f2(g_st.lsum[bh]);
        bool ok = l.y == UPB;
#pragma unroll
        for (int J = 0; J < NJ; J++) {
#pragma unroll
            for (int e = 0; e < 4; e++) ok &= v[J][e].w == UPB;
        }
        if (all(ok)) break;
    }
    const float rl = __fdividef(1.0f, l.x);
#pragma unroll
    for (int J = 0; J < NJ; J++) {
        ob[3 * J][0] = pack_bf16(v[J][0].x * rl, v[J][1].x * rl);     ob[3 * J][1] = pack_bf16(v[J][2].x * rl, v[J][3].x * rl);
        ob[3 * J + 1][0] = pack_bf16(v[J][0].y * rl, v[J][1].y * rl); ob[3 * J + 1][1] = pack_bf16(v[J][2].y * rl, v[J][3].y * rl);
        ob[3 * J + 2][0] = pack_bf16(v[J][0].z * rl, v[J][1].z * rl); ob[3 * J + 2][1] = pack_bf16(v[J][2].z * rl, v[J][3].z * rl);
    }
}
__device__ __forceinline__ int near_side(uint32_t sb) {
    uint32_t v;
    asm volatile("ld.volatile.shared.u32 %0, [%1];" : "=r"(v) : "r"(sb + SM_SIDE) : "memory");
    return v;
}
__device__ __forceinline__ void poll_row(uint4& a, uint4& b, uint2& c, const void* pa, const void* pb, const void* pc, uint32_t sa, uint32_t sc,
                                         bool arrive, bool nap, uint32_t bar, Warm& warm) {
    asm volatile("{\n.reg .pred p, q, r, s;\n.reg .b32 m, n, it;\n"
                 "setp.ne.u32 r, %19, 0;\nsetp.ne.u32 s, %20, 0;\nmov.u32 it, 0;\n"
                 "POLL:\n"
                 SLOT_ASM("m", "n", "p", "%23", "%24", "%25")
                 "ld.relaxed.gpu.global.v4.u32 {%0,%1,%2,%3}, [%14];\n"
                 "ld.relaxed.gpu.global.v4.u32 {%4,%5,%6,%7}, [%15];\n"
                 "ld.relaxed.gpu.global.v2.u32 {%8,%9}, [%16];\n"
                 "add.u32 it, it, 1;\nsetp.ge.u32 q, it, %21;\n"
                 "mov.u32 m, 0;\nmma.sync.aligned.m16n8k8.row.col.f32.bf16.bf16.f32 {%10,%11,%12,%13}, {m,m}, {m}, {%10,%11,%12,%13};\n"
                 "st.shared.v4.u32 [%17], {%0,%1,%2,%3};\n"
                 "st.shared.v4.u32 [%17+512], {%4,%5,%6,%7};\n"
                 "st.shared.v2.u32 [%18], {%8,%9};\n"
                 "min.u32 m, %0, %1;\nmin.u32 m, m, %2;\nmin.u32 n, %3, %4;\nmin.u32 n, n, %5;\nmin.u32 m, m, %6;\nmin.u32 m, m, %7;\n"
                 "min.u32 n, n, m;\nmin.u32 m, %8, %9;\nmin.u32 m, m, n;\n"
                 "setp.ne.or.u32 p, m, 0, q;\n"
                 "vote.sync.all.pred p, p, 0xffffffff;\n"
                 "and.pred q, p, r;\n"
                 "bar.warp.sync 0xffffffff;\n"
                 "@q mbarrier.arrive.shared::cta.b64 _, [%22];\n"
                 "@p bra.uni DONE;\n"
                 "@s nanosleep.u32 500;\n"
                 "bra.uni POLL;\n"
                 "DONE:\n}"
                 : "=&r"(a.x), "=&r"(a.y), "=&r"(a.z), "=&r"(a.w), "=&r"(b.x), "=&r"(b.y), "=&r"(b.z), "=&r"(b.w), "=&r"(c.x), "=&r"(c.y),
                   "+f"(warm.c[0]), "+f"(warm.c[1]), "+f"(warm.c[2]), "+f"(warm.c[3])
                 : "l"(pa), "l"(pb), "l"(pc), "r"(sa), "r"(sc), "r"((uint32_t)arrive), "r"((uint32_t)nap), "n"(SPIN_MAX), "r"(bar),
                   "n"(slot_phase<PH_H>()), "n"(SLOT_K), "n"(SLOT_OPEN * SLOT_K) : "memory");
}
__device__ __forceinline__ void aux_sync() { asm volatile("bar.sync 1, 256;" ::: "memory"); }

__global__ void __launch_bounds__(NTHREADS, 1)
fused_decode_kernel(const __grid_constant__ Params p) {
    extern __shared__ __align__(1024) unsigned char smem[];
    const uint32_t sb = s2u(smem);
    const int tid = threadIdx.x, cta = blockIdx.x;
    if (tid < 32 && cta < NQ_CTAS) {
        asm volatile("{\n.reg .pred p;\nelect.sync _|p, 0xffffffff;\n"
                     "@p mbarrier.init.shared::cta.b64 [%2], 1;\n"
                     "@p fence.mbarrier_init.release.cluster;\n"
                     "@p mbarrier.arrive.expect_tx.shared::cta.b64 _, [%2], 15360;\n"
                     "@p cp.async.bulk.tensor.2d.shared::cluster.global.mbarrier::complete_tx::bytes [%0], [%1, {%3, %4}], [%2];\n"
                     "@p mbarrier.init.shared::cta.b64 [%2+8], 1;\n@p mbarrier.init.shared::cta.b64 [%2+16], 1;\n"
                     "@p mbarrier.init.shared::cta.b64 [%2+24], 1;\n"
                     "@p fence.mbarrier_init.release.cluster;\n"
                     "@p mbarrier.arrive.expect_tx.shared::cta.b64 _, [%2+8], 15360;\n"
                     "@p cp.async.bulk.tensor.2d.shared::cluster.global.mbarrier::complete_tx::bytes [%0+15360], [%1, {%3, %5}], [%2+8];\n"
                     "@p mbarrier.arrive.expect_tx.shared::cta.b64 _, [%2+16], 15360;\n"
                     "@p cp.async.bulk.tensor.2d.shared::cluster.global.mbarrier::complete_tx::bytes [%0+30720], [%1, {%3, %6}], [%2+16];\n"
                     "@p mbarrier.arrive.expect_tx.shared::cta.b64 _, [%2+24], 15360;\n"
                     "@p cp.async.bulk.tensor.2d.shared::cluster.global.mbarrier::complete_tx::bytes [%0+46080], [%1, {%3, %7}], [%2+24];\n}"
                     :: "r"(sb + SM_W), "l"(&p.wq), "r"(sb + BAR_WQ), "r"(cta * 48), "r"(0), "r"(160), "r"(320), "r"(480) : "memory");
    }
    const int warp = __shfl_sync(0xffffffffu, tid >> 5, 0), lane = tid & 31;
    constexpr int grid = NCTAS;
    const int g = lane >> 2, j = lane & 3;
    uint32_t t_start;
    asm volatile("mov.u32 %0, %%globaltimer_lo;" : "=r"(t_start));
    TS(0);
    if (tid == 32) {
        mbar_init(sb + BAR_WO, 1);
        mbar_init(sb + BAR_H, 1);
#pragma unroll
        for (int i = 0; i < 8 + NWORK; i++) mbar_init(sb + BAR_FW + i * 8, 1);
        sts32f(sb + SM_SIDE, 0.f);
        asm volatile("fence.mbarrier_init.release.cluster;" ::: "memory");
        asm volatile("fence.proxy.async.shared::cta;" ::: "memory");
    }
    __syncthreads();
    if (warp >= NAUX + NWORK) {
        const int fw = warp - (NAUX + NWORK), fi = ffn_slice(cta);
        if (fw == 0) {
            if (cta < NQ_CTAS) {
#pragma unroll
                for (int i = lane; i < STATE_V4; i += 32)
                    if (cta * STATE_V4 + i < (int)(sizeof(State) / 16)) reinterpret_cast<uint4*>(&g_st)[cta * STATE_V4 + i] = make_uint4(0u, 0u, 0u, 0u);
                __syncwarp();
                if (lane == 0) red_release(g_cnt_z);
            }
            TSW(2); wait_count(g_cnt_z, NQ_CTAS); TSW(29);
            asm volatile("bar.arrive 2, %0;" :: "n"((NWORK + 2) * 32) : "memory");
            fin_arrive<3>();
        } else {
#pragma unroll 1
            for (int n = cta < NE_CTAS ? 5 : 4, i = n - 1; i >= 0; i--) {
                const int head = cta < NE_CTAS ? cta >> 2 : 28 + i;
                wait_time(t_start + WO_AT_NS + (NH - 1 - head) * WO_STEP_NS);
                request_box(sb + SM_A + i * 12288, &p.wo, cta < NE_CTAS ? (cta & 3) * 160 + i * 32 : (cta - NE_CTAS) * 32,
                            head * DH, sb + BAR_WO, i == n - 1 ? n * 12288 : 0);
            }
            asm volatile("bar.sync 2, %0;" :: "n"((NWORK + 2) * 32) : "memory");
            uint32_t best[2] = {~0u, ~0u};
#pragma unroll 1
            for (int i = 0; i < NPROBE; i++) {
#pragma unroll
                for (int c = 0; c < 2; c++) {
                    uint32_t t0 = clock(), t1 = t0;
                    int v = 0;
                    draw(v, &g_st.hx.w[c][PROBE], lane == 0);
                    asm volatile("{\n.reg .pred p;\nsetp.ne.u32 p, %1, 0xffffffff;\n@p mov.u32 %0, %%clock;\n}" : "+r"(t1) : "r"(v) : "memory");
                    best[c] = min(best[c], t1 - t0);
                }
                __nanosleep(1000);
            }
            if (lane == 0) sts32f(sb + SM_SIDE, __uint_as_float(best[1] < best[0]));
        }
        int job = cta;
        auto sum_rows = [&](int row_end) {
#pragma unroll 1
            for (; job < 8 * min(row_end, RED0); job += NCTAS) {
                const int row = job >> 3, grp = (job & 7) * 8 + (lane & 7);
                wait_row(row, UPB);
                const float4* src = &g_ring[row % RING][lane >> 3][grp];
                float sx = 0.f, sy = 0.f, sz = 0.f;
#pragma unroll 1
                for (int i = 0; i < 2; i++, src += 64 * 64) {
                    float4 v[16];
#pragma unroll 1
                    for (int it = 0; it < SPIN_MAX; it++) {
                        bool ok = true;
#pragma unroll
                        for (int k = 0; k < 16; k++) v[k] = ld_relaxed_b128(src + k * 4 * 64);
#pragma unroll
                        for (int k = 0; k < 16; k++) ok &= v[k].w == (float)(row + 1);
                        if (all(ok)) break;
                    }
#pragma unroll
                    for (int k = 0; k < 16; k++) { sx += v[k].x; sy += v[k].y; sz += v[k].z; }
                }
#pragma unroll
                for (int o = 8; o < 32; o <<= 1) {
                    sx += __shfl_xor_sync(0xffffffffu, sx, o); sy += __shfl_xor_sync(0xffffffffu, sy, o); sz += __shfl_xor_sync(0xffffffffu, sz, o);
                }
                if (lane < 8) st_relaxed_b128(&g_st.oacc[oidx(row, grp)], sx, sy, sz, UPB);
            }
        };
        const int ho0 = lane / 20 * 256 + lane % 20 * 4, ho1 = (lane + 32) / 20 * 256 + (lane + 32) % 20 * 4, ho2 = 3 * 256 + 16 + 2 * lane;
        uint32_t wr[10] = {};
        float wsum = 0.f;
        if (is_g(cta) && fw == 0) {
#pragma unroll
            for (int i = 0; i < 10; i++) {
                const int w = 4 * lane + 128 * (i >> 2) + (i & 3) - (i >= 8 ? 2 * lane : 0);
                wr[i] = *reinterpret_cast<const uint32_t*>(p.wr + (w >> 4) * 32 + (w & 3) * 8 + ((w >> 1) & 6));
                wsum += lo_f(wr[i]) + hi_f(wr[i]);
            }
            wsum = warp_sum(wsum);
        }
        const int fb = lane >> 3, fg = lane & 7;
        if (fw == 0) {
#pragma unroll
            for (int i = lane; i < DM / 2; i += 32) sts32f(sb + SM_X + 4 * HPITCH + i * 4, __uint_as_float(0x3f803f80u));
        }
        Warm warm;
        float nmean = 0.f, rden = 0.f, sig = 0.f;
#pragma unroll 1
        for (int b = 0; b < NB; b++) {
            const bool ffn = b >= NB - 2;
            if (fw == 0) {
                sum_rows((b + 1) * NH);
                if (ffn) asm volatile("bar.arrive 8, 64;" ::: "memory");
            } else if (ffn) {
                asm volatile("bar.sync 8, 64;" ::: "memory");
                if (b == NB - 1 && (is_f(cta) || is_g(cta) || ALL_LOADERS)) {
                    uint32_t t0 = 0;
#pragma unroll 1
                    for (int it = 0; it < SPIN_MAX; it++) {
                        t0 = ld_relaxed_u32(g_st.fw_time);
                        if (all(t0 != 0)) break;
                        __nanosleep(150);
                    }
                    asm volatile("fence.proxy.async.shared::cta;" ::: "memory");
                    wait_time(t0 + FW_AT_NS);
                    TSW(9);
                    uint32_t t = clock() + (is_f(cta) ? ((fi & 1) * 24 + (fi >> 1)) * FW_GAP / 48 : FW_MID + ((fi & 3) * 10 + (fi >> 2)) * FW_GAP2 / 40);
#pragma unroll 1
                    for (int i = 0; i < 8; i++) {
                        const uint32_t bar = sb + BAR_FW + i * 8;
                        if (is_f(cta)) {
                            wait_clock(t, warm);
                            request_box(sb + SM_W + i * 10240, (i & 1) ? &p.wu : &p.wg, fi * 32, (i >> 1) * 160, bar, 10240);
                            t += FW_GAP;
                        } else if (is_g(cta)) {
                            wait_clock(t, warm);
                            asm volatile("{\n.reg .pred p;\nelect.sync _|p, 0xffffffff;\n"
                                         "@p mbarrier.arrive.expect_tx.shared::cta.b64 _, [%2], 6144;\n"
                                         "@p cp.async.bulk.tensor.4d.shared::cluster.global.mbarrier::complete_tx::bytes [%0], [%1, {%3, %4, %4, %5}], [%2];\n}"
                                         :: "r"(sb + SM_W + i * 6144), "l"(&p.wd), "r"(bar), "r"(fi * 16), "r"(0), "r"(i * 12) : "memory");
                            t += FW_GAP2;
                        }
                    }
                }
                if (is_f(cta)) {
                    const uint32_t* src = &g_st.hx.w[near_side(sb)][min(fb, b) * 256 + 96];
                    float4 m;
#pragma unroll 1
                    for (int it = 0; it < SPIN_MAX; it++) {
                        wait_slot<PH_M>();
                        m = ld_relaxed_f4(src);
                        warm();
                        if (all(m.y + m.w == 2 * (NCTAS - NE_CTAS))) break;
                        if (b < NB - 1) __nanosleep(500);
                    }
                    moments(m.x, m.z, m.x, m.z);
                    sts64f(sb + SM_RED + 5120 + fb * 8, m.x, m.z);
                }
            }
            if (fw == 0 && cta >= NE_CTAS) {
                const int lc = cta - NE_CTAS, col = lc * 32 + 2 * (lane & 15);
                const uint32_t xv = *reinterpret_cast<const uint32_t*>(p.x + b * DM + col);
                uint32_t* dst = &(ffn ? g_st.hx.w : g_st.lx.w + 2)[lane >> 4][(b & 1) * 128 + lc / 5 * 256 + lc % 5 * 16 + (col & 6) * 2 + ((col >> 3) & 3)];
                uint32_t part = sb + SM_RED + (lane & 15) * 8;
                wait_row(b * NH + 28, 1);
                float4 early;
#pragma unroll 1
                for (int it = 0; it < SPIN_MAX; it++) {
                    early = ld_relaxed_f4(&g_st.attn[b][col]);
                    if (all(early.y == NE_CTAS / 4 && early.w == NE_CTAS / 4)) break;
                }
                if (early.x != 1.2345f && lane == 0) TS2(6);
                CK(1, __float_as_uint(early.x));
                const float x0 = -(lo_f(xv) + early.x), x1 = -(hi_f(xv) + early.z);
                fin_sync<4>(after(after(288, x0), x1));
                CK(2, lds32(sb + SM_RED));
                const float2 late = sum8(part, 128);
                const uint32_t hv = nonzero(pack_bf16(x0 - late.x, x1 - late.y));
                st_relaxed(dst, hv);
                if (ffn) st_relaxed(dst + 2048, hv);
                CK(3, 0);
                float m = lane < 16 ? lo_f(hv) + hi_f(hv) : fmaf(lo_f(hv), lo_f(hv), hi_f(hv) * hi_f(hv));
#pragma unroll
                for (int o = 1; o < 16; o <<= 1) m += __shfl_xor_sync(0xffffffffu, m, o);
                if ((lane & 14) == 0) red_f2(reinterpret_cast<float*>(&g_st.hx.w[lane & 1][b * 256 + 96 + (lane >> 4) * 2]), m, 1.f);
                fin_arrive<5>();
            }
            if (fw == 0 && (is_g(cta) || is_f(cta))) {
                const uint32_t* src = &(ffn ? g_st.hx.w : g_st.lx.w + 2)[near_side(sb) ^ (ffn && is_g(cta) ? 3 : 0)][(b & 1) * 128];
                const uint32_t hrow = sb + SM_X + b * HPITCH;
                wait_sum(b == NB - 1 ? (const void*)&g_st.lx.w[near_side(sb) ^ 1][3 * 256] : g_st.lsum[b * NH + NH - 1], UPB, 100);
                wait_clock(clock() + HGATE_NS * 2, warm);
                uint4 h0, h1;
                uint2 h2;
                poll_row(h0, h1, h2, src + ho0, src + ho1, src + ho2, hrow + lane * 16, hrow + 1024 + lane * 8, ffn && lane == 0, b < NB - 1, sb + BAR_H, warm);
                CK(4, h0.x);
                if (is_g(cta)) {
                    const uint32_t hw[10] = {h0.x, h0.y, h0.z, h0.w, h1.x, h1.y, h1.z, h1.w, h2.x, h2.y};
                    float m1 = 0.f, m2 = 0.f, rr = 0.f;
#pragma unroll
                    for (int i = 0; i < 10; i++) {
                        const float v0 = lo_f(hw[i]), v1 = hi_f(hw[i]);
                        m1 += v0 + v1;
                        m2 = fmaf(v0, v0, fmaf(v1, v1, m2));
                        rr = fmaf(v0, lo_f(wr[i]), fmaf(v1, hi_f(wr[i]), rr));
                    }
                    moments(warp_sum(m1), warp_sum(m2), m1, m2);
                    const float sg = bf16r(sigmoid_approx(bf16r((m1 * wsum - warp_sum(rr)) * m2)));
                    if (fb == b) { nmean = m1; rden = m2; sig = sg; }
                    __syncwarp();
                    if (ffn) {
                        const int yj = 2 * (fb & 1) + (fb >> 1);
                        uint32_t ypart = sb + SM_RED2 + yj * 128 + ((fg + 2 * yj) & 7) * 16;
                        __nv_bfloat16* out = p.out + fb * DM + fi * 16 + fg;
                        const float2 hw2 = lds64f(sb + SM_X + fb * HPITCH + ((fi >> 1) * 16 + (fg & 6) * 2 + (fi & 1) * 2) * 4);
                        const uint32_t w0 = __float_as_uint(hw2.x), w1 = __float_as_uint(hw2.y);
                        const float nh0 = (fg & 1) ? hi_f(w0) : lo_f(w0), nh1 = (fg & 1) ? hi_f(w1) : lo_f(w1);
                        const float ln0 = bf16r(bf16r(nmean - nh0) * rden) - nh0, ln1 = bf16r(bf16r(nmean - nh1) * rden) - nh1;
                        pin(ypart); pin(out);
                        fin_sync<6>(after(after(after(288, sig), ln0), ln1));
                        CK(10, lds32(ypart));
                        const float4 ya = sum4x4(ypart, 512), yb = sum4x4(ypart + 2048, 512);
                        const float4 y = make_float4(ya.x + yb.x, ya.y + yb.y, ya.z + yb.z, ya.w + yb.w);
                        const float y0 = -(((fb & 1) ? y.y : y.x) + __shfl_xor_sync(0xffffffffu, (fb & 1) ? y.x : y.y, 8));
                        const float y1 = -(((fb & 1) ? y.w : y.z) + __shfl_xor_sync(0xffffffffu, (fb & 1) ? y.z : y.w, 8));
                        const uint32_t ov = pack_bf16(fmaf(y0, sig, ln0), fmaf(y1, sig, ln1));
                        asm volatile("{\n.reg .pred p;\n.reg .b16 lo, hi;\nsetp.ne.u32 p, %2, 0;\nmov.b32 {lo, hi}, %1;\n"
                                     "@p st.global.u16 [%0], lo;\n@p st.global.u16 [%0+16], hi;\n"
                                     "@p exit;\n"
                                     "}" :: "l"(out), "r"(ov), "r"((uint32_t)(b == NB - 1)) : "memory");
                        CK(11, 0);
                        if (lane == 0) TS2(13);
                    }
                }
            }
            if (is_f(cta) && ffn) {
                const int ks = (2 * fi + fw) % 12;
                const int far = near_side(sb) ^ 1;
                uint32_t* dst = &g_st.ax[ks >> 2].w[(~b & 1) * 2 + far][(fi / 6) * 128 + (ks & 3) * 32 + fb * 8 + (fg & 1) * 4 + ((fg >> 1) ^ (ks & 1))];
                uint32_t* dst2 = dst + (far ? -1024 : 1024);
                uint32_t part = sb + SM_RED + fw * 2560 + fb * 128 + ((fg + (fb & 2)) & 7) * 16;
                uint32_t psum = sb + SM_RED + fw * 2560 + 4 * 128 + ((fg + 4) & 7) * 16;
                pin(dst); pin(part); pin(psum);
                asm volatile("bar.sync 4, 320;" ::: "memory");
                CK(6, lds32(part));
                const float4 d = sum4x4(part, 640), cs = sum4x4(psum, 640);
                const float2 mo = lds64f(sb + SM_RED + 5120 + fb * 8);
                nmean = mo.x; rden = mo.y;
                const float g0 = fmaf(nmean, cs.x, -d.x), g1 = fmaf(nmean, cs.y, -d.y), ke = rden * -1.4426950408889634f, r2 = rden * rden;
                const float p0 = g0 * fmaf(-nmean, cs.z, d.z) * r2, p1 = g1 * fmaf(-nmean, cs.w, d.w) * r2;
                const uint32_t av = nonzero(pack_bf16(p0 * rcp_approx(1.0f + ex2_approx(g0 * ke)), p1 * rcp_approx(1.0f + ex2_approx(g1 * ke))));
                st_relaxed(dst, av);
                st_relaxed(dst2, av);
                CK(7, 0);
            }
        }
        warm.done(sb + SM_SCRAP);
        if (cta == 0 && tid == (NAUX + NWORK) * 32) { g_work[0] = 0; g_work[32] = 0; g_cnt_z[0] = 0; }
        return;
    }
    if (warp >= NAUX) {
        const int wk = warp - NAUX;
        const uint32_t bar = sb + BAR_KV + wk * 8;
        const uint32_t buf = sb + SM_KV + wk * TILE_BYTES;
        uint64_t pol;
        asm volatile("createpolicy.fractional.L2::evict_first.b64 %0, 1.0;" : "=l"(pol));
        const int nstatic = NWORK * grid;
        constexpr int POOL0 = NUNITS - NPOOL;
        int uk = wk * grid + cta;
        wait_time(t_start + K0_AT_NS + uk * KSWEEP_NS / nstatic);
        request_tile(buf, &p.k, uk, bar, pol);
        uint32_t koff[3], voff[3];
        {
            const int r = lane & 7, hf = (lane >> 3) & 1;
            const int kkey = hf ? 8 + (r ^ 1) : r;
            const int vh = lane >> 4;
            const int vkey = ((r & 1) ? 8 : 0) + (vh ? (r ^ 1) : r);
#pragma unroll
            for (int b = 0; b < 3; b++) {
                const int rk = 3 * kkey + b, rv = 3 * vkey + b;
                koff[b] = buf + rk * 128 + (((lane >> 4) ^ (rk & 7)) << 4);
                voff[b] = buf + rv * 128 + ((hf ^ (rv & 7)) << 4);
            }
        }
        uint32_t phase = 0;
        uint32_t qf[12][2];
        auto load_q = [&](int u) {
            const uint32_t* q = g_early[u / UPB].q[0][j];
#pragma unroll
            for (int i = 0; i < 4; i++) {
                const uint4 a = ld_relaxed_v4(q + i * 32);
                const float2 c = ld_relaxed_f2(q + i * 32 + 4);
                qf[3 * i][0] = a.x; qf[3 * i][1] = a.y; qf[3 * i + 1][0] = a.z; qf[3 * i + 1][1] = a.w;
                qf[3 * i + 2][0] = __float_as_uint(c.x); qf[3 * i + 2][1] = __float_as_uint(c.y);
            }
        };
        load_q(uk);
        int uq[LAG];
        uint32_t sq[LAG];
#pragma unroll
        for (int i = 0; i < LAG; i++) { uq[i] = -1; sq[i] = 0; }
        uint4 mv = make_uint4(0u, 0u, 0u, 0u);
        float freed = UPB;
        while (true) {
            const int uv = uq[0];
            uint32_t sv = sq[0];
#pragma unroll
            for (int i = 0; i + 1 < LAG; i++) { uq[i] = uq[i + 1]; sq[i] = sq[i + 1]; }
            uq[LAG - 1] = uk;
            if (uk < NUNITS) {
                PH(7);
#pragma unroll 1
                for (int it = 0; it < SPIN_MAX; it++) {
                    uint32_t lo = 0xffffffffu;
#pragma unroll
                    for (int i = 0; i < 12; i++) lo = min(lo, min(qf[i][0], qf[i][1]));
                    if (all(lo != 0)) break;
                    __nanosleep(250);
                    load_q(uk);
                }
                mbar_wait(bar, phase); phase ^= 1;
                PH(0); ARR();
                TSI(0, 16); TSI(1, 18);
                float acc[2][4][4] = {};
#pragma unroll
                for (int ks = 0; ks < 12; ks++) {
#pragma unroll
                    for (int mt = 0; mt < 4; mt++) {
                        uint32_t a[4];
                        ldsm4(a, (koff[ks >> 2] ^ ((ks & 3) << 5)) + mt * 6144);
                        mma16816(acc[ks & 1][mt], a, qf[ks][0], qf[ks][1]);
                    }
                }
                PH(1);
                TSI(0, 17); TSI(1, 19);
                if (uk < nstatic) wait_time(t_start + K1_AT_NS + uk * KSWEEP_NS / nstatic);
                if (uv < NUNITS) request_tile(buf, uv >= 0 ? &p.v : &p.k, uv >= 0 ? uv : uk + nstatic, bar, pol);
                const float sa = sel4(j, acc[0][0][0], acc[0][1][0], acc[0][2][0], acc[0][3][0]) + sel4(j, acc[1][0][0], acc[1][1][0], acc[1][2][0], acc[1][3][0]);
                const float sc = sel4(j, acc[0][0][2], acc[0][1][2], acc[0][2][2], acc[0][3][2]) + sel4(j, acc[1][0][2], acc[1][1][2], acc[1][2][2], acc[1][3][2]);
                const uint32_t raw = pack_bf16(sa, sc);
                const float scale = -0.07216878364870322f;
                const uint32_t sk = pack_bf16(lo_f(raw) * scale, hi_f(raw) * scale);
                sq[LAG - 1] = sk;
                if (uk >= POOL0) st_relaxed(&g_st.score[uk - POOL0][lane], sk ? sk : 0x80008000u);
                int a = (int)(sk << 16), b = (int)(sk & 0xffff0000u);
                a ^= (a >> 31) & 0x7fff0000; b ^= (b >> 31) & 0x7fff0000;
                const int mx = __reduce_max_sync(0xffffffffu, max(a, b));
                if (lane == 0) st_relaxed(&g_early[uk / UPB].umax[uk % UPB], (uint32_t)mx | 1u);
            }
            if (uv < 0) {
                uk += nstatic;
                load_q(uk);
                continue;
            }
            if (uv >= NUNITS) break;
            const int bh = uv / UPB;
#pragma unroll 1
            for (int it = 0; it < SPIN_MAX; it++) {
                if (all((mv.x & mv.y & mv.z & mv.w & 1u) && (uv < POOL0 || sv != 0) && freed == UPB)) break;
                mv = ld_relaxed_v4(&g_early[bh].umax[lane * 4]);
                if (bh >= RING && bh < RED0) freed = __uint_as_float(ld_relaxed_u32(&g_st.oacc[oidx(bh - RING, (lane & 7) * 8)].w));
                if (uv >= POOL0) sv = ld_relaxed_u32(&g_st.score[uv - POOL0][lane]);
            }
            PH(2); CK(8, sv);
            int un = NUNITS, vn = 0;
            draw(un, g_work, uk < NUNITS && lane == 0);
            uint32_t tdraw;
            asm volatile("mov.u32 %0, %%globaltimer_lo;" : "=r"(tdraw));
            draw(vn, g_work + 32, uq[0] >= POOL0 && lane == 0);
            int mx = __reduce_max_sync(0xffffffffu, max(max((int)mv.x, (int)mv.y), max((int)mv.z, (int)mv.w))) & 0xffff0000;
            mx ^= (mx >> 31) & 0x7fff0000;
            const float m = __int_as_float(mx);
            const float l2e = 1.4426950408889634f;
            const uint32_t pp = pack_bf16(exp2f((lo_f(sv) - m) * l2e), exp2f((hi_f(sv) - m) * l2e));
            uint32_t pb[8];
#pragma unroll
            for (int t = 0; t < 4; t++) {
                pb[2 * t] = __shfl_sync(0xffffffffu, pp, 8 * j + t);
                pb[2 * t + 1] = __shfl_sync(0xffffffffu, pp, 8 * j + 4 + t);
            }
            float lacc[4] = {};
            const uint32_t ones[4] = {0x3f803f80u, 0x3f803f80u, 0x3f803f80u, 0x3f803f80u};
#pragma unroll
            for (int t = 0; t < 4; t++) mma16816(lacc, ones, pb[2 * t], pb[2 * t + 1]);
            if (uv < nstatic) {
                asm volatile("bar.sync 2, %0;" :: "n"((NWORK + 2) * 32) : "memory");
                TSW(3);
            }
            const int grp = 16 * j + 4 * (g & 1) + (g >> 1);
            uint32_t mode = (bh >= RED0) + (bh >= NBH - 4);
            float tag = mode ? 1.f : (float)(bh + 1), tag2 = fmaf(__uint_as_float(voff[0]), 0.f, tag);
            void* dst = mode == 0 ? (void*)&g_ring[bh % RING][uv % UPB][grp] :
                        mode == 1 ? (void*)&g_st.oacc[oidx(bh, grp)] : (void*)&g_st.ox[0].w[uv % OREP * 2 + (~(near_side(sb) ^ uv % OREP) & 1)][oidx(bh & 3, grp) * 4];
            if (mode == 2 && lane < 2) red_f2(reinterpret_cast<float*>(&g_st.lx.w[lane][(bh & 3) * 256]), lacc[0], 1.f);
            CK(10, __float_as_uint(lacc[0]));
            un = __shfl_sync(0xffffffffu, un, 0) + (LAG + 1) * nstatic;
            un = unit_of(un);
            vn = __shfl_sync(0xffffffffu, vn, 0);
            if (uq[0] >= POOL0) uq[0] = unit_of(POOL0 + vn);
            if (vn == FW_TICKET && lane == 0) st_relaxed(g_st.fw_time, tdraw | 1u);
            if (uq[0] < NUNITS && un >= NUNITS) {
                mv = ld_relaxed_v4(&g_early[uq[0] / UPB].umax[lane * 4]);
                if (uq[0] < RED0 * UPB) freed = 0.f;
                if (uq[0] >= POOL0) sq[0] = ld_relaxed_u32(&g_st.score[uq[0] - POOL0][lane]);
            }
            pin(dst); pin(mode); pin(tag); pin(tag2); pin(voff[0]); pin(voff[1]); pin(voff[2]);
            PH(3); CK(9, vn);
            mbar_wait(bar, phase); phase ^= 1;
            PH(4); ARR(); CK(12, lds32(buf));
            float acc[12][4] = {};
#pragma unroll
            for (int t = 0; t < 4; t++) {
#pragma unroll
                for (int mt = 0; mt < 12; mt++) {
                    uint32_t a[4];
                    ldsm4t(a, (voff[mt >> 2] ^ ((mt & 3) << 5)) + t * 6144);
                    mma16816(acc[mt], a, pb[2 * t], pb[2 * t + 1]);
                }
            }
            PH(5);
            if (lane == 0) PROG(un);
            if (un < NUNITS || uq[0] < NUNITS) request_tile(buf, un < NUNITS ? &p.k : &p.v, un < NUNITS ? un : uq[0], bar, pol);
            if (un < NUNITS || uq[0] < NUNITS) CK(11, 0);
            float o[6];
#pragma unroll
            for (int e = 0; e < 6; e++) {
                const int q = e % 3, c = (e / 3) * 2;
                o[e] = sel4(j, acc[q][c], acc[3 + q][c], acc[6 + q][c], acc[9 + q][c]);
            }
            put_groups(dst, mode, o, tag, tag2);
            CK(13, 0);
            if (un < NUNITS) load_q(un);
            if (lane == 0) red_f2(&g_st.lsum[bh][0].x, lacc[0], 1.f);
            PH(6);
            if (uq[0] >= NUNITS && un >= NUNITS) break;
            uk = un;
            if (uq[0] < NUNITS && un < NUNITS) {
                const int nb = uq[0] / UPB;
                mv = ld_relaxed_v4(&g_early[nb].umax[lane * 4]);
                freed = nb >= RING && nb < RED0 ? __uint_as_float(ld_relaxed_u32(&g_st.oacc[oidx(nb - RING, (lane & 7) * 8)].w)) : UPB;
                if (uq[0] >= POOL0) sq[0] = ld_relaxed_u32(&g_st.score[uq[0] - POOL0][lane]);
            }
        }
        TSW(4 + wk);
        return;
    }

    __nv_bfloat16* xs = reinterpret_cast<__nv_bfloat16*>(smem + SM_X);
    float* red = reinterpret_cast<float*>(smem + SM_RED);
    const int frow = (lane & 7) + ((lane >> 4) << 3), fcol = (lane >> 3) & 1;
    const uint32_t f64b = sb + (frow * 4 + (fcol ^ ((frow >> 1) & 3))) * 16;
    if (cta < NQ_CTAS) {
        TS(26);
        if (warp >= 4) {
            uint2 xr[5];
#pragma unroll
            for (int i = 0; i < 5; i++) xr[i] = *reinterpret_cast<const uint2*>(p.x + (warp - 4) * DM + i * 128 + lane * 4);
            float v[20];
#pragma unroll
            for (int i = 0; i < 5; i++) {
                v[4 * i] = lo_f(xr[i].x); v[4 * i + 1] = hi_f(xr[i].x); v[4 * i + 2] = lo_f(xr[i].y); v[4 * i + 3] = hi_f(xr[i].y);
            }
            layernorm20(v);
#pragma unroll
            for (int i = 0; i < 5; i++)
                *reinterpret_cast<uint2*>(xs + (warp - 4) * XPITCH + i * 128 + lane * 4) =
                    make_uint2(pack_bf16(v[4 * i], v[4 * i + 1]), pack_bf16(v[4 * i + 2], v[4 * i + 3]));
        }
        aux_sync();
        TS(27);
        mbar_wait(sb + BAR_WQ + (warp >> 1) * 8, 0);
        TS(1);
        const uint32_t xfrag = sb + SM_X + ((g & 3) * XPITCH + 2 * j) * 2;
        float acc[3][4] = {};
#pragma unroll
        for (int s = 0; s < 5; s++) {
            const int ks = warp * 5 + s;
            const uint32_t b0 = lds32(xfrag + ks * 32), b1 = lds32(xfrag + ks * 32 + 16);
            const int row = ks * 16 + frow;
#pragma unroll
            for (int mt = 0; mt < 3; mt++) {
                uint32_t a[4];
                ldsm4t(a, sb + SM_W + (row * 6 + 2 * mt + fcol) * 16);
                mma16816(acc[mt], a, b0, b1);
            }
        }
        if (j < 2) {
#pragma unroll
            for (int mt = 0; mt < 3; mt++) {
                *reinterpret_cast<float2*>(red + warp * 216 + mt * 72 + g * 4 + 2 * j) = make_float2(acc[mt][0], acc[mt][1]);
                *reinterpret_cast<float2*>(red + warp * 216 + mt * 72 + 36 + g * 4 + 2 * j) = make_float2(acc[mt][2], acc[mt][3]);
            }
        }
        aux_sync();
        if (warp < 4) {
            const float* src = red + min(g, 5) * 36 + warp * 8 + j;
            float s0 = 0.f, s1 = 0.f;
#pragma unroll
            for (int w = 0; w < 8; w++) { s0 += src[w * 216]; s1 += src[w * 216 + 4]; }
            st_relaxed(&g_early[j * NH + (cta >> 2)].q[cta & 3][warp][g], pack_neg(s0, s1));
        }
        TS(28);
    }
    fin_sync<3>();
    mbar_wait(sb + BAR_WO, 0);
    TS(7);
    uint32_t part = sb + SM_RED + (warp * 32 + 8 * j + g) * 4;

#pragma unroll 1
    for (int b = 0; b < NB; b++) {
        if (cta >= NE_CTAS) {
            uint32_t a[6][2][4];
#pragma unroll
            for (int s = 0; s < 6; s++) {
#pragma unroll
                for (int mt = 0; mt < 2; mt++) ldsm4t(a[s][mt], (f64b ^ (mt * 32)) + SM_A + (warp * 6 + s) * 1024);
            }
            const int bh = b * NH + 28 + (warp >> 1);
            const int side = near_side(sb) ^ 1;
            const void* osrc[OREP];
#pragma unroll
            for (int c = 0; c < OREP; c++)
                osrc[c] = b == NB - 1 ? (const void*)&g_st.ox[c >> 1].w[side ^ (c & 1) * 3][oidx(bh & 3, (warp & 1) * 32 + lane) * 4] : &g_st.oacc[oidx(bh, (warp & 1) * 32 + lane)];
            const void* lsrc = b == NB - 1 ? (const void*)&g_st.lx.w[side][(bh & 3) * 256] : g_st.lsum[bh];
            wait_row_o(bh, 1);
            const float rl = rcp_approx(wait_sum(lsrc, UPB)) * (b == NB - 1 ? 1.f : 1.f / OREP), full = b == NB - 1 ? UPB : UPB * OREP;
            float4 ov;
            float px, py, pz;
            Warm warm;
#pragma unroll 1
            for (int it = 0; it < SPIN_MAX; it++) {
                wait_slot<PH_O>();
                float4 oc[OREP];
#pragma unroll
                for (int c = 0; c < OREP; c++) oc[c] = ld_relaxed_f4(osrc[c]);
                warm();
                ov = oc[0];
#pragma unroll
                for (int c = 1; c < OREP; c++) { ov.x += oc[c].x; ov.y += oc[c].y; ov.z += oc[c].z; ov.w += oc[c].w; }
                ov.x *= rl; ov.y *= rl; ov.z *= rl;
                px = __shfl_xor_sync(0xffffffffu, ov.x, 4); py = __shfl_xor_sync(0xffffffffu, ov.y, 4); pz = __shfl_xor_sync(0xffffffffu, ov.z, 4);
                if (all(ov.w == full)) break;
            }
            CK(0, __float_as_uint(ov.x));
            if (ov.x != 1.2345f && warp == 7) TSW(14);
            const uint32_t w[3] = {pack_bf16(ov.x, px), pack_bf16(ov.y, py), pack_bf16(ov.z, pz)};
            float acc[2][2][4] = {};
#pragma unroll
            for (int s = 0; s < 6; s++) {
                const uint32_t b0 = __shfl_sync(0xffffffffu, w[s % 3], (s / 3) * 16 + j);
                const uint32_t b1 = __shfl_sync(0xffffffffu, w[s % 3], (s / 3) * 16 + 8 + j);
#pragma unroll
                for (int mt = 0; mt < 2; mt++) mma16816(acc[mt][s & 1], a[s][mt], b0, b1);
            }
            sts32f(part, sel4(j, acc[0][0][0] + acc[0][1][0], acc[0][0][2] + acc[0][1][2], acc[1][0][0] + acc[1][1][0], acc[1][0][2] + acc[1][1][2]));
            CK(1, 0);
            fin_arrive<4>();
            warm.done(sb + SM_SCRAP);
            fin_sync<5>();
            if (cta < NE_CTAS + 4 && tid < 64) reinterpret_cast<uint4*>(&g_early[b * NH + 28 + cta - NE_CTAS])[tid] = make_uint4(0u, 0u, 0u, 0u);
        } else {
            const int bh = b * NH + (cta >> 2);
            if (warp == 0) wait_row_o(bh, UPB);
            aux_sync();
            if (warp < 5) {
                uint32_t ob[12][2];
                load_o<4>(ob, bh, 0, j);
                float acc[2][2][4] = {};
#pragma unroll
                for (int ks = 0; ks < 12; ks++) {
#pragma unroll
                    for (int mt = 0; mt < 2; mt++) {
                        uint32_t a[4];
                        ldsm4t(a, (f64b ^ (mt * 32)) + SM_A + warp * 12288 + ks * 1024);
                        mma16816(acc[mt][ks & 1], a, ob[ks][0], ob[ks][1]);
                    }
                }
                red_f2(&g_st.attn[b][(cta & 3) * 160 + warp * 32 + 8 * j + g].x,
                       sel4(j, acc[0][0][0] + acc[0][1][0], acc[0][0][2] + acc[0][1][2], acc[1][0][0] + acc[1][1][0], acc[1][0][2] + acc[1][1][2]), 1.f);
                TS(8);
            } else if (warp > 5 && (cta & 3) == 0) {
                reinterpret_cast<uint4*>(&g_early[bh])[tid - 192] = make_uint4(0u, 0u, 0u, 0u);
            }
        }
        if (b < NB - 2) continue;

        if (is_f(cta)) {
            uint32_t ga[10][2][4];
            uint4 hv[5];
            const uint32_t hfrag = sb + SM_X + min(g, 4) * HPITCH + ((warp >> 1) * 80 + 4 * j) * 4;
            if (b == NB - 1) mbar_wait(sb + BAR_FW + warp * 8, 0);
            if (warp == 7) TSW(10);
            CK(12, lds32(sb + SM_W));
#pragma unroll
            for (int s = 0; s < 10; s++) {
#pragma unroll
                for (int mt = 0; mt < 2; mt++) ldsm4t(ga[s][mt], (f64b ^ (mt * 32)) + SM_W + (warp * 10 + s) * 1024);
            }
            const uint32_t gpart = sb + SM_RED + (warp >> 1) * 640 + j * 256 + ((g + 2 * j) & 7) * 16 + (warp & 1) * 8;
            mbar_wait(sb + BAR_H, b & 1);
#pragma unroll
            for (int s = 0; s < 5; s++) hv[s] = lds128(hfrag + s * 64);
            CK(4, hv[0].x);
            float acc[2][2][4] = {};
#pragma unroll
            for (int s = 0; s < 10; s++) {
#pragma unroll
                for (int mt = 0; mt < 2; mt++)
                    mma16816(acc[mt][s & 1], ga[s][mt], (s & 1) ? hv[s >> 1].z : hv[s >> 1].x, (s & 1) ? hv[s >> 1].w : hv[s >> 1].y);
            }
#pragma unroll
            for (int mt = 0; mt < 2; mt++) {
                if (j < 3) sts64f(gpart + mt * 2560, acc[mt][0][0] + acc[mt][1][0], acc[mt][0][2] + acc[mt][1][2]);
                if (j < 2) sts64f(gpart + mt * 2560 + 128, acc[mt][0][1] + acc[mt][1][1], acc[mt][0][3] + acc[mt][1][3]);
            }
            CK(5, 0);
            asm volatile("bar.arrive 4, 320;" ::: "memory");
        } else if (is_g(cta)) {
            const uint32_t* asrc = &g_st.ax[0].w[(~b & 1) * 2 + near_side(sb)][warp * 128 + ((g >> 2) * 2 + (j >> 1)) * 32 + (g & 3) * 8 + (j & 1) * 4];
            const uint32_t ypart = sb + SM_RED2 + warp * 512 + j * 128 + ((g + 2 * j) & 7) * 16;
            uint32_t wb[12][4];
            uint4 va[3] = {};
            uint32_t lo[3] = {};
            auto ask = [&]() {
#pragma unroll
                for (int i = 0; i < 3; i++) ld_relaxed_v4_if(va[i], asrc + i * 4096, lo[i] == 0);
            };
            auto complete = [&]() {
#pragma unroll
                for (int i = 0; i < 3; i++) lo[i] = min(min(va[i].x, va[i].y), min(va[i].z, va[i].w));
                return all(min(lo[0], min(lo[1], lo[2])) != 0);
            };
            const int jj = (lane & 7) >> 1, q = jj >> 1, hi = lane >> 4;
            const uint32_t wsrc = sb + SM_W + warp * 6144 + q * 512 + ((hi ^ q) * 4 + (jj & 1) * 2 + (lane & 1)) * 32 + ((fcol ^ hi ^ q) << 4);
            mbar_wait(sb + BAR_H, b & 1);
            if (b == NB - 1) mbar_wait(sb + BAR_FW + warp * 8, 0);
            if (warp == 7) TSW(11);
            CK(13, lds32(sb + SM_W));
            ask();
#pragma unroll
            for (int s = 0; s < 12; s++) ldsm4t(wb[s], wsrc + (s >> 2) * 2048 + (s & 1) * 1024 + (s & 2) * 128);
            Warm warm;
            if (!complete()) {
#pragma unroll 1
                for (int it = 0; it < SPIN_MAX; it++) {
                    ask();
                    warm();
                    if (complete()) break;
                }
            }
            CK(8, va[0].x);
            if (va[0].x != 0x12345 && warp == 7) TSW(15);
            float acc[6][4] = {};
#pragma unroll
            for (int s = 0; s < 12; s++) {
                const uint4 v = va[s >> 2];
                mma16816(acc[s % 6], wb[s], (s & 2) ? v.z : v.x, (s & 2) ? v.w : v.y);
            }
            float y[4];
#pragma unroll
            for (int e = 0; e < 4; e++) y[e] = j < 2 ? (acc[0][e] + acc[2][e]) + acc[4][e] : (acc[1][e] + acc[3][e]) + acc[5][e];
            sts128f(ypart, y[0], y[1], y[2], y[3]);
            CK(9, 0);
            fin_arrive<6>();
            warm.done(sb + SM_SCRAP);
        }
    }
}

typedef CUresult (*EncodeFn)(CUtensorMap*, CUtensorMapDataType, cuuint32_t, void*, const cuuint64_t*, const cuuint64_t*,
                             const cuuint32_t*, const cuuint32_t*, CUtensorMapInterleave, CUtensorMapSwizzle,
                             CUtensorMapL2promotion, CUtensorMapFloatOOBfill);

CUtensorMap make_map(EncodeFn enc, void* ptr, uint64_t cols, uint64_t rows, uint32_t bcols, uint32_t brows,
                     CUtensorMapSwizzle sw, CUtensorMapL2promotion promo) {
    CUtensorMap m;
    const cuuint64_t dims[2] = {cols, rows};
    const cuuint64_t strides[1] = {cols * 2};
    const cuuint32_t box[2] = {bcols, brows};
    const cuuint32_t es[2] = {1, 1};
    enc(&m, CU_TENSOR_MAP_DATA_TYPE_BFLOAT16, 2, ptr, dims, strides, box, es, CU_TENSOR_MAP_INTERLEAVE_NONE, sw, promo,
        CU_TENSOR_MAP_FLOAT_OOB_FILL_NONE);
    return m;
}

}

extern "C" void kernel_launch(void* const* d_in, const int* in_sizes, int n_in, void* d_out, int out_size) {
    (void)in_sizes; (void)n_in; (void)out_size;
    static EncodeFn enc = nullptr;
    static int sms = 0;
    if (!enc) {
        cudaDriverEntryPointQueryResult qr;
        cudaGetDriverEntryPoint("cuTensorMapEncodeTiled", (void**)&enc, cudaEnableDefault, &qr);
        int dev = 0;
        cudaGetDevice(&dev);
        cudaDeviceGetAttribute(&sms, cudaDevAttrMultiProcessorCount, dev);
        cudaFuncSetAttribute(fused_decode_kernel, cudaFuncAttributeMaxDynamicSharedMemorySize, SM_TOTAL);
    }
    if (sms < NCTAS) return;
    const CUtensorMapL2promotion WPROMO = CU_TENSOR_MAP_L2_PROMOTION_L2_128B;
    Params p;
    p.k = make_map(enc, d_in[1], 64, (uint64_t)NBH * SK * 3, 64, TILE_ROWS, CU_TENSOR_MAP_SWIZZLE_128B, CU_TENSOR_MAP_L2_PROMOTION_NONE);
    p.v = make_map(enc, d_in[2], 64, (uint64_t)NBH * SK * 3, 64, TILE_ROWS, CU_TENSOR_MAP_SWIZZLE_128B, CU_TENSOR_MAP_L2_PROMOTION_NONE);
    p.wq = make_map(enc, d_in[3], NH * DH, DM, 48, 160, CU_TENSOR_MAP_SWIZZLE_NONE, WPROMO);
    p.wo = make_map(enc, d_in[4], DM, NH * DH, 32, DH, CU_TENSOR_MAP_SWIZZLE_64B, WPROMO);
    p.wg = make_map(enc, d_in[7], FF, DM, 32, 160, CU_TENSOR_MAP_SWIZZLE_64B, WPROMO);
    p.wu = make_map(enc, d_in[8], FF, DM, 32, 160, CU_TENSOR_MAP_SWIZZLE_64B, WPROMO);
    {
        const cuuint64_t dims[4] = {DM, 2, 8, FF / 16}, strides[3] = {8 * DM * 2, DM * 2, 16 * DM * 2};
        const cuuint32_t box[4] = {16, 2, 8, 12}, es[4] = {1, 1, 1, 1};
        enc(&p.wd, CU_TENSOR_MAP_DATA_TYPE_BFLOAT16, 4, d_in[9], dims, strides, box, es, CU_TENSOR_MAP_INTERLEAVE_NONE,
            CU_TENSOR_MAP_SWIZZLE_32B, WPROMO, CU_TENSOR_MAP_FLOAT_OOB_FILL_NONE);
    }
    p.x = (const __nv_bfloat16*)d_in[0];
    p.wr = (const __nv_bfloat16*)d_in[6];
    p.out = (__nv_bfloat16*)d_out;
    fused_decode_kernel<<<NCTAS, NTHREADS, SM_TOTAL, cudaStreamPerThread>>>(p);
}
```

```cpp
#include <cuda_runtime.h>
#include <cuda_bf16.h>
#include <cuda.h>
#include <stdint.h>

namespace {

constexpr int NB = 4, NH = 32, SK = 8192, DH = 192, DM = 640, FF = 1536;
constexpr int NBH = NB * NH;
constexpr int TILE = 64;
constexpr int UPB = SK / TILE;
constexpr int NUNITS = NBH * UPB;
constexpr int TILE_BYTES = TILE * DH * 2;
constexpr int TILE_ROWS = TILE * 3;
constexpr int NCTAS = 132;
constexpr int NQ_CTAS = 128;
constexpr int NE_CTAS = 112;
__host__ __device__ constexpr bool is_f(int cta) { return cta < NE_CTAS && cta % 14 < 11 && !(cta & 1); }
__host__ __device__ constexpr bool is_g(int cta) { return cta < NE_CTAS && cta % 14 < 11 && (cta & 1); }
__host__ __device__ constexpr int ffn_slice(int cta) { return cta / 14 * ((cta & 1) ? 5 : 6) + cta % 14 / 2; }

#define NWORK 2
#define LAG 3
#define NPOOL 896
#define RED0 116
#define RING 12
#define OREP 2
#define K0_AT_NS 1150
#define WO_AT_NS (K0_AT_NS + 2000)
#define K1_AT_NS (K0_AT_NS + 4400)
#define WO_STEP_NS 75
constexpr int KSWEEP_NS = 2000;
#define FW_TICKET (NPOOL + 32)
#define FW_AT_NS 2090
#define FW_GAP 280
#define FW_MID 2100
#define FW_GAP2 200
#define HGATE_NS 700
#define SLOT_TICKS 9
#define SLOT_OPEN 3
#define PH_O 0
#define PH_H 8
#define PH_M 2
#define NPROBE 24
#define MIX_R 6
#define MIX_FROM 1
#define MIX_ROWS 3
constexpr int MIX = MIX_ROWS * UPB, MIX1 = (NBH - 4) * UPB, MIX0 = MIX1 - (MIX1 - MIX_FROM * NWORK * NCTAS) / MIX * MIX;
static_assert((MIX1 - (NUNITS - NPOOL)) % MIX == 0, "the pool starts with a group of rows");
__device__ __forceinline__ int unit_of(int t) {
    const unsigned r = (unsigned)(t - MIX0) % MIX, e = t - MIX1;
    if (e < 4 * UPB) return MIX1 + (e & 256) + (e & 3) * 64 + (e & 255) / 4;
    return t < MIX0 || t >= MIX1 ? t : t - r + r % MIX_R * (MIX / MIX_R) + r / MIX_R;
}
static_assert(FW_TICKET < NPOOL + NWORK * NCTAS, "every worker draws one ticket beyond the pool");
constexpr int NAUX = 8;
constexpr int NTHREADS = (NAUX + NWORK + 2) * 32;
constexpr int SPIN_MAX = 1 << 22;

constexpr int SM_KV = 0;
constexpr int SM_A = SM_KV + NWORK * TILE_BYTES;
constexpr int SM_W = SM_A + 61440;
constexpr int SM_X = SM_W + 81920;
constexpr int XPITCH = 648;
constexpr int HPITCH = 1344;
constexpr int SM_RED = SM_X + 5 * HPITCH + 64;
constexpr int SM_RED2 = SM_RED + 8 * 48 * 4 * 4;
constexpr int SM_MISC = SM_RED2 + 4096;
constexpr int BAR_WQ = SM_MISC, SM_SCRAP = SM_MISC + 32, BAR_WO = SM_MISC + 40, SM_SIDE = SM_MISC + 48, BAR_H = SM_MISC + 56, BAR_FW = SM_MISC + 64;
constexpr int BAR_KV = BAR_FW + 64;
constexpr int SM_TOTAL = BAR_KV + NWORK * 8;
static_assert(SM_W % 1024 == 0 && NB * XPITCH * 2 <= 4 * HPITCH && SM_RED % 128 == 0, "smem layout");

struct Params {
    CUtensorMap k, v;
    CUtensorMap wq;
    CUtensorMap wo;
    CUtensorMap wg, wu;
    CUtensorMap wd;
    const __nv_bfloat16 *x, *wr;
    __nv_bfloat16* out;
};

struct Early {
    uint32_t q[4][4][8];
    uint32_t umax[UPB];
};
struct Twin { uint32_t w[4][1024]; };
constexpr int PROBE = 1024 - 32;
#define LSTRIDE 16
struct State {
    Twin ax[3];
    Twin hx;
    Twin ox[(OREP + 1) / 2];
    Twin lx;
    float4 oacc[NBH * 64];
    float2 attn[NB][DM];
    uint32_t fw_time[32];
    float2 lsum[NBH][LSTRIDE];
    uint32_t score[NPOOL][32];
};
__host__ __device__ constexpr int oidx(int row, int grp) {
    return (row >> 2) * 256 + ((row & 1) * 2 + (grp >> 5)) * 64 + (row & 2) * 16 + (grp & 31);
}
constexpr int STATE_V4 = ((sizeof(State) / 32 + NQ_CTAS - 1) / NQ_CTAS) * 2;
static_assert(sizeof(State) % 32 == 0, "State is cleared in whole sectors");
static_assert(sizeof(Early) == 64 * 16, "an Early entry is cleared by 64 threads");
struct Scratch {
    State st;
    unsigned work[64];
    unsigned cnt_z[32];
    Early early[NBH];
    alignas(4096) float4 ring[RING][UPB][64];
};
constexpr size_t PAGE = 2u << 20;
static_assert(sizeof(Scratch) <= PAGE, "scratch must fit one page");
__device__ __align__(128) unsigned char g_raw[2 * PAGE];
__device__ __forceinline__ Scratch* scratch() {
    return reinterpret_cast<Scratch*>((reinterpret_cast<uintptr_t>(g_raw) + PAGE - 1) & ~(uintptr_t)(PAGE - 1));
}
#define g_early scratch()->early
#define g_st scratch()->st
#define g_ring scratch()->ring
#define g_cnt_z scratch()->cnt_z
#define g_work scratch()->work
#define ALL_LOADERS 0
#define TS(i)
#define TSW(i)
#define TS2(i)
#define TSI(n, i)
#define PH(i)
#define CK(i, dep)
#define ARR()
#define PROG(u)

__device__ __forceinline__ uint32_t s2u(const void* p) { return (uint32_t)__cvta_generic_to_shared(p); }
__device__ __forceinline__ void mbar_init(uint32_t bar, int cnt) {
    asm volatile("mbarrier.init.shared::cta.b64 [%0], %1;" :: "r"(bar), "r"(cnt) : "memory");
}
__device__ __forceinline__ void mbar_wait(uint32_t bar, uint32_t parity) {
    asm volatile("{\n.reg .pred p;\n.reg .u32 n;\nmov.u32 n, 0;\nWAIT_LOOP:\n"
                 "mbarrier.try_wait.parity.shared::cta.b64 p, [%0], %1;\n"
                 "@p bra WAIT_DONE;\nadd.u32 n, n, 1;\nsetp.lt.u32 p, n, %2;\n@p bra WAIT_LOOP;\nWAIT_DONE:\n}"
                 :: "r"(bar), "r"(parity), "n"(SPIN_MAX) : "memory");
}
__device__ __forceinline__ void request_tile(uint32_t dst, const CUtensorMap* tm, int unit, uint32_t bar, uint64_t pol) {
    asm volatile("{\n.reg .pred p;\nelect.sync _|p, 0xffffffff;\n"
                 "@p mbarrier.arrive.expect_tx.shared::cta.b64 _, [%2], %6;\n"
                 "@p cp.async.bulk.tensor.2d.shared::cluster.global.mbarrier::complete_tx::bytes.L2::cache_hint "
                 "[%0], [%1, {%3, %4}], [%2], %5;\n}"
                 :: "r"(dst), "l"(tm), "r"(bar), "r"(0), "r"(unit * TILE_ROWS), "l"(pol), "n"(TILE_BYTES) : "memory");
}
__device__ __forceinline__ void put_groups(void* dst, int mode, const float (&o)[6], float tag, float tag2) {
    asm volatile("{\n.reg .pred s, t;\n.reg .b128 u, v;\n.reg .b64 a, b;\n"
                 "setp.eq.s32 s, %1, 0;\nsetp.ne.s32 t, %1, 2;\nxor.b64 a, %0, 4096;\n"
                 "@t bra.uni SINGLE;\n"
                 "red.relaxed.gpu.global.add.v4.f32 [a], {%2,%3,%4,%8};\n"
                 "red.relaxed.gpu.global.add.v4.f32 [a+128], {%5,%6,%7,%9};\n"
                 "SINGLE:\n"
                 "@s bra.uni STORE;\n"
                 "red.relaxed.gpu.global.add.v4.f32 [%0], {%2,%3,%4,%8};\n"
                 "red.relaxed.gpu.global.add.v4.f32 [%0+128], {%5,%6,%7,%9};\n"
                 "STORE:\n"
                 "mov.b64 a, {%2, %3};\nmov.b64 b, {%4, %8};\nmov.b128 u, {a, b};\n"
                 "mov.b64 a, {%5, %6};\nmov.b64 b, {%7, %9};\nmov.b128 v, {a, b};\n"
                 "@s st.relaxed.gpu.global.b128 [%0], u;\n@s st.relaxed.gpu.global.b128 [%0+128], v;\n}"
                 :: "l"(dst), "r"(mode), "f"(o[0]), "f"(o[1]), "f"(o[2]), "f"(o[3]), "f"(o[4]), "f"(o[5]), "f"(tag), "f"(tag2) : "memory");
}
__device__ __forceinline__ void request_box(uint32_t dst, const CUtensorMap* tm, int col, int row, uint32_t bar, uint32_t bytes) {
    asm volatile("{\n.reg .pred p, q;\nelect.sync _|p, 0xffffffff;\nsetp.ne.and.u32 q, %5, 0, p;\n"
                 "@q mbarrier.arrive.expect_tx.shared::cta.b64 _, [%2], %5;\n"
                 "@p cp.async.bulk.tensor.2d.shared::cluster.global.mbarrier::complete_tx::bytes [%0], [%1, {%3, %4}], [%2];\n}"
                 :: "r"(dst), "l"(tm), "r"(bar), "r"(col), "r"(row), "r"(bytes) : "memory");
}
__device__ __forceinline__ uint32_t lds32(uint32_t addr) {
    uint32_t v;
    asm volatile("ld.shared.u32 %0, [%1];" : "=r"(v) : "r"(addr) : "memory");
    return v;
}
__device__ __forceinline__ void ldsm4(uint32_t (&r)[4], uint32_t addr) {
    asm volatile("ldmatrix.sync.aligned.m8n8.x4.shared.b16 {%0,%1,%2,%3}, [%4];"
                 : "=r"(r[0]), "=r"(r[1]), "=r"(r[2]), "=r"(r[3]) : "r"(addr) : "memory");
}
__device__ __forceinline__ void ldsm4t(uint32_t (&r)[4], uint32_t addr) {
    asm volatile("ldmatrix.sync.aligned.m8n8.x4.trans.shared.b16 {%0,%1,%2,%3}, [%4];"
                 : "=r"(r[0]), "=r"(r[1]), "=r"(r[2]), "=r"(r[3]) : "r"(addr) : "memory");
}
__device__ __forceinline__ void mma16816(float (&c)[4], const uint32_t (&a)[4], uint32_t b0, uint32_t b1) {
    asm volatile("mma.sync.aligned.m16n8k16.row.col.f32.bf16.bf16.f32 {%0,%1,%2,%3}, {%4,%5,%6,%7}, {%8,%9}, {%0,%1,%2,%3};"
                 : "+f"(c[0]), "+f"(c[1]), "+f"(c[2]), "+f"(c[3])
                 : "r"(a[0]), "r"(a[1]), "r"(a[2]), "r"(a[3]), "r"(b0), "r"(b1));
}
struct Warm {
    float c[4] = {};
    __device__ __forceinline__ void operator()() {
        asm volatile("mma.sync.aligned.m16n8k8.row.col.f32.bf16.bf16.f32 {%0,%1,%2,%3}, {%4,%4}, {%4}, {%0,%1,%2,%3};"
                     : "+f"(c[0]), "+f"(c[1]), "+f"(c[2]), "+f"(c[3]) : "r"(0));
    }
    __device__ __forceinline__ void done(uint32_t scrap) {
        asm volatile("{\n.reg .pred p;\nsetp.gt.f32 p, %1, 0f3f800000;\n@p st.shared.f32 [%0], %1;\n}" :: "r"(scrap), "f"(c[0]) : "memory");
    }
};
__device__ __forceinline__ uint4 ld_relaxed_v4(const void* p) {
    uint4 v;
    asm volatile("ld.relaxed.gpu.global.v4.u32 {%0,%1,%2,%3}, [%4];" : "=r"(v.x), "=r"(v.y), "=r"(v.z), "=r"(v.w) : "l"(p) : "memory");
    return v;
}
__device__ __forceinline__ float4 ld_relaxed_f4(const void* p) {
    float4 v;
    asm volatile("ld.relaxed.gpu.global.v4.f32 {%0,%1,%2,%3}, [%4];" : "=f"(v.x), "=f"(v.y), "=f"(v.z), "=f"(v.w) : "l"(p) : "memory");
    return v;
}
__device__ __forceinline__ float2 ld_relaxed_f2(const void* p) {
    float2 v;
    asm volatile("ld.relaxed.gpu.global.v2.f32 {%0,%1}, [%2];" : "=f"(v.x), "=f"(v.y) : "l"(p) : "memory");
    return v;
}
__device__ __forceinline__ float4 ld_relaxed_b128(const void* p) {
    float4 v;
    asm volatile("{\n.reg .b128 t;\n.reg .b64 a, b;\nld.relaxed.gpu.global.b128 t, [%4];\nmov.b128 {a, b}, t;\n"
                 "mov.b64 {%0, %1}, a;\nmov.b64 {%2, %3}, b;\n}" : "=f"(v.x), "=f"(v.y), "=f"(v.z), "=f"(v.w) : "l"(p) : "memory");
    return v;
}
__device__ __forceinline__ void st_relaxed_b128(void* p, float x, float y, float z, float w) {
    asm volatile("{\n.reg .b128 t;\n.reg .b64 a, b;\nmov.b64 a, {%1, %2};\nmov.b64 b, {%3, %4};\nmov.b128 t, {a, b};\n"
                 "st.relaxed.gpu.global.b128 [%0], t;\n}" :: "l"(p), "f"(x), "f"(y), "f"(z), "f"(w) : "memory");
}
__device__ __forceinline__ unsigned ld_acquire(const unsigned* p) {
    unsigned v;
    asm volatile("ld.acquire.gpu.global.u32 %0, [%1];" : "=r"(v) : "l"(p) : "memory");
    return v;
}
__device__ __forceinline__ void st_relaxed(void* p, uint32_t v) {
    asm volatile("st.relaxed.gpu.global.u32 [%0], %1;" :: "l"(p), "r"(v) : "memory");
}
__device__ __forceinline__ void red_f2(float* p, float a, float b) {
    asm volatile("red.relaxed.gpu.global.add.v2.f32 [%0], {%1,%2};" :: "l"(p), "f"(a), "f"(b) : "memory");
}
__device__ __forceinline__ void draw(int& ticket, unsigned* ctr, bool pred) {
    asm volatile("{\n.reg .pred p;\nsetp.ne.u32 p, %2, 0;\n@p atom.relaxed.gpu.global.inc.u32 %0, [%1], 0x7fffffff;\n}"
                 : "+r"(ticket) : "l"(ctr), "r"((uint32_t)pred) : "memory");
}
__device__ __forceinline__ void red_release(unsigned* p) {
    asm volatile("red.release.gpu.global.add.u32 [%0], 1;" :: "l"(p) : "memory");
}
__device__ __forceinline__ uint32_t ld_relaxed_u32(const void* p) {
    uint32_t v;
    asm volatile("ld.relaxed.gpu.global.u32 %0, [%1];" : "=r"(v) : "l"(p) : "memory");
    return v;
}
__device__ __forceinline__ float rcp_approx(float v) {
    float r;
    asm("rcp.approx.ftz.f32 %0, %1;" : "=f"(r) : "f"(v));
    return r;
}
__device__ __forceinline__ float ex2_approx(float v) {
    float e;
    asm("ex2.approx.ftz.f32 %0, %1;" : "=f"(e) : "f"(v));
    return e;
}
__device__ __forceinline__ float sigmoid_approx(float v) { return rcp_approx(1.0f + ex2_approx(v * -1.4426950408889634f)); }
__device__ __forceinline__ float sqrt_approx(float v) {
    float r;
    asm("sqrt.approx.ftz.f32 %0, %1;" : "=f"(r) : "f"(v));
    return r;
}
__device__ __forceinline__ bool all(bool v) { return __all_sync(0xffffffffu, v); }
__device__ __forceinline__ void wait_count(const unsigned* p, unsigned target) {
#pragma unroll 1
    for (int it = 0; it < SPIN_MAX; it++) {
        if (all(ld_acquire(p) >= target)) break;
        __nanosleep(400);
    }
}
__device__ __forceinline__ float wait_sum(const void* p, float n, int nap = 0) {
    float2 v;
#pragma unroll 1
    for (int it = 0; it < SPIN_MAX; it++) {
        v = ld_relaxed_f2(p);
        if (all(v.y >= n)) break;
        if (all(v.y == 0.f)) __nanosleep(600);
        else if (nap) __nanosleep(nap);
    }
    return v.x;
}
__device__ __forceinline__ void wait_row(int bh, float n) { wait_sum(g_st.lsum[bh], n); }
__device__ __forceinline__ void wait_row_o(int bh, float n) {
    wait_row(bh, n);
    if (bh >= RED0) return;
#pragma unroll 1
    for (int it = 0; it < SPIN_MAX; it++) {
        if (all(__uint_as_float(ld_relaxed_u32(&g_st.oacc[oidx(bh, 0)].w)) == UPB)) break;
        __nanosleep(300);
    }
}
constexpr uint32_t SLOT_K = (uint32_t)(((1ull << 32) + SLOT_TICKS - 1) / SLOT_TICKS);
#define SLOT_ASM(t, n, p, phase, k, open) \
    "mov.u32 " n ", 0;\nSLOT:\nmov.u32 " t ", %%globaltimer_lo;\nadd.u32 " n ", " n ", 1;\nsetp.lt.u32 " p ", " n ", 24;\nshr.u32 " t ", " t ", 5;\n" \
    "mad.lo.u32 " t ", " t ", " k ", " phase ";\nsetp.ge.and.u32 " p ", " t ", " open ", " p ";\n@" p " bra.uni SLOT;\n"
template <int PHASE> __host__ __device__ constexpr uint32_t slot_phase() { return SLOT_K / 2 - PHASE * SLOT_K; }
template <int PHASE> __device__ __forceinline__ void wait_slot() {
    if (PHASE < 0) return;
    asm volatile("{\n.reg .pred p;\n.reg .b32 t, n;\n" SLOT_ASM("t", "n", "p", "%0", "%1", "%2") "}"
                 :: "n"(slot_phase<PHASE>()), "n"(SLOT_K), "n"(SLOT_OPEN * SLOT_K) : "memory");
}
__device__ __forceinline__ void wait_time(uint32_t t) {
#pragma unroll 1
    for (int it = 0; it < SPIN_MAX; it++) {
        uint32_t now;
        asm volatile("mov.u32 %0, %%globaltimer_lo;" : "=r"(now));
        if (all((int)(now - t) >= 0)) break;
    }
}
__device__ __forceinline__ void wait_clock(uint32_t t, Warm& warm) { while (!all((int)(clock() - t) >= 0)) { warm(); } }
__device__ __forceinline__ uint32_t pack_bf16(float lo, float hi) {
    uint32_t r;
    asm("cvt.rn.bf16x2.f32 %0, %1, %2;" : "=r"(r) : "f"(hi), "f"(lo));
    return r;
}
__device__ __forceinline__ float bf16r(float v) { return __uint_as_float(pack_bf16(0.f, v)); }
__device__ __forceinline__ uint32_t nonzero(uint32_t w) { return w ? w : 0x80008000u; }
__device__ __forceinline__ uint32_t pack_neg(float lo, float hi) { return nonzero(pack_bf16(-lo, -hi)); }
__device__ __forceinline__ float lo_f(uint32_t v) { return __uint_as_float(v << 16); }
__device__ __forceinline__ float hi_f(uint32_t v) { return __uint_as_float(v & 0xffff0000u); }
__device__ __forceinline__ float warp_sum(float v) {
#pragma unroll
    for (int o = 16; o; o >>= 1) v += __shfl_xor_sync(0xffffffffu, v, o);
    return v;
}
__device__ __forceinline__ void layernorm20(float (&v)[20]) {
    float s = 0.f;
#pragma unroll
    for (int i = 0; i < 20; i++) s += v[i];
    const float mean = warp_sum(s) * (1.0f / DM);
    float q = 0.f;
#pragma unroll
    for (int i = 0; i < 20; i++) { const float d = v[i] - mean; q += d * d; }
    const float var = bf16r(warp_sum(q) * (1.0f / DM));
    const float m = bf16r(mean);
    const float rden = 1.0f / bf16r(sqrtf(bf16r(var + 1e-5f)));
#pragma unroll
    for (int i = 0; i < 20; i++) v[i] = bf16r(bf16r(v[i] - m) * rden);
}

__device__ __forceinline__ void moments(float m1, float m2, float& nmean, float& rden) {
    m1 *= 1.0f / DM;
    const float var = bf16r(fmaxf(fmaf(-m1, m1, m2 * (1.0f / DM)), 0.f));
    nmean = bf16r(m1);
    rden = rcp_approx(bf16r(sqrt_approx(bf16r(var + 1e-5f))));
}
__device__ __forceinline__ float sel4(int j, float a, float b, float c, float d) {
    float lo, hi, r;
    asm("{\n.reg .pred p;\nsetp.ne.s32 p, %3, 0;\nselp.f32 %0, %2, %1, p;\n}" : "=f"(lo) : "f"(a), "f"(b), "r"(j & 1));
    asm("{\n.reg .pred p;\nsetp.ne.s32 p, %3, 0;\nselp.f32 %0, %2, %1, p;\n}" : "=f"(hi) : "f"(c), "f"(d), "r"(j & 1));
    asm("{\n.reg .pred p;\nsetp.ne.s32 p, %3, 0;\nselp.f32 %0, %2, %1, p;\n}" : "=f"(r) : "f"(lo), "f"(hi), "r"(j & 2));
    return r;
}
template <typename T> __device__ __forceinline__ void pin(T*& p) { asm volatile("" : "+l"(p)); }
__device__ __forceinline__ void pin(uint32_t& v) { asm volatile("" : "+r"(v)); }
__device__ __forceinline__ void pin(float& v) { asm volatile("" : "+f"(v)); }
__device__ __forceinline__ uint32_t after(uint32_t n, float v) {
    asm volatile("{\n.reg .pred p;\nsetp.eq.u32 p, %1, 0x7fc1a5a5;\n@p add.u32 %0, %0, 32;\n}" : "+r"(n) : "r"(__float_as_uint(v)));
    return n;
}
__device__ __forceinline__ float2 lds64f(uint32_t addr) {
    float2 v;
    asm volatile("ld.shared.v2.f32 {%0,%1}, [%2];" : "=f"(v.x), "=f"(v.y) : "r"(addr) : "memory");
    return v;
}
__device__ __forceinline__ void sts32f(uint32_t addr, float v) { asm volatile("st.shared.f32 [%0], %1;" :: "r"(addr), "f"(v) : "memory"); }
template <int ID> __device__ __forceinline__ void fin_arrive() { asm volatile("bar.arrive %0, 288;" :: "n"(ID) : "memory"); }
template <int ID> __device__ __forceinline__ void fin_sync() { asm volatile("bar.sync %0, 288;" :: "n"(ID) : "memory"); }
template <int ID> __device__ __forceinline__ void fin_sync(uint32_t n) { asm volatile("bar.sync %0, %1;" :: "n"(ID), "r"(n) : "memory"); }
__device__ __forceinline__ float2 sum8(uint32_t addr, int pitch) {
    float2 t[8];
#pragma unroll
    for (int w = 0; w < 8; w++) t[w] = lds64f(addr + w * pitch);
    return make_float2(((t[0].x + t[1].x) + (t[2].x + t[3].x)) + ((t[4].x + t[5].x) + (t[6].x + t[7].x)),
                       ((t[0].y + t[1].y) + (t[2].y + t[3].y)) + ((t[4].y + t[5].y) + (t[6].y + t[7].y)));
}
__device__ __forceinline__ float4 sum4x4(uint32_t addr, int pitch) {
    float4 t[4];
#pragma unroll
    for (int w = 0; w < 4; w++)
        asm volatile("ld.shared.v4.f32 {%0,%1,%2,%3}, [%4];" : "=f"(t[w].x), "=f"(t[w].y), "=f"(t[w].z), "=f"(t[w].w) : "r"(addr + w * pitch) : "memory");
    return make_float4((t[0].x + t[1].x) + (t[2].x + t[3].x), (t[0].y + t[1].y) + (t[2].y + t[3].y),
                       (t[0].z + t[1].z) + (t[2].z + t[3].z), (t[0].w + t[1].w) + (t[2].w + t[3].w));
}
__device__ __forceinline__ void sts64f(uint32_t addr, float x, float y) {
    asm volatile("st.shared.v2.f32 [%0], {%1,%2};" :: "r"(addr), "f"(x), "f"(y) : "memory");
}
__device__ __forceinline__ uint4 lds128(uint32_t addr) {
    uint4 v;
    asm volatile("ld.shared.v4.u32 {%0,%1,%2,%3}, [%4];" : "=r"(v.x), "=r"(v.y), "=r"(v.z), "=r"(v.w) : "r"(addr) : "memory");
    return v;
}
__device__ __forceinline__ void ld_relaxed_v4_if(uint4& v, const void* p, bool pred) {
    asm volatile("{\n.reg .pred p;\nsetp.ne.u32 p, %5, 0;\n@p ld.relaxed.gpu.global.v4.u32 {%0,%1,%2,%3}, [%4];\n}"
                 : "+r"(v.x), "+r"(v.y), "+r"(v.z), "+r"(v.w) : "l"(p), "r"((uint32_t)pred) : "memory");
}
__device__ __forceinline__ void sts128f(uint32_t addr, float x, float y, float z, float w) {
    asm volatile("st.shared.v4.f32 [%0], {%1,%2,%3,%4};" :: "r"(addr), "f"(x), "f"(y), "f"(z), "f"(w) : "memory");
}
template <int NJ>
__device__ __forceinline__ void load_o(uint32_t (&ob)[3 * NJ][2], int bh, int J0, int j) {
    float4 v[NJ][4];
    float2 l;
#pragma unroll 1
    for (int it = 0; it < SPIN_MAX; it++) {
#pragma unroll
        for (int J = 0; J < NJ; J++) {
#pragma unroll
            for (int e = 0; e < 4; e++) v[J][e] = ld_relaxed_f4(&g_st.oacc[oidx(bh, j)] + oidx(0, (J0 + J) * 16 + e * 4));
        }
        l = ld_relaxed_f2(g_st.lsum[bh]);
        bool ok = l.y == UPB;
#pragma unroll
        for (int J = 0; J < NJ; J++) {
#pragma unroll
            for (int e = 0; e < 4; e++) ok &= v[J][e].w == UPB;
        }
        if (all(ok)) break;
    }
    const float rl = __fdividef(1.0f, l.x);
#pragma unroll
    for (int J = 0; J < NJ; J++) {
        ob[3 * J][0] = pack_bf16(v[J][0].x * rl, v[J][1].x * rl);     ob[3 * J][1] = pack_bf16(v[J][2].x * rl, v[J][3].x * rl);
        ob[3 * J + 1][0] = pack_bf16(v[J][0].y * rl, v[J][1].y * rl); ob[3 * J + 1][1] = pack_bf16(v[J][2].y * rl, v[J][3].y * rl);
        ob[3 * J + 2][0] = pack_bf16(v[J][0].z * rl, v[J][1].z * rl); ob[3 * J + 2][1] = pack_bf16(v[J][2].z * rl, v[J][3].z * rl);
    }
}
__device__ __forceinline__ int near_side(uint32_t sb) {
    uint32_t v;
    asm volatile("ld.volatile.shared.u32 %0, [%1];" : "=r"(v) : "r"(sb + SM_SIDE) : "memory");
    return v;
}
__device__ __forceinline__ void poll_row(uint4& a, uint4& b, uint2& c, const void* pa, const void* pb, const void* pc, uint32_t sa, uint32_t sc,
                                         bool arrive, bool nap, uint32_t bar, Warm& warm) {
    asm volatile("{\n.reg .pred p, q, r, s;\n.reg .b32 m, n, it;\n"
                 "setp.ne.u32 r, %19, 0;\nsetp.ne.u32 s, %20, 0;\nmov.u32 it, 0;\n"
                 "POLL:\n"
                 SLOT_ASM("m", "n", "p", "%23", "%24", "%25")
                 "ld.relaxed.gpu.global.v4.u32 {%0,%1,%2,%3}, [%14];\n"
                 "ld.relaxed.gpu.global.v4.u32 {%4,%5,%6,%7}, [%15];\n"
                 "ld.relaxed.gpu.global.v2.u32 {%8,%9}, [%16];\n"
                 "add.u32 it, it, 1;\nsetp.ge.u32 q, it, %21;\n"
                 "mov.u32 m, 0;\nmma.sync.aligned.m16n8k8.row.col.f32.bf16.bf16.f32 {%10,%11,%12,%13}, {m,m}, {m}, {%10,%11,%12,%13};\n"
                 "st.shared.v4.u32 [%17], {%0,%1,%2,%3};\n"
                 "st.shared.v4.u32 [%17+512], {%4,%5,%6,%7};\n"
                 "st.shared.v2.u32 [%18], {%8,%9};\n"
                 "min.u32 m, %0, %1;\nmin.u32 m, m, %2;\nmin.u32 n, %3, %4;\nmin.u32 n, n, %5;\nmin.u32 m, m, %6;\nmin.u32 m, m, %7;\n"
                 "min.u32 n, n, m;\nmin.u32 m, %8, %9;\nmin.u32 m, m, n;\n"
                 "setp.ne.or.u32 p, m, 0, q;\n"
                 "vote.sync.all.pred p, p, 0xffffffff;\n"
                 "and.pred q, p, r;\n"
                 "bar.warp.sync 0xffffffff;\n"
                 "@q mbarrier.arrive.shared::cta.b64 _, [%22];\n"
                 "@p bra.uni DONE;\n"
                 "@s nanosleep.u32 500;\n"
                 "bra.uni POLL;\n"
                 "DONE:\n}"
                 : "=&r"(a.x), "=&r"(a.y), "=&r"(a.z), "=&r"(a.w), "=&r"(b.x), "=&r"(b.y), "=&r"(b.z), "=&r"(b.w), "=&r"(c.x), "=&r"(c.y),
                   "+f"(warm.c[0]), "+f"(warm.c[1]), "+f"(warm.c[2]), "+f"(warm.c[3])
                 : "l"(pa), "l"(pb), "l"(pc), "r"(sa), "r"(sc), "r"((uint32_t)arrive), "r"((uint32_t)nap), "n"(SPIN_MAX), "r"(bar),
                   "n"(slot_phase<PH_H>()), "n"(SLOT_K), "n"(SLOT_OPEN * SLOT_K) : "memory");
}
__device__ __forceinline__ void aux_sync() { asm volatile("bar.sync 1, 256;" ::: "memory"); }

__global__ void __launch_bounds__(NTHREADS, 1)
fused_decode_kernel(const __grid_constant__ Params p) {
    extern __shared__ __align__(1024) unsigned char smem[];
    const uint32_t sb = s2u(smem);
    const int tid = threadIdx.x, cta = blockIdx.x;
    if (tid < 32 && cta < NQ_CTAS) {
        asm volatile("{\n.reg .pred p;\nelect.sync _|p, 0xffffffff;\n"
                     "@p mbarrier.init.shared::cta.b64 [%2], 1;\n"
                     "@p fence.mbarrier_init.release.cluster;\n"
                     "@p mbarrier.arrive.expect_tx.shared::cta.b64 _, [%2], 15360;\n"
                     "@p cp.async.bulk.tensor.2d.shared::cluster.global.mbarrier::complete_tx::bytes [%0], [%1, {%3, %4}], [%2];\n"
                     "@p mbarrier.init.shared::cta.b64 [%2+8], 1;\n@p mbarrier.init.shared::cta.b64 [%2+16], 1;\n"
                     "@p mbarrier.init.shared::cta.b64 [%2+24], 1;\n"
                     "@p fence.mbarrier_init.release.cluster;\n"
                     "@p mbarrier.arrive.expect_tx.shared::cta.b64 _, [%2+8], 15360;\n"
                     "@p cp.async.bulk.tensor.2d.shared::cluster.global.mbarrier::complete_tx::bytes [%0+15360], [%1, {%3, %5}], [%2+8];\n"
                     "@p mbarrier.arrive.expect_tx.shared::cta.b64 _, [%2+16], 15360;\n"
                     "@p cp.async.bulk.tensor.2d.shared::cluster.global.mbarrier::complete_tx::bytes [%0+30720], [%1, {%3, %6}], [%2+16];\n"
                     "@p mbarrier.arrive.expect_tx.shared::cta.b64 _, [%2+24], 15360;\n"
                     "@p cp.async.bulk.tensor.2d.shared::cluster.global.mbarrier::complete_tx::bytes [%0+46080], [%1, {%3, %7}], [%2+24];\n}"
                     :: "r"(sb + SM_W), "l"(&p.wq), "r"(sb + BAR_WQ), "r"(cta * 48), "r"(0), "r"(160), "r"(320), "r"(480) : "memory");
    }
    const int warp = __shfl_sync(0xffffffffu, tid >> 5, 0), lane = tid & 31;
    constexpr int grid = NCTAS;
    const int g = lane >> 2, j = lane & 3;
    uint32_t t_start;
    asm volatile("mov.u32 %0, %%globaltimer_lo;" : "=r"(t_start));
    TS(0);
    if (tid == 32) {
        mbar_init(sb + BAR_WO, 1);
        mbar_init(sb + BAR_H, 1);
#pragma unroll
        for (int i = 0; i < 8 + NWORK; i++) mbar_init(sb + BAR_FW + i * 8, 1);
        sts32f(sb + SM_SIDE, 0.f);
        asm volatile("fence.mbarrier_init.release.cluster;" ::: "memory");
        asm volatile("fence.proxy.async.shared::cta;" ::: "memory");
    }
    __syncthreads();
    if (warp >= NAUX + NWORK) {
        const int fw = warp - (NAUX + NWORK), fi = ffn_slice(cta);
        if (fw == 0) {
            if (cta < NQ_CTAS) {
#pragma unroll
                for (int i = lane; i < STATE_V4; i += 32)
                    if (cta * STATE_V4 + i < (int)(sizeof(State) / 16)) reinterpret_cast<uint4*>(&g_st)[cta * STATE_V4 + i] = make_uint4(0u, 0u, 0u, 0u);
                __syncwarp();
                if (lane == 0) red_release(g_cnt_z);
            }
            TSW(2); wait_count(g_cnt_z, NQ_CTAS); TSW(29);
            asm volatile("bar.arrive 2, %0;" :: "n"((NWORK + 2) * 32) : "memory");
            fin_arrive<3>();
        } else {
#pragma unroll 1
            for (int n = cta < NE_CTAS ? 5 : 4, i = n - 1; i >= 0; i--) {
                const int head = cta < NE_CTAS ? cta >> 2 : 28 + i;
                wait_time(t_start + WO_AT_NS + (NH - 1 - head) * WO_STEP_NS);
                request_box(sb + SM_A + i * 12288, &p.wo, cta < NE_CTAS ? (cta & 3) * 160 + i * 32 : (cta - NE_CTAS) * 32,
                            head * DH, sb + BAR_WO, i == n - 1 ? n * 12288 : 0);
            }
            asm volatile("bar.sync 2, %0;" :: "n"((NWORK + 2) * 32) : "memory");
            uint32_t best[2] = {~0u, ~0u};
#pragma unroll 1
            for (int i = 0; i < NPROBE; i++) {
#pragma unroll
                for (int c = 0; c < 2; c++) {
                    uint32_t t0 = clock(), t1 = t0;
                    int v = 0;
                    draw(v, &g_st.hx.w[c][PROBE], lane == 0);
                    asm volatile("{\n.reg .pred p;\nsetp.ne.u32 p, %1, 0xffffffff;\n@p mov.u32 %0, %%clock;\n}" : "+r"(t1) : "r"(v) : "memory");
                    best[c] = min(best[c], t1 - t0);
                }
                __nanosleep(1000);
            }
            if (lane == 0) sts32f(sb + SM_SIDE, __uint_as_float(best[1] < best[0]));
        }
        int job = cta;
        auto sum_rows = [&](int row_end) {
#pragma unroll 1
            for (; job < 8 * min(row_end, RED0); job += NCTAS) {
                const int row = job >> 3, grp = (job & 7) * 8 + (lane & 7);
                wait_row(row, UPB);
                const float4* src = &g_ring[row % RING][lane >> 3][grp];
                float sx = 0.f, sy = 0.f, sz = 0.f;
#pragma unroll 1
                for (int i = 0; i < 2; i++, src += 64 * 64) {
                    float4 v[16];
#pragma unroll 1
                    for (int it = 0; it < SPIN_MAX; it++) {
                        bool ok = true;
#pragma unroll
                        for (int k = 0; k < 16; k++) v[k] = ld_relaxed_b128(src + k * 4 * 64);
#pragma unroll
                        for (int k = 0; k < 16; k++) ok &= v[k].w == (float)(row + 1);
                        if (all(ok)) break;
                    }
#pragma unroll
                    for (int k = 0; k < 16; k++) { sx += v[k].x; sy += v[k].y; sz += v[k].z; }
                }
#pragma unroll
                for (int o = 8; o < 32; o <<= 1) {
                    sx += __shfl_xor_sync(0xffffffffu, sx, o); sy += __shfl_xor_sync(0xffffffffu, sy, o); sz += __shfl_xor_sync(0xffffffffu, sz, o);
                }
                if (lane < 8) st_relaxed_b128(&g_st.oacc[oidx(row, grp)], sx, sy, sz, UPB);
            }
        };
        const int ho0 = lane / 20 * 256 + lane % 20 * 4, ho1 = (lane + 32) / 20 * 256 + (lane + 32) % 20 * 4, ho2 = 3 * 256 + 16 + 2 * lane;
        uint32_t wr[10] = {};
        float wsum = 0.f;
        if (is_g(cta) && fw == 0) {
#pragma unroll
            for (int i = 0; i < 10; i++) {
                const int w = 4 * lane + 128 * (i >> 2) + (i & 3) - (i >= 8 ? 2 * lane : 0);
                wr[i] = *reinterpret_cast<const uint32_t*>(p.wr + (w >> 4) * 32 + (w & 3) * 8 + ((w >> 1) & 6));
                wsum += lo_f(wr[i]) + hi_f(wr[i]);
            }
            wsum = warp_sum(wsum);
        }
        const int fb = lane >> 3, fg = lane & 7;
        if (fw == 0) {
#pragma unroll
            for (int i = lane; i < DM / 2; i += 32) sts32f(sb + SM_X + 4 * HPITCH + i * 4, __uint_as_float(0x3f803f80u));
        }
        Warm warm;
        float nmean = 0.f, rden = 0.f, sig = 0.f;
#pragma unroll 1
        for (int b = 0; b < NB; b++) {
            const bool ffn = b >= NB - 2;
            if (fw == 0) {
                sum_rows((b + 1) * NH);
                if (ffn) asm volatile("bar.arrive 8, 64;" ::: "memory");
            } else if (ffn) {
                asm volatile("bar.sync 8, 64;" ::: "memory");
                if (b == NB - 1 && (is_f(cta) || is_g(cta) || ALL_LOADERS)) {
                    uint32_t t0 = 0;
#pragma unroll 1
                    for (int it = 0; it < SPIN_MAX; it++) {
                        t0 = ld_relaxed_u32(g_st.fw_time);
                        if (all(t0 != 0)) break;
                        __nanosleep(150);
                    }
                    asm volatile("fence.proxy.async.shared::cta;" ::: "memory");
                    wait_time(t0 + FW_AT_NS);
                    TSW(9);
                    uint32_t t = clock() + (is_f(cta) ? ((fi & 1) * 24 + (fi >> 1)) * FW_GAP / 48 : FW_MID + ((fi & 3) * 10 + (fi >> 2)) * FW_GAP2 / 40);
#pragma unroll 1
                    for (int i = 0; i < 8; i++) {
                        const uint32_t bar = sb + BAR_FW + i * 8;
                        if (is_f(cta)) {
                            wait_clock(t, warm);
                            request_box(sb + SM_W + i * 10240, (i & 1) ? &p.wu : &p.wg, fi * 32, (i >> 1) * 160, bar, 10240);
                            t += FW_GAP;
                        } else if (is_g(cta)) {
                            wait_clock(t, warm);
                            asm volatile("{\n.reg .pred p;\nelect.sync _|p, 0xffffffff;\n"
                                         "@p mbarrier.arrive.expect_tx.shared::cta.b64 _, [%2], 6144;\n"
                                         "@p cp.async.bulk.tensor.4d.shared::cluster.global.mbarrier::complete_tx::bytes [%0], [%1, {%3, %4, %4, %5}], [%2];\n}"
                                         :: "r"(sb + SM_W + i * 6144), "l"(&p.wd), "r"(bar), "r"(fi * 16), "r"(0), "r"(i * 12) : "memory");
                            t += FW_GAP2;
                        }
                    }
                }
                if (is_f(cta)) {
                    const uint32_t* src = &g_st.hx.w[near_side(sb)][min(fb, b) * 256 + 96];
                    float4 m;
#pragma unroll 1
                    for (int it = 0; it < SPIN_MAX; it++) {
                        wait_slot<PH_M>();
                        m = ld_relaxed_f4(src);
                        warm();
                        if (all(m.y + m.w == 2 * (NCTAS - NE_CTAS))) break;
                        if (b < NB - 1) __nanosleep(500);
                    }
                    moments(m.x, m.z, m.x, m.z);
                    sts64f(sb + SM_RED + 5120 + fb * 8, m.x, m.z);
                }
            }
            if (fw == 0 && cta >= NE_CTAS) {
                const int lc = cta - NE_CTAS, col = lc * 32 + 2 * (lane & 15);
                const uint32_t xv = *reinterpret_cast<const uint32_t*>(p.x + b * DM + col);
                uint32_t* dst = &(ffn ? g_st.hx.w : g_st.lx.w + 2)[lane >> 4][(b & 1) * 128 + lc / 5 * 256 + lc % 5 * 16 + (col & 6) * 2 + ((col >> 3) & 3)];
                uint32_t part = sb + SM_RED + (lane & 15) * 8;
                wait_row(b * NH + 28, 1);
                float4 early;
#pragma unroll 1
                for (int it = 0; it < SPIN_MAX; it++) {
                    early = ld_relaxed_f4(&g_st.attn[b][col]);
                    if (all(early.y == NE_CTAS / 4 && early.w == NE_CTAS / 4)) break;
                }
                if (early.x != 1.2345f && lane == 0) TS2(6);
                CK(1, __float_as_uint(early.x));
                const float x0 = -(lo_f(xv) + early.x), x1 = -(hi_f(xv) + early.z);
                fin_sync<4>(after(after(288, x0), x1));
                CK(2, lds32(sb + SM_RED));
                const float2 late = sum8(part, 128);
                const uint32_t hv = nonzero(pack_bf16(x0 - late.x, x1 - late.y));
                st_relaxed(dst, hv);
                if (ffn) st_relaxed(dst + 2048, hv);
                CK(3, 0);
                float m = lane < 16 ? lo_f(hv) + hi_f(hv) : fmaf(lo_f(hv), lo_f(hv), hi_f(hv) * hi_f(hv));
#pragma unroll
                for (int o = 1; o < 16; o <<= 1) m += __shfl_xor_sync(0xffffffffu, m, o);
                if ((lane & 14) == 0) red_f2(reinterpret_cast<float*>(&g_st.hx.w[lane & 1][b * 256 + 96 + (lane >> 4) * 2]), m, 1.f);
                fin_arrive<5>();
            }
            if (fw == 0 && (is_g(cta) || is_f(cta))) {
                const uint32_t* src = &(ffn ? g_st.hx.w : g_st.lx.w + 2)[near_side(sb) ^ (ffn && is_g(cta) ? 3 : 0)][(b & 1) * 128];
                const uint32_t hrow = sb + SM_X + b * HPITCH;
                wait_sum(b == NB - 1 ? (const void*)&g_st.lx.w[near_side(sb) ^ 1][3 * 256] : g_st.lsum[b * NH + NH - 1], UPB, 100);
                wait_clock(clock() + HGATE_NS * 2, warm);
                uint4 h0, h1;
                uint2 h2;
                poll_row(h0, h1, h2, src + ho0, src + ho1, src + ho2, hrow + lane * 16, hrow + 1024 + lane * 8, ffn && lane == 0, b < NB - 1, sb + BAR_H, warm);
                CK(4, h0.x);
                if (is_g(cta)) {
                    const uint32_t hw[10] = {h0.x, h0.y, h0.z, h0.w, h1.x, h1.y, h1.z, h1.w, h2.x, h2.y};
                    float m1 = 0.f, m2 = 0.f, rr = 0.f;
#pragma unroll
                    for (int i = 0; i < 10; i++) {
                        const float v0 = lo_f(hw[i]), v1 = hi_f(hw[i]);
                        m1 += v0 + v1;
                        m2 = fmaf(v0, v0, fmaf(v1, v1, m2));
                        rr = fmaf(v0, lo_f(wr[i]), fmaf(v1, hi_f(wr[i]), rr));
                    }
                    moments(warp_sum(m1), warp_sum(m2), m1, m2);
                    const float sg = bf16r(sigmoid_approx(bf16r((m1 * wsum - warp_sum(rr)) * m2)));
                    if (fb == b) { nmean = m1; rden = m2; sig = sg; }
                    __syncwarp();
                    if (ffn) {
                        const int yj = 2 * (fb & 1) + (fb >> 1);
                        uint32_t ypart = sb + SM_RED2 + yj * 128 + ((fg + 2 * yj) & 7) * 16;
                        __nv_bfloat16* out = p.out + fb * DM + fi * 16 + fg;
                        const float2 hw2 = lds64f(sb + SM_X + fb * HPITCH + ((fi >> 1) * 16 + (fg & 6) * 2 + (fi & 1) * 2) * 4);
                        const uint32_t w0 = __float_as_uint(hw2.x), w1 = __float_as_uint(hw2.y);
                        const float nh0 = (fg & 1) ? hi_f(w0) : lo_f(w0), nh1 = (fg & 1) ? hi_f(w1) : lo_f(w1);
                        const float ln0 = bf16r(bf16r(nmean - nh0) * rden) - nh0, ln1 = bf16r(bf16r(nmean - nh1) * rden) - nh1;
                        pin(ypart); pin(out);
                        fin_sync<6>(after(after(after(288, sig), ln0), ln1));
                        CK(10, lds32(ypart));
                        const float4 ya = sum4x4(ypart, 512), yb = sum4x4(ypart + 2048, 512);
                        const float4 y = make_float4(ya.x + yb.x, ya.y + yb.y, ya.z + yb.z, ya.w + yb.w);
                        const float y0 = -(((fb & 1) ? y.y : y.x) + __shfl_xor_sync(0xffffffffu, (fb & 1) ? y.x : y.y, 8));
                        const float y1 = -(((fb & 1) ? y.w : y.z) + __shfl_xor_sync(0xffffffffu, (fb & 1) ? y.z : y.w, 8));
                        const uint32_t ov = pack_bf16(fmaf(y0, sig, ln0), fmaf(y1, sig, ln1));
                        asm volatile("{\n.reg .pred p;\n.reg .b16 lo, hi;\nsetp.ne.u32 p, %2, 0;\nmov.b32 {lo, hi}, %1;\n"
                                     "@p st.global.u16 [%0], lo;\n@p st.global.u16 [%0+16], hi;\n"
                                     "@p exit;\n"
                                     "}" :: "l"(out), "r"(ov), "r"((uint32_t)(b == NB - 1)) : "memory");
                        CK(11, 0);
                        if (lane == 0) TS2(13);
                    }
                }
            }
            if (is_f(cta) && ffn) {
                const int ks = (2 * fi + fw) % 12;
                const int far = near_side(sb) ^ 1;
                uint32_t* dst = &g_st.ax[ks >> 2].w[(~b & 1) * 2 + far][(fi / 6) * 128 + (ks & 3) * 32 + fb * 8 + (fg & 1) * 4 + ((fg >> 1) ^ (ks & 1))];
                uint32_t* dst2 = dst + (far ? -1024 : 1024);
                uint32_t part = sb + SM_RED + fw * 2560 + fb * 128 + ((fg + (fb & 2)) & 7) * 16;
                uint32_t psum = sb + SM_RED + fw * 2560 + 4 * 128 + ((fg + 4) & 7) * 16;
                pin(dst); pin(part); pin(psum);
                asm volatile("bar.sync 4, 320;" ::: "memory");
                CK(6, lds32(part));
                const float4 d = sum4x4(part, 640), cs = sum4x4(psum, 640);
                const float2 mo = lds64f(sb + SM_RED + 5120 + fb * 8);
                nmean = mo.x; rden = mo.y;
                const float g0 = fmaf(nmean, cs.x, -d.x), g1 = fmaf(nmean, cs.y, -d.y), ke = rden * -1.4426950408889634f, r2 = rden * rden;
                const float p0 = g0 * fmaf(-nmean, cs.z, d.z) * r2, p1 = g1 * fmaf(-nmean, cs.w, d.w) * r2;
                const uint32_t av = nonzero(pack_bf16(p0 * rcp_approx(1.0f + ex2_approx(g0 * ke)), p1 * rcp_approx(1.0f + ex2_approx(g1 * ke))));
                st_relaxed(dst, av);
                st_relaxed(dst2, av);
                CK(7, 0);
            }
        }
        warm.done(sb + SM_SCRAP);
        if (cta == 0 && tid == (NAUX + NWORK) * 32) { g_work[0] = 0; g_work[32] = 0; g_cnt_z[0] = 0; }
        return;
    }
    if (warp >= NAUX) {
        const int wk = warp - NAUX;
        const uint32_t bar = sb + BAR_KV + wk * 8;
        const uint32_t buf = sb + SM_KV + wk * TILE_BYTES;
        uint64_t pol;
        asm volatile("createpolicy.fractional.L2::evict_first.b64 %0, 1.0;" : "=l"(pol));
        const int nstatic = NWORK * grid;
        constexpr int POOL0 = NUNITS - NPOOL;
        int uk = wk * grid + cta;
        wait_time(t_start + K0_AT_NS + uk * KSWEEP_NS / nstatic);
        request_tile(buf, &p.k, uk, bar, pol);
        uint32_t koff[3], voff[3];
        {
            const int r = lane & 7, hf = (lane >> 3) & 1;
            const int kkey = hf ? 8 + (r ^ 1) : r;
            const int vh = lane >> 4;
            const int vkey = ((r & 1) ? 8 : 0) + (vh ? (r ^ 1) : r);
#pragma unroll
            for (int b = 0; b < 3; b++) {
                const int rk = 3 * kkey + b, rv = 3 * vkey + b;
                koff[b] = buf + rk * 128 + (((lane >> 4) ^ (rk & 7)) << 4);
                voff[b] = buf + rv * 128 + ((hf ^ (rv & 7)) << 4);
            }
        }
        uint32_t phase = 0;
        uint32_t qf[12][2];
        auto load_q = [&](int u) {
            const uint32_t* q = g_early[u / UPB].q[0][j];
#pragma unroll
            for (int i = 0; i < 4; i++) {
                const uint4 a = ld_relaxed_v4(q + i * 32);
                const float2 c = ld_relaxed_f2(q + i * 32 + 4);
                qf[3 * i][0] = a.x; qf[3 * i][1] = a.y; qf[3 * i + 1][0] = a.z; qf[3 * i + 1][1] = a.w;
                qf[3 * i + 2][0] = __float_as_uint(c.x); qf[3 * i + 2][1] = __float_as_uint(c.y);
            }
        };
        load_q(uk);
        int uq[LAG];
        uint32_t sq[LAG];
#pragma unroll
        for (int i = 0; i < LAG; i++) { uq[i] = ~unit_of(uk + (i + 1) * nstatic); sq[i] = 0; }
        uint4 mv = make_uint4(0u, 0u, 0u, 0u);
        float freed = UPB;
        while (true) {
            const int uv = uq[0];
            uint32_t sv = sq[0];
#pragma unroll
            for (int i = 0; i + 1 < LAG; i++) { uq[i] = uq[i + 1]; sq[i] = sq[i + 1]; }
            uq[LAG - 1] = uk;
            if (uk < NUNITS) {
                PH(7);
#pragma unroll 1
                for (int it = 0; it < SPIN_MAX; it++) {
                    uint32_t lo = 0xffffffffu;
#pragma unroll
                    for (int i = 0; i < 12; i++) lo = min(lo, min(qf[i][0], qf[i][1]));
                    if (all(lo != 0)) break;
                    __nanosleep(250);
                    load_q(uk);
                }
                mbar_wait(bar, phase); phase ^= 1;
                PH(0); ARR();
                TSI(0, 16); TSI(1, 18);
                float acc[2][4][4] = {};
#pragma unroll
                for (int ks = 0; ks < 12; ks++) {
#pragma unroll
                    for (int mt = 0; mt < 4; mt++) {
                        uint32_t a[4];
                        ldsm4(a, (koff[ks >> 2] ^ ((ks & 3) << 5)) + mt * 6144);
                        mma16816(acc[ks & 1][mt], a, qf[ks][0], qf[ks][1]);
                    }
                }
                PH(1);
                TSI(0, 17); TSI(1, 19);
                if (uk < nstatic) wait_time(t_start + K1_AT_NS + uk * KSWEEP_NS / nstatic);
                if (uv < NUNITS) request_tile(buf, uv >= 0 ? &p.v : &p.k, uv >= 0 ? uv : ~uv, bar, pol);
                const float sa = sel4(j, acc[0][0][0], acc[0][1][0], acc[0][2][0], acc[0][3][0]) + sel4(j, acc[1][0][0], acc[1][1][0], acc[1][2][0], acc[1][3][0]);
                const float sc = sel4(j, acc[0][0][2], acc[0][1][2], acc[0][2][2], acc[0][3][2]) + sel4(j, acc[1][0][2], acc[1][1][2], acc[1][2][2], acc[1][3][2]);
                const uint32_t raw = pack_bf16(sa, sc);
                const float scale = -0.07216878364870322f;
                const uint32_t sk = pack_bf16(lo_f(raw) * scale, hi_f(raw) * scale);
                sq[LAG - 1] = sk;
                if (uk >= POOL0) st_relaxed(&g_st.score[uk - POOL0][lane], sk ? sk : 0x80008000u);
                int a = (int)(sk << 16), b = (int)(sk & 0xffff0000u);
                a ^= (a >> 31) & 0x7fff0000; b ^= (b >> 31) & 0x7fff0000;
                const int mx = __reduce_max_sync(0xffffffffu, max(a, b));
                if (lane == 0) st_relaxed(&g_early[uk / UPB].umax[uk % UPB], (uint32_t)mx | 1u);
            }
            if (uv < 0) {
                uk = ~uv;
                load_q(uk);
                continue;
            }
            if (uv >= NUNITS) break;
            const int bh = uv / UPB;
#pragma unroll 1
            for (int it = 0; it < SPIN_MAX; it++) {
                if (all((mv.x & mv.y & mv.z & mv.w & 1u) && (uv < POOL0 || sv != 0) && freed == UPB)) break;
                mv = ld_relaxed_v4(&g_early[bh].umax[lane * 4]);
                if (bh >= RING && bh < RED0) freed = __uint_as_float(ld_relaxed_u32(&g_st.oacc[oidx(bh - RING, (lane & 7) * 8)].w));
                if (uv >= POOL0) sv = ld_relaxed_u32(&g_st.score[uv - POOL0][lane]);
            }
            PH(2); CK(8, sv);
            int un = NUNITS, vn = 0;
            draw(un, g_work, uk < NUNITS && lane == 0);
            uint32_t tdraw;
            asm volatile("mov.u32 %0, %%globaltimer_lo;" : "=r"(tdraw));
            draw(vn, g_work + 32, uq[0] >= POOL0 && lane == 0);
            int mx = __reduce_max_sync(0xffffffffu, max(max((int)mv.x, (int)mv.y), max((int)mv.z, (int)mv.w))) & 0xffff0000;
            mx ^= (mx >> 31) & 0x7fff0000;
            const float m = __int_as_float(mx);
            const float l2e = 1.4426950408889634f;
            const uint32_t pp = pack_bf16(exp2f((lo_f(sv) - m) * l2e), exp2f((hi_f(sv) - m) * l2e));
            uint32_t pb[8];
#pragma unroll
            for (int t = 0; t < 4; t++) {
                pb[2 * t] = __shfl_sync(0xffffffffu, pp, 8 * j + t);
                pb[2 * t + 1] = __shfl_sync(0xffffffffu, pp, 8 * j + 4 + t);
            }
            float lacc[4] = {};
            const uint32_t ones[4] = {0x3f803f80u, 0x3f803f80u, 0x3f803f80u, 0x3f803f80u};
#pragma unroll
            for (int t = 0; t < 4; t++) mma16816(lacc, ones, pb[2 * t], pb[2 * t + 1]);
            if (uv < nstatic) {
                asm volatile("bar.sync 2, %0;" :: "n"((NWORK + 2) * 32) : "memory");
                TSW(3);
            }
            const int grp = 16 * j + 4 * (g & 1) + (g >> 1);
            uint32_t mode = (bh >= RED0) + (bh >= NBH - 4);
            float tag = mode ? 1.f : (float)(bh + 1), tag2 = fmaf(__uint_as_float(voff[0]), 0.f, tag);
            void* dst = mode == 0 ? (void*)&g_ring[bh % RING][uv % UPB][grp] :
                        mode == 1 ? (void*)&g_st.oacc[oidx(bh, grp)] : (void*)&g_st.ox[0].w[uv % OREP * 2 + (~(near_side(sb) ^ uv % OREP) & 1)][oidx(bh & 3, grp) * 4];
            if (mode == 2 && lane < 2) red_f2(reinterpret_cast<float*>(&g_st.lx.w[lane][(bh & 3) * 256]), lacc[0], 1.f);
            CK(10, __float_as_uint(lacc[0]));
            un = __shfl_sync(0xffffffffu, un, 0) + (LAG + 1) * nstatic;
            un = unit_of(un);
            vn = __shfl_sync(0xffffffffu, vn, 0);
            if (uq[0] >= POOL0) uq[0] = unit_of(POOL0 + vn);
            if (vn == FW_TICKET && lane == 0) st_relaxed(g_st.fw_time, tdraw | 1u);
            if (uq[0] < NUNITS && un >= NUNITS) {
                mv = ld_relaxed_v4(&g_early[uq[0] / UPB].umax[lane * 4]);
                if (uq[0] < RED0 * UPB) freed = 0.f;
                if (uq[0] >= POOL0) sq[0] = ld_relaxed_u32(&g_st.score[uq[0] - POOL0][lane]);
            }
            pin(dst); pin(mode); pin(tag); pin(tag2); pin(voff[0]); pin(voff[1]); pin(voff[2]);
            PH(3); CK(9, vn);
            mbar_wait(bar, phase); phase ^= 1;
            PH(4); ARR(); CK(12, lds32(buf));
            float acc[12][4] = {};
#pragma unroll
            for (int t = 0; t < 4; t++) {
#pragma unroll
                for (int mt = 0; mt < 12; mt++) {
                    uint32_t a[4];
                    ldsm4t(a, (voff[mt >> 2] ^ ((mt & 3) << 5)) + t * 6144);
                    mma16816(acc[mt], a, pb[2 * t], pb[2 * t + 1]);
                }
            }
            PH(5);
            if (lane == 0) PROG(un);
            if (un < NUNITS || uq[0] < NUNITS) request_tile(buf, un < NUNITS ? &p.k : &p.v, un < NUNITS ? un : uq[0], bar, pol);
            if (un < NUNITS || uq[0] < NUNITS) CK(11, 0);
            float o[6];
#pragma unroll
            for (int e = 0; e < 6; e++) {
                const int q = e % 3, c = (e / 3) * 2;
                o[e] = sel4(j, acc[q][c], acc[3 + q][c], acc[6 + q][c], acc[9 + q][c]);
            }
            put_groups(dst, mode, o, tag, tag2);
            CK(13, 0);
            if (un < NUNITS) load_q(un);
            if (lane == 0) red_f2(&g_st.lsum[bh][0].x, lacc[0], 1.f);
            PH(6);
            if (uq[0] >= NUNITS && un >= NUNITS) break;
            uk = un;
            if (uq[0] < NUNITS && un < NUNITS) {
                const int nb = uq[0] / UPB;
                mv = ld_relaxed_v4(&g_early[nb].umax[lane * 4]);
                freed = nb >= RING && nb < RED0 ? __uint_as_float(ld_relaxed_u32(&g_st.oacc[oidx(nb - RING, (lane & 7) * 8)].w)) : UPB;
                if (uq[0] >= POOL0) sq[0] = ld_relaxed_u32(&g_st.score[uq[0] - POOL0][lane]);
            }
        }
        TSW(4 + wk);
        return;
    }

    __nv_bfloat16* xs = reinterpret_cast<__nv_bfloat16*>(smem + SM_X);
    float* red = reinterpret_cast<float*>(smem + SM_RED);
    const int frow = (lane & 7) + ((lane >> 4) << 3), fcol = (lane >> 3) & 1;
    const uint32_t f64b = sb + (frow * 4 + (fcol ^ ((frow >> 1) & 3))) * 16;
    if (cta < NQ_CTAS) {
        TS(26);
        if (warp >= 4) {
            uint2 xr[5];
#pragma unroll
            for (int i = 0; i < 5; i++) xr[i] = *reinterpret_cast<const uint2*>(p.x + (warp - 4) * DM + i * 128 + lane * 4);
            float v[20];
#pragma unroll
            for (int i = 0; i < 5; i++) {
                v[4 * i] = lo_f(xr[i].x); v[4 * i + 1] = hi_f(xr[i].x); v[4 * i + 2] = lo_f(xr[i].y); v[4 * i + 3] = hi_f(xr[i].y);
            }
            layernorm20(v);
#pragma unroll
            for (int i = 0; i < 5; i++)
                *reinterpret_cast<uint2*>(xs + (warp - 4) * XPITCH + i * 128 + lane * 4) =
                    make_uint2(pack_bf16(v[4 * i], v[4 * i + 1]), pack_bf16(v[4 * i + 2], v[4 * i + 3]));
        }
        aux_sync();
        TS(27);
        mbar_wait(sb + BAR_WQ + (warp >> 1) * 8, 0);
        TS(1);
        const uint32_t xfrag = sb + SM_X + ((g & 3) * XPITCH + 2 * j) * 2;
        float acc[3][4] = {};
#pragma unroll
        for (int s = 0; s < 5; s++) {
            const int ks = warp * 5 + s;
            const uint32_t b0 = lds32(xfrag + ks * 32), b1 = lds32(xfrag + ks * 32 + 16);
            const int row = ks * 16 + frow;
#pragma unroll
            for (int mt = 0; mt < 3; mt++) {
                uint32_t a[4];
                ldsm4t(a, sb + SM_W + (row * 6 + 2 * mt + fcol) * 16);
                mma16816(acc[mt], a, b0, b1);
            }
        }
        if (j < 2) {
#pragma unroll
            for (int mt = 0; mt < 3; mt++) {
                *reinterpret_cast<float2*>(red + warp * 216 + mt * 72 + g * 4 + 2 * j) = make_float2(acc[mt][0], acc[mt][1]);
                *reinterpret_cast<float2*>(red + warp * 216 + mt * 72 + 36 + g * 4 + 2 * j) = make_float2(acc[mt][2], acc[mt][3]);
            }
        }
        aux_sync();
        if (warp < 4) {
            const float* src = red + min(g, 5) * 36 + warp * 8 + j;
            float s0 = 0.f, s1 = 0.f;
#pragma unroll
            for (int w = 0; w < 8; w++) { s0 += src[w * 216]; s1 += src[w * 216 + 4]; }
            st_relaxed(&g_early[j * NH + (cta >> 2)].q[cta & 3][warp][g], pack_neg(s0, s1));
        }
        TS(28);
    }
    fin_sync<3>();
    mbar_wait(sb + BAR_WO, 0);
    TS(7);
    uint32_t part = sb + SM_RED + (warp * 32 + 8 * j + g) * 4;

#pragma unroll 1
    for (int b = 0; b < NB; b++) {
        if (cta >= NE_CTAS) {
            uint32_t a[6][2][4];
#pragma unroll
            for (int s = 0; s < 6; s++) {
#pragma unroll
                for (int mt = 0; mt < 2; mt++) ldsm4t(a[s][mt], (f64b ^ (mt * 32)) + SM_A + (warp * 6 + s) * 1024);
            }
            const int bh = b * NH + 28 + (warp >> 1);
            const int side = near_side(sb) ^ 1;
            const void* osrc[OREP];
#pragma unroll
            for (int c = 0; c < OREP; c++)
                osrc[c] = b == NB - 1 ? (const void*)&g_st.ox[c >> 1].w[side ^ (c & 1) * 3][oidx(bh & 3, (warp & 1) * 32 + lane) * 4] : &g_st.oacc[oidx(bh, (warp & 1) * 32 + lane)];
            const void* lsrc = b == NB - 1 ? (const void*)&g_st.lx.w[side][(bh & 3) * 256] : g_st.lsum[bh];
            wait_row_o(bh, 1);
            const float rl = rcp_approx(wait_sum(lsrc, UPB)) * (b == NB - 1 ? 1.f : 1.f / OREP), full = b == NB - 1 ? UPB : UPB * OREP;
            float4 ov;
            float px, py, pz;
            Warm warm;
#pragma unroll 1
            for (int it = 0; it < SPIN_MAX; it++) {
                wait_slot<PH_O>();
                float4 oc[OREP];
#pragma unroll
                for (int c = 0; c < OREP; c++) oc[c] = ld_relaxed_f4(osrc[c]);
                warm();
                ov = oc[0];
#pragma unroll
                for (int c = 1; c < OREP; c++) { ov.x += oc[c].x; ov.y += oc[c].y; ov.z += oc[c].z; ov.w += oc[c].w; }
                ov.x *= rl; ov.y *= rl; ov.z *= rl;
                px = __shfl_xor_sync(0xffffffffu, ov.x, 4); py = __shfl_xor_sync(0xffffffffu, ov.y, 4); pz = __shfl_xor_sync(0xffffffffu, ov.z, 4);
                if (all(ov.w == full)) break;
            }
            CK(0, __float_as_uint(ov.x));
            if (ov.x != 1.2345f && warp == 7) TSW(14);
            const uint32_t w[3] = {pack_bf16(ov.x, px), pack_bf16(ov.y, py), pack_bf16(ov.z, pz)};
            float acc[2][2][4] = {};
#pragma unroll
            for (int s = 0; s < 6; s++) {
                const uint32_t b0 = __shfl_sync(0xffffffffu, w[s % 3], (s / 3) * 16 + j);
                const uint32_t b1 = __shfl_sync(0xffffffffu, w[s % 3], (s / 3) * 16 + 8 + j);
#pragma unroll
                for (int mt = 0; mt < 2; mt++) mma16816(acc[mt][s & 1], a[s][mt], b0, b1);
            }
            sts32f(part, sel4(j, acc[0][0][0] + acc[0][1][0], acc[0][0][2] + acc[0][1][2], acc[1][0][0] + acc[1][1][0], acc[1][0][2] + acc[1][1][2]));
            CK(1, 0);
            fin_arrive<4>();
            warm.done(sb + SM_SCRAP);
            fin_sync<5>();
            if (cta < NE_CTAS + 4 && tid < 64) reinterpret_cast<uint4*>(&g_early[b * NH + 28 + cta - NE_CTAS])[tid] = make_uint4(0u, 0u, 0u, 0u);
        } else {
            const int bh = b * NH + (cta >> 2);
            if (warp == 0) wait_row_o(bh, UPB);
            aux_sync();
            if (warp < 5) {
                uint32_t ob[12][2];
                load_o<4>(ob, bh, 0, j);
                float acc[2][2][4] = {};
#pragma unroll
                for (int ks = 0; ks < 12; ks++) {
#pragma unroll
                    for (int mt = 0; mt < 2; mt++) {
                        uint32_t a[4];
                        ldsm4t(a, (f64b ^ (mt * 32)) + SM_A + warp * 12288 + ks * 1024);
                        mma16816(acc[mt][ks & 1], a, ob[ks][0], ob[ks][1]);
                    }
                }
                red_f2(&g_st.attn[b][(cta & 3) * 160 + warp * 32 + 8 * j + g].x,
                       sel4(j, acc[0][0][0] + acc[0][1][0], acc[0][0][2] + acc[0][1][2], acc[1][0][0] + acc[1][1][0], acc[1][0][2] + acc[1][1][2]), 1.f);
                TS(8);
            } else if (warp > 5 && (cta & 3) == 0) {
                reinterpret_cast<uint4*>(&g_early[bh])[tid - 192] = make_uint4(0u, 0u, 0u, 0u);
            }
        }
        if (b < NB - 2) continue;

        if (is_f(cta)) {
            uint32_t ga[10][2][4];
            uint4 hv[5];
            const uint32_t hfrag = sb + SM_X + min(g, 4) * HPITCH + ((warp >> 1) * 80 + 4 * j) * 4;
            if (b == NB - 1) mbar_wait(sb + BAR_FW + warp * 8, 0);
            if (warp == 7) TSW(10);
            CK(12, lds32(sb + SM_W));
#pragma unroll
            for (int s = 0; s < 10; s++) {
#pragma unroll
                for (int mt = 0; mt < 2; mt++) ldsm4t(ga[s][mt], (f64b ^ (mt * 32)) + SM_W + (warp * 10 + s) * 1024);
            }
            const uint32_t gpart = sb + SM_RED + (warp >> 1) * 640 + j * 256 + ((g + 2 * j) & 7) * 16 + (warp & 1) * 8;
            mbar_wait(sb + BAR_H, b & 1);
#pragma unroll
            for (int s = 0; s < 5; s++) hv[s] = lds128(hfrag + s * 64);
            CK(4, hv[0].x);
            float acc[2][2][4] = {};
#pragma unroll
            for (int s = 0; s < 10; s++) {
#pragma unroll
                for (int mt = 0; mt < 2; mt++)
                    mma16816(acc[mt][s & 1], ga[s][mt], (s & 1) ? hv[s >> 1].z : hv[s >> 1].x, (s & 1) ? hv[s >> 1].w : hv[s >> 1].y);
            }
#pragma unroll
            for (int mt = 0; mt < 2; mt++) {
                if (j < 3) sts64f(gpart + mt * 2560, acc[mt][0][0] + acc[mt][1][0], acc[mt][0][2] + acc[mt][1][2]);
                if (j < 2) sts64f(gpart + mt * 2560 + 128, acc[mt][0][1] + acc[mt][1][1], acc[mt][0][3] + acc[mt][1][3]);
            }
            CK(5, 0);
            asm volatile("bar.arrive 4, 320;" ::: "memory");
        } else if (is_g(cta)) {
            const uint32_t* asrc = &g_st.ax[0].w[(~b & 1) * 2 + near_side(sb)][warp * 128 + ((g >> 2) * 2 + (j >> 1)) * 32 + (g & 3) * 8 + (j & 1) * 4];
            const uint32_t ypart = sb + SM_RED2 + warp * 512 + j * 128 + ((g + 2 * j) & 7) * 16;
            uint32_t wb[12][4];
            uint4 va[3] = {};
            uint32_t lo[3] = {};
            auto ask = [&]() {
#pragma unroll
                for (int i = 0; i < 3; i++) ld_relaxed_v4_if(va[i], asrc + i * 4096, lo[i] == 0);
            };
            auto complete = [&]() {
#pragma unroll
                for (int i = 0; i < 3; i++) lo[i] = min(min(va[i].x, va[i].y), min(va[i].z, va[i].w));
                return all(min(lo[0], min(lo[1], lo[2])) != 0);
            };
            const int jj = (lane & 7) >> 1, q = jj >> 1, hi = lane >> 4;
            const uint32_t wsrc = sb + SM_W + warp * 6144 + q * 512 + ((hi ^ q) * 4 + (jj & 1) * 2 + (lane & 1)) * 32 + ((fcol ^ hi ^ q) << 4);
            mbar_wait(sb + BAR_H, b & 1);
            if (b == NB - 1) mbar_wait(sb + BAR_FW + warp * 8, 0);
            if (warp == 7) TSW(11);
            CK(13, lds32(sb + SM_W));
            ask();
#pragma unroll
            for (int s = 0; s < 12; s++) ldsm4t(wb[s], wsrc + (s >> 2) * 2048 + (s & 1) * 1024 + (s & 2) * 128);
            Warm warm;
            if (!complete()) {
#pragma unroll 1
                for (int it = 0; it < SPIN_MAX; it++) {
                    ask();
                    warm();
                    if (complete()) break;
                }
            }
            CK(8, va[0].x);
            if (va[0].x != 0x12345 && warp == 7) TSW(15);
            float acc[6][4] = {};
#pragma unroll
            for (int s = 0; s < 12; s++) {
                const uint4 v = va[s >> 2];
                mma16816(acc[s % 6], wb[s], (s & 2) ? v.z : v.x, (s & 2) ? v.w : v.y);
            }
            float y[4];
#pragma unroll
            for (int e = 0; e < 4; e++) y[e] = j < 2 ? (acc[0][e] + acc[2][e]) + acc[4][e] : (acc[1][e] + acc[3][e]) + acc[5][e];
            sts128f(ypart, y[0], y[1], y[2], y[3]);
            CK(9, 0);
            fin_arrive<6>();
            warm.done(sb + SM_SCRAP);
        }
    }
}

typedef CUresult (*EncodeFn)(CUtensorMap*, CUtensorMapDataType, cuuint32_t, void*, const cuuint64_t*, const cuuint64_t*,
                             const cuuint32_t*, const cuuint32_t*, CUtensorMapInterleave, CUtensorMapSwizzle,
                             CUtensorMapL2promotion, CUtensorMapFloatOOBfill);

CUtensorMap make_map(EncodeFn enc, void* ptr, uint64_t cols, uint64_t rows, uint32_t bcols, uint32_t brows,
                     CUtensorMapSwizzle sw, CUtensorMapL2promotion promo) {
    CUtensorMap m;
    const cuuint64_t dims[2] = {cols, rows};
    const cuuint64_t strides[1] = {cols * 2};
    const cuuint32_t box[2] = {bcols, brows};
    const cuuint32_t es[2] = {1, 1};
    enc(&m, CU_TENSOR_MAP_DATA_TYPE_BFLOAT16, 2, ptr, dims, strides, box, es, CU_TENSOR_MAP_INTERLEAVE_NONE, sw, promo,
        CU_TENSOR_MAP_FLOAT_OOB_FILL_NONE);
    return m;
}

}

extern "C" void kernel_launch(void* const* d_in, const int* in_sizes, int n_in, void* d_out, int out_size) {
    (void)in_sizes; (void)n_in; (void)out_size;
    static EncodeFn enc = nullptr;
    static int sms = 0;
    if (!enc) {
        cudaDriverEntryPointQueryResult qr;
        cudaGetDriverEntryPoint("cuTensorMapEncodeTiled", (void**)&enc, cudaEnableDefault, &qr);
        int dev = 0;
        cudaGetDevice(&dev);
        cudaDeviceGetAttribute(&sms, cudaDevAttrMultiProcessorCount, dev);
        cudaFuncSetAttribute(fused_decode_kernel, cudaFuncAttributeMaxDynamicSharedMemorySize, SM_TOTAL);
    }
    if (sms < NCTAS) return;
    const CUtensorMapL2promotion WPROMO = CU_TENSOR_MAP_L2_PROMOTION_L2_128B;
    Params p;
    p.k = make_map(enc, d_in[1], 64, (uint64_t)NBH * SK * 3, 64, TILE_ROWS, CU_TENSOR_MAP_SWIZZLE_128B, CU_TENSOR_MAP_L2_PROMOTION_NONE);
    p.v = make_map(enc, d_in[2], 64, (uint64_t)NBH * SK * 3, 64, TILE_ROWS, CU_TENSOR_MAP_SWIZZLE_128B, CU_TENSOR_MAP_L2_PROMOTION_NONE);
    p.wq = make_map(enc, d_in[3], NH * DH, DM, 48, 160, CU_TENSOR_MAP_SWIZZLE_NONE, WPROMO);
    p.wo = make_map(enc, d_in[4], DM, NH * DH, 32, DH, CU_TENSOR_MAP_SWIZZLE_64B, WPROMO);
    p.wg = make_map(enc, d_in[7], FF, DM, 32, 160, CU_TENSOR_MAP_SWIZZLE_64B, WPROMO);
    p.wu = make_map(enc, d_in[8], FF, DM, 32, 160, CU_TENSOR_MAP_SWIZZLE_64B, WPROMO);
    {
        const cuuint64_t dims[4] = {DM, 2, 8, FF / 16}, strides[3] = {8 * DM * 2, DM * 2, 16 * DM * 2};
        const cuuint32_t box[4] = {16, 2, 8, 12}, es[4] = {1, 1, 1, 1};
        enc(&p.wd, CU_TENSOR_MAP_DATA_TYPE_BFLOAT16, 4, d_in[9], dims, strides, box, es, CU_TENSOR_MAP_INTERLEAVE_NONE,
            CU_TENSOR_MAP_SWIZZLE_32B, WPROMO, CU_TENSOR_MAP_FLOAT_OOB_FILL_NONE);
    }
    p.x = (const __nv_bfloat16*)d_in[0];
    p.wr = (const __nv_bfloat16*)d_in[6];
    p.out = (__nv_bfloat16*)d_out;
    fused_decode_kernel<<<NCTAS, NTHREADS, SM_TOTAL, cudaStreamPerThread>>>(p);
}
```

```cpp
#include <cuda_runtime.h>
#include <cuda_bf16.h>
#include <cuda.h>
#include <stdint.h>

namespace {

constexpr int NB = 4, NH = 32, SK = 8192, DH = 192, DM = 640, FF = 1536;
constexpr int NBH = NB * NH;
constexpr int TILE = 64;
constexpr int UPB = SK / TILE;
constexpr int NUNITS = NBH * UPB;
constexpr int TILE_BYTES = TILE * DH * 2;
constexpr int TILE_ROWS = TILE * 3;
constexpr int NCTAS = 132;
constexpr int NQ_CTAS = 128;
constexpr int NE_CTAS = 112;
__host__ __device__ constexpr bool is_f(int cta) { return cta < NE_CTAS && cta % 14 < 11 && !(cta & 1); }
__host__ __device__ constexpr bool is_g(int cta) { return cta < NE_CTAS && cta % 14 < 11 && (cta & 1); }
__host__ __device__ constexpr int ffn_slice(int cta) { return cta / 14 * ((cta & 1) ? 5 : 6) + cta % 14 / 2; }

#define NWORK 2
#define LAG 3
#define NPOOL 896
#define RED0 116
#define RING 12
#define OREP 2
#define K0_AT_NS 1150
#define WO_AT_NS (K0_AT_NS + 2000)
#define K1_AT_NS (K0_AT_NS + 4400)
#define WO_STEP_NS 75
#define CLEAR_AT_NS 7000
constexpr int KSWEEP_NS = 2000;
#define FW_TICKET (NPOOL + 32)
#define FW_AT_NS 2090
#define FW_GAP 280
#define FW_MID 2100
#define FW_GAP2 200
#define HGATE_NS 700
#define SLOT_TICKS 9
#define SLOT_OPEN 3
#define PH_O 0
#define PH_H 8
#define PH_M 2
#define NPROBE 24
#define MIX_R 6
#define MIX_FROM 1
#define MIX_ROWS 3
constexpr int MIX = MIX_ROWS * UPB, MIX1 = (NBH - 4) * UPB, MIX0 = MIX1 - (MIX1 - MIX_FROM * NWORK * NCTAS) / MIX * MIX;
static_assert((MIX1 - (NUNITS - NPOOL)) % MIX == 0, "the pool starts with a group of rows");
__device__ __forceinline__ int unit_of(int t) {
    const unsigned r = (unsigned)(t - MIX0) % MIX, e = t - MIX1;
    if (e < 4 * UPB) return MIX1 + (e & 256) + (e & 3) * 64 + (e & 255) / 4;
    return t < MIX0 || t >= MIX1 ? t : t - r + r % MIX_R * (MIX / MIX_R) + r / MIX_R;
}
static_assert(FW_TICKET < NPOOL + NWORK * NCTAS, "every worker draws one ticket beyond the pool");
constexpr int NAUX = 8;
constexpr int NTHREADS = (NAUX + NWORK + 2) * 32;
constexpr int SPIN_MAX = 1 << 22;

constexpr int SM_KV = 0;
constexpr int SM_A = SM_KV + NWORK * TILE_BYTES;
constexpr int SM_W = SM_A + 61440;
constexpr int SM_X = SM_W + 81920;
constexpr int XPITCH = 648;
constexpr int HPITCH = 1344;
constexpr int SM_RED = SM_X + 5 * HPITCH + 64;
constexpr int SM_RED2 = SM_RED + 8 * 48 * 4 * 4;
constexpr int SM_MISC = SM_RED2 + 4096;
constexpr int BAR_WQ = SM_MISC, SM_SCRAP = SM_MISC + 32, BAR_WO = SM_MISC + 40, SM_SIDE = SM_MISC + 48, BAR_H = SM_MISC + 56, BAR_FW = SM_MISC + 64;
constexpr int BAR_KV = BAR_FW + 64;
constexpr int SM_TOTAL = BAR_KV + NWORK * 8;
static_assert(SM_W % 1024 == 0 && NB * XPITCH * 2 <= 4 * HPITCH && SM_RED % 128 == 0, "smem layout");

struct Params {
    CUtensorMap k, v;
    CUtensorMap wq;
    CUtensorMap wo;
    CUtensorMap wg, wu;
    CUtensorMap wd;
};

struct Early {
    uint32_t q[4][4][8];
    uint32_t umax[UPB];
};
struct Twin { uint32_t w[4][1024]; };
constexpr int PROBE = 1024 - 32;
#define LSTRIDE 16
struct State {
    Twin ax[3];
    Twin hx;
    Twin ox[(OREP + 1) / 2];
    Twin lx;
    float4 oacc[NBH * 64];
    float2 attn[NB][DM];
    uint32_t fw_time[32];
    float2 lsum[NBH][LSTRIDE];
    uint32_t score[NPOOL][32];
};
__host__ __device__ constexpr int oidx(int row, int grp) {
    return (row >> 2) * 256 + ((row & 1) * 2 + (grp >> 5)) * 64 + (row & 2) * 16 + (grp & 31);
}
constexpr int STATE_V4 = ((sizeof(State) / 32 + NQ_CTAS - 1) / NQ_CTAS) * 2;
static_assert(sizeof(State) % 32 == 0, "State is cleared in whole sectors");
static_assert(sizeof(Early) == 64 * 16, "an Early entry is cleared by 64 threads");
struct Scratch {
    State st;
    unsigned work[64];
    unsigned cnt_z[32];
    Early early[NBH];
    alignas(4096) float4 ring[RING][UPB][64];
};
constexpr size_t PAGE = 2u << 20;
static_assert(sizeof(Scratch) <= PAGE, "scratch must fit one page");
__device__ __align__(128) unsigned char g_raw[2 * PAGE];
#define g_early scr->early
#define g_st scr->st
#define g_ring scr->ring
#define g_cnt_z scr->cnt_z
#define g_work scr->work
#define ALL_LOADERS 0
#define TS(i)
#define TSW(i)
#define TS2(i)
#define TSI(n, i)
#define PH(i)
#define CK(i, dep)
#define ARR()
#define PROG(u)

__device__ __forceinline__ uint32_t s2u(const void* p) { return (uint32_t)__cvta_generic_to_shared(p); }
__device__ __forceinline__ void mbar_init(uint32_t bar, int cnt) {
    asm volatile("mbarrier.init.shared::cta.b64 [%0], %1;" :: "r"(bar), "r"(cnt) : "memory");
}
__device__ __forceinline__ void mbar_wait(uint32_t bar, uint32_t parity) {
    asm volatile("{\n.reg .pred p;\n.reg .u32 n;\nmov.u32 n, 0;\nWAIT_LOOP:\n"
                 "mbarrier.try_wait.parity.shared::cta.b64 p, [%0], %1;\n"
                 "@p bra WAIT_DONE;\nadd.u32 n, n, 1;\nsetp.lt.u32 p, n, %2;\n@p bra WAIT_LOOP;\nWAIT_DONE:\n}"
                 :: "r"(bar), "r"(parity), "n"(SPIN_MAX) : "memory");
}
__device__ __forceinline__ void request_tile(uint32_t dst, const CUtensorMap* tm, int unit, uint32_t bar, uint64_t pol) {
    asm volatile("{\n.reg .pred p;\nelect.sync _|p, 0xffffffff;\n"
                 "@p mbarrier.arrive.expect_tx.shared::cta.b64 _, [%2], %6;\n"
                 "@p cp.async.bulk.tensor.2d.shared::cluster.global.mbarrier::complete_tx::bytes.L2::cache_hint "
                 "[%0], [%1, {%3, %4}], [%2], %5;\n}"
                 :: "r"(dst), "l"(tm), "r"(bar), "r"(0), "r"(unit * TILE_ROWS), "l"(pol), "n"(TILE_BYTES) : "memory");
}
__device__ __forceinline__ void put_groups(void* dst, int mode, const float (&o)[6], float tag, float tag2) {
    asm volatile("{\n.reg .pred s, t;\n.reg .b128 u, v;\n.reg .b64 a, b;\n"
                 "setp.eq.s32 s, %1, 0;\nsetp.ne.s32 t, %1, 2;\nxor.b64 a, %0, 4096;\n"
                 "@t bra.uni SINGLE;\n"
                 "red.relaxed.gpu.global.add.v4.f32 [a], {%2,%3,%4,%8};\n"
                 "red.relaxed.gpu.global.add.v4.f32 [a+128], {%5,%6,%7,%9};\n"
                 "SINGLE:\n"
                 "@s bra.uni STORE;\n"
                 "red.relaxed.gpu.global.add.v4.f32 [%0], {%2,%3,%4,%8};\n"
                 "red.relaxed.gpu.global.add.v4.f32 [%0+128], {%5,%6,%7,%9};\n"
                 "STORE:\n"
                 "mov.b64 a, {%2, %3};\nmov.b64 b, {%4, %8};\nmov.b128 u, {a, b};\n"
                 "mov.b64 a, {%5, %6};\nmov.b64 b, {%7, %9};\nmov.b128 v, {a, b};\n"
                 "@s st.relaxed.gpu.global.b128 [%0], u;\n@s st.relaxed.gpu.global.b128 [%0+128], v;\n}"
                 :: "l"(dst), "r"(mode), "f"(o[0]), "f"(o[1]), "f"(o[2]), "f"(o[3]), "f"(o[4]), "f"(o[5]), "f"(tag), "f"(tag2) : "memory");
}
__device__ __forceinline__ void request_box(uint32_t dst, const CUtensorMap* tm, int col, int row, uint32_t bar, uint32_t bytes) {
    asm volatile("{\n.reg .pred p, q;\nelect.sync _|p, 0xffffffff;\nsetp.ne.and.u32 q, %5, 0, p;\n"
                 "@q mbarrier.arrive.expect_tx.shared::cta.b64 _, [%2], %5;\n"
                 "@p cp.async.bulk.tensor.2d.shared::cluster.global.mbarrier::complete_tx::bytes [%0], [%1, {%3, %4}], [%2];\n}"
                 :: "r"(dst), "l"(tm), "r"(bar), "r"(col), "r"(row), "r"(bytes) : "memory");
}
__device__ __forceinline__ uint32_t lds32(uint32_t addr) {
    uint32_t v;
    asm volatile("ld.shared.u32 %0, [%1];" : "=r"(v) : "r"(addr) : "memory");
    return v;
}
__device__ __forceinline__ void ldsm4(uint32_t (&r)[4], uint32_t addr) {
    asm volatile("ldmatrix.sync.aligned.m8n8.x4.shared.b16 {%0,%1,%2,%3}, [%4];"
                 : "=r"(r[0]), "=r"(r[1]), "=r"(r[2]), "=r"(r[3]) : "r"(addr) : "memory");
}
__device__ __forceinline__ void ldsm4t(uint32_t (&r)[4], uint32_t addr) {
    asm volatile("ldmatrix.sync.aligned.m8n8.x4.trans.shared.b16 {%0,%1,%2,%3}, [%4];"
                 : "=r"(r[0]), "=r"(r[1]), "=r"(r[2]), "=r"(r[3]) : "r"(addr) : "memory");
}
__device__ __forceinline__ void mma16816(float (&c)[4], const uint32_t (&a)[4], uint32_t b0, uint32_t b1) {
    asm volatile("mma.sync.aligned.m16n8k16.row.col.f32.bf16.bf16.f32 {%0,%1,%2,%3}, {%4,%5,%6,%7}, {%8,%9}, {%0,%1,%2,%3};"
                 : "+f"(c[0]), "+f"(c[1]), "+f"(c[2]), "+f"(c[3])
                 : "r"(a[0]), "r"(a[1]), "r"(a[2]), "r"(a[3]), "r"(b0), "r"(b1));
}
struct Warm {
    float c[4] = {};
    __device__ __forceinline__ void operator()() {
        asm volatile("mma.sync.aligned.m16n8k8.row.col.f32.bf16.bf16.f32 {%0,%1,%2,%3}, {%4,%4}, {%4}, {%0,%1,%2,%3};"
                     : "+f"(c[0]), "+f"(c[1]), "+f"(c[2]), "+f"(c[3]) : "r"(0));
    }
    __device__ __forceinline__ void done(uint32_t scrap) {
        asm volatile("{\n.reg .pred p;\nsetp.gt.f32 p, %1, 0f3f800000;\n@p st.shared.f32 [%0], %1;\n}" :: "r"(scrap), "f"(c[0]) : "memory");
    }
};
__device__ __forceinline__ uint4 ld_relaxed_v4(const void* p) {
    uint4 v;
    asm volatile("ld.relaxed.gpu.global.v4.u32 {%0,%1,%2,%3}, [%4];" : "=r"(v.x), "=r"(v.y), "=r"(v.z), "=r"(v.w) : "l"(p) : "memory");
    return v;
}
__device__ __forceinline__ float4 ld_relaxed_f4(const void* p) {
    float4 v;
    asm volatile("ld.relaxed.gpu.global.v4.f32 {%0,%1,%2,%3}, [%4];" : "=f"(v.x), "=f"(v.y), "=f"(v.z), "=f"(v.w) : "l"(p) : "memory");
    return v;
}
__device__ __forceinline__ float2 ld_relaxed_f2(const void* p) {
    float2 v;
    asm volatile("ld.relaxed.gpu.global.v2.f32 {%0,%1}, [%2];" : "=f"(v.x), "=f"(v.y) : "l"(p) : "memory");
    return v;
}
__device__ __forceinline__ float4 ld_relaxed_b128(const void* p) {
    float4 v;
    asm volatile("{\n.reg .b128 t;\n.reg .b64 a, b;\nld.relaxed.gpu.global.b128 t, [%4];\nmov.b128 {a, b}, t;\n"
                 "mov.b64 {%0, %1}, a;\nmov.b64 {%2, %3}, b;\n}" : "=f"(v.x), "=f"(v.y), "=f"(v.z), "=f"(v.w) : "l"(p) : "memory");
    return v;
}
__device__ __forceinline__ void st_relaxed_b128(void* p, float x, float y, float z, float w) {
    asm volatile("{\n.reg .b128 t;\n.reg .b64 a, b;\nmov.b64 a, {%1, %2};\nmov.b64 b, {%3, %4};\nmov.b128 t, {a, b};\n"
                 "st.relaxed.gpu.global.b128 [%0], t;\n}" :: "l"(p), "f"(x), "f"(y), "f"(z), "f"(w) : "memory");
}
__device__ __forceinline__ unsigned ld_acquire(const unsigned* p) {
    unsigned v;
    asm volatile("ld.acquire.gpu.global.u32 %0, [%1];" : "=r"(v) : "l"(p) : "memory");
    return v;
}
__device__ __forceinline__ void st_relaxed(void* p, uint32_t v) {
    asm volatile("st.relaxed.gpu.global.u32 [%0], %1;" :: "l"(p), "r"(v) : "memory");
}
__device__ __forceinline__ void red_f2(float* p, float a, float b) {
    asm volatile("red.relaxed.gpu.global.add.v2.f32 [%0], {%1,%2};" :: "l"(p), "f"(a), "f"(b) : "memory");
}
__device__ __forceinline__ void draw(int& ticket, unsigned* ctr, bool pred) {
    asm volatile("{\n.reg .pred p;\nsetp.ne.u32 p, %2, 0;\n@p atom.relaxed.gpu.global.inc.u32 %0, [%1], 0x7fffffff;\n}"
                 : "+r"(ticket) : "l"(ctr), "r"((uint32_t)pred) : "memory");
}
__device__ __forceinline__ void red_release(unsigned* p) {
    asm volatile("red.release.gpu.global.add.u32 [%0], 1;" :: "l"(p) : "memory");
}
__device__ __forceinline__ uint32_t ld_relaxed_u32(const void* p) {
    uint32_t v;
    asm volatile("ld.relaxed.gpu.global.u32 %0, [%1];" : "=r"(v) : "l"(p) : "memory");
    return v;
}
__device__ __forceinline__ float rcp_approx(float v) {
    float r;
    asm("rcp.approx.ftz.f32 %0, %1;" : "=f"(r) : "f"(v));
    return r;
}
__device__ __forceinline__ float ex2_approx(float v) {
    float e;
    asm("ex2.approx.ftz.f32 %0, %1;" : "=f"(e) : "f"(v));
    return e;
}
__device__ __forceinline__ float sigmoid_approx(float v) { return rcp_approx(1.0f + ex2_approx(v * -1.4426950408889634f)); }
__device__ __forceinline__ float sqrt_approx(float v) {
    float r;
    asm("sqrt.approx.ftz.f32 %0, %1;" : "=f"(r) : "f"(v));
    return r;
}
__device__ __forceinline__ bool all(bool v) { return __all_sync(0xffffffffu, v); }
__device__ __forceinline__ void wait_count(const unsigned* p, unsigned target) {
#pragma unroll 1
    for (int it = 0; it < SPIN_MAX; it++) {
        if (all(ld_acquire(p) >= target)) break;
        __nanosleep(400);
    }
}
__device__ __forceinline__ float wait_sum(const void* p, float n, int nap = 0) {
    float2 v;
#pragma unroll 1
    for (int it = 0; it < SPIN_MAX; it++) {
        v = ld_relaxed_f2(p);
        if (all(v.y >= n)) break;
        if (all(v.y == 0.f)) __nanosleep(600);
        else if (nap) __nanosleep(nap);
    }
    return v.x;
}
__device__ __forceinline__ void wait_row(const Scratch* scr, int bh, float n) { wait_sum(g_st.lsum[bh], n); }
__device__ __forceinline__ void wait_row_o(const Scratch* scr, int bh, float n) {
    wait_row(scr, bh, n);
    if (bh >= RED0) return;
#pragma unroll 1
    for (int it = 0; it < SPIN_MAX; it++) {
        if (all(__uint_as_float(ld_relaxed_u32(&g_st.oacc[oidx(bh, 0)].w)) == UPB)) break;
        __nanosleep(300);
    }
}
constexpr uint32_t SLOT_K = (uint32_t)(((1ull << 32) + SLOT_TICKS - 1) / SLOT_TICKS);
#define SLOT_ASM(t, n, p, phase, k, open) \
    "mov.u32 " n ", 0;\nSLOT:\nmov.u32 " t ", %%globaltimer_lo;\nadd.u32 " n ", " n ", 1;\nsetp.lt.u32 " p ", " n ", 24;\nshr.u32 " t ", " t ", 5;\n" \
    "mad.lo.u32 " t ", " t ", " k ", " phase ";\nsetp.ge.and.u32 " p ", " t ", " open ", " p ";\n@" p " bra.uni SLOT;\n"
template <int PHASE> __host__ __device__ constexpr uint32_t slot_phase() { return SLOT_K / 2 - PHASE * SLOT_K; }
template <int PHASE> __device__ __forceinline__ void wait_slot() {
    if (PHASE < 0) return;
    asm volatile("{\n.reg .pred p;\n.reg .b32 t, n;\n" SLOT_ASM("t", "n", "p", "%0", "%1", "%2") "}"
                 :: "n"(slot_phase<PHASE>()), "n"(SLOT_K), "n"(SLOT_OPEN * SLOT_K) : "memory");
}
__device__ __forceinline__ void wait_time(uint32_t t) {
#pragma unroll 1
    for (int it = 0; it < SPIN_MAX; it++) {
        uint32_t now;
        asm volatile("mov.u32 %0, %%globaltimer_lo;" : "=r"(now));
        if (all((int)(now - t) >= 0)) break;
    }
}
__device__ __forceinline__ void wait_clock(uint32_t t, Warm& warm) { while (!all((int)(clock() - t) >= 0)) { warm(); } }
__device__ __forceinline__ uint32_t pack_bf16(float lo, float hi) {
    uint32_t r;
    asm("cvt.rn.bf16x2.f32 %0, %1, %2;" : "=r"(r) : "f"(hi), "f"(lo));
    return r;
}
__device__ __forceinline__ float bf16r(float v) { return __uint_as_float(pack_bf16(0.f, v)); }
__device__ __forceinline__ uint32_t nonzero(uint32_t w) { return w ? w : 0x80008000u; }
__device__ __forceinline__ uint32_t pack_neg(float lo, float hi) { return nonzero(pack_bf16(-lo, -hi)); }
__device__ __forceinline__ float lo_f(uint32_t v) { return __uint_as_float(v << 16); }
__device__ __forceinline__ float hi_f(uint32_t v) { return __uint_as_float(v & 0xffff0000u); }
__device__ __forceinline__ float warp_sum(float v) {
#pragma unroll
    for (int o = 16; o; o >>= 1) v += __shfl_xor_sync(0xffffffffu, v, o);
    return v;
}
__device__ __forceinline__ void layernorm20(float (&v)[20]) {
    float s = 0.f;
#pragma unroll
    for (int i = 0; i < 20; i++) s += v[i];
    const float mean = warp_sum(s) * (1.0f / DM);
    float q = 0.f;
#pragma unroll
    for (int i = 0; i < 20; i++) { const float d = v[i] - mean; q += d * d; }
    const float var = bf16r(warp_sum(q) * (1.0f / DM));
    const float m = bf16r(mean);
    const float rden = 1.0f / bf16r(sqrtf(bf16r(var + 1e-5f)));
#pragma unroll
    for (int i = 0; i < 20; i++) v[i] = bf16r(bf16r(v[i] - m) * rden);
}

__device__ __forceinline__ void moments(float m1, float m2, float& nmean, float& rden) {
    m1 *= 1.0f / DM;
    const float var = bf16r(fmaxf(fmaf(-m1, m1, m2 * (1.0f / DM)), 0.f));
    nmean = bf16r(m1);
    rden = rcp_approx(bf16r(sqrt_approx(bf16r(var + 1e-5f))));
}
__device__ __forceinline__ float sel4(int j, float a, float b, float c, float d) {
    float lo, hi, r;
    asm("{\n.reg .pred p;\nsetp.ne.s32 p, %3, 0;\nselp.f32 %0, %2, %1, p;\n}" : "=f"(lo) : "f"(a), "f"(b), "r"(j & 1));
    asm("{\n.reg .pred p;\nsetp.ne.s32 p, %3, 0;\nselp.f32 %0, %2, %1, p;\n}" : "=f"(hi) : "f"(c), "f"(d), "r"(j & 1));
    asm("{\n.reg .pred p;\nsetp.ne.s32 p, %3, 0;\nselp.f32 %0, %2, %1, p;\n}" : "=f"(r) : "f"(lo), "f"(hi), "r"(j & 2));
    return r;
}
template <typename T> __device__ __forceinline__ void pin(T*& p) { asm volatile("" : "+l"(p)); }
__device__ __forceinline__ void pin(uint32_t& v) { asm volatile("" : "+r"(v)); }
__device__ __forceinline__ void pin(float& v) { asm volatile("" : "+f"(v)); }
__device__ __forceinline__ uint32_t after(uint32_t n, float v) {
    asm volatile("{\n.reg .pred p;\nsetp.eq.u32 p, %1, 0x7fc1a5a5;\n@p add.u32 %0, %0, 32;\n}" : "+r"(n) : "r"(__float_as_uint(v)));
    return n;
}
__device__ __forceinline__ float2 lds64f(uint32_t addr) {
    float2 v;
    asm volatile("ld.shared.v2.f32 {%0,%1}, [%2];" : "=f"(v.x), "=f"(v.y) : "r"(addr) : "memory");
    return v;
}
__device__ __forceinline__ void sts32f(uint32_t addr, float v) { asm volatile("st.shared.f32 [%0], %1;" :: "r"(addr), "f"(v) : "memory"); }
template <int ID> __device__ __forceinline__ void fin_arrive() { asm volatile("bar.arrive %0, 288;" :: "n"(ID) : "memory"); }
template <int ID> __device__ __forceinline__ void fin_sync() { asm volatile("bar.sync %0, 288;" :: "n"(ID) : "memory"); }
template <int ID> __device__ __forceinline__ void fin_sync(uint32_t n) { asm volatile("bar.sync %0, %1;" :: "n"(ID), "r"(n) : "memory"); }
__device__ __forceinline__ float2 sum8(uint32_t addr, int pitch) {
    float2 t[8];
#pragma unroll
    for (int w = 0; w < 8; w++) t[w] = lds64f(addr + w * pitch);
    return make_float2(((t[0].x + t[1].x) + (t[2].x + t[3].x)) + ((t[4].x + t[5].x) + (t[6].x + t[7].x)),
                       ((t[0].y + t[1].y) + (t[2].y + t[3].y)) + ((t[4].y + t[5].y) + (t[6].y + t[7].y)));
}
__device__ __forceinline__ float4 sum4x4(uint32_t addr, int pitch) {
    float4 t[4];
#pragma unroll
    for (int w = 0; w < 4; w++)
        asm volatile("ld.shared.v4.f32 {%0,%1,%2,%3}, [%4];" : "=f"(t[w].x), "=f"(t[w].y), "=f"(t[w].z), "=f"(t[w].w) : "r"(addr + w * pitch) : "memory");
    return make_float4((t[0].x + t[1].x) + (t[2].x + t[3].x), (t[0].y + t[1].y) + (t[2].y + t[3].y),
                       (t[0].z + t[1].z) + (t[2].z + t[3].z), (t[0].w + t[1].w) + (t[2].w + t[3].w));
}
__device__ __forceinline__ void sts64f(uint32_t addr, float x, float y) {
    asm volatile("st.shared.v2.f32 [%0], {%1,%2};" :: "r"(addr), "f"(x), "f"(y) : "memory");
}
__device__ __forceinline__ uint4 lds128(uint32_t addr) {
    uint4 v;
    asm volatile("ld.shared.v4.u32 {%0,%1,%2,%3}, [%4];" : "=r"(v.x), "=r"(v.y), "=r"(v.z), "=r"(v.w) : "r"(addr) : "memory");
    return v;
}
__device__ __forceinline__ void ld_relaxed_v4_if(uint4& v, const void* p, bool pred) {
    asm volatile("{\n.reg .pred p;\nsetp.ne.u32 p, %5, 0;\n@p ld.relaxed.gpu.global.v4.u32 {%0,%1,%2,%3}, [%4];\n}"
                 : "+r"(v.x), "+r"(v.y), "+r"(v.z), "+r"(v.w) : "l"(p), "r"((uint32_t)pred) : "memory");
}
__device__ __forceinline__ void sts128f(uint32_t addr, float x, float y, float z, float w) {
    asm volatile("st.shared.v4.f32 [%0], {%1,%2,%3,%4};" :: "r"(addr), "f"(x), "f"(y), "f"(z), "f"(w) : "memory");
}
template <int NJ>
__device__ __forceinline__ void load_o(uint32_t (&ob)[3 * NJ][2], const Scratch* scr, int bh, int J0, int j) {
    float4 v[NJ][4];
    float2 l;
#pragma unroll 1
    for (int it = 0; it < SPIN_MAX; it++) {
#pragma unroll
        for (int J = 0; J < NJ; J++) {
#pragma unroll
            for (int e = 0; e < 4; e++) v[J][e] = ld_relaxed_f4(&g_st.oacc[oidx(bh, j)] + oidx(0, (J0 + J) * 16 + e * 4));
        }
        l = ld_relaxed_f2(g_st.lsum[bh]);
        bool ok = l.y == UPB;
#pragma unroll
        for (int J = 0; J < NJ; J++) {
#pragma unroll
            for (int e = 0; e < 4; e++) ok &= v[J][e].w == UPB;
        }
        if (all(ok)) break;
    }
    const float rl = __fdividef(1.0f, l.x);
#pragma unroll
    for (int J = 0; J < NJ; J++) {
        ob[3 * J][0] = pack_bf16(v[J][0].x * rl, v[J][1].x * rl);     ob[3 * J][1] = pack_bf16(v[J][2].x * rl, v[J][3].x * rl);
        ob[3 * J + 1][0] = pack_bf16(v[J][0].y * rl, v[J][1].y * rl); ob[3 * J + 1][1] = pack_bf16(v[J][2].y * rl, v[J][3].y * rl);
        ob[3 * J + 2][0] = pack_bf16(v[J][0].z * rl, v[J][1].z * rl); ob[3 * J + 2][1] = pack_bf16(v[J][2].z * rl, v[J][3].z * rl);
    }
}
__device__ __forceinline__ int near_side(uint32_t sb) {
    uint32_t v;
    asm volatile("ld.volatile.shared.u32 %0, [%1];" : "=r"(v) : "r"(sb + SM_SIDE) : "memory");
    return v;
}
__device__ __forceinline__ void poll_row(uint4& a, uint4& b, uint2& c, const void* pa, const void* pb, const void* pc, uint32_t sa, uint32_t sc,
                                         bool arrive, bool nap, uint32_t bar, Warm& warm) {
    asm volatile("{\n.reg .pred p, q, r, s;\n.reg .b32 m, n, it;\n"
                 "setp.ne.u32 r, %19, 0;\nsetp.ne.u32 s, %20, 0;\nmov.u32 it, 0;\n"
                 "POLL:\n"
                 SLOT_ASM("m", "n", "p", "%23", "%24", "%25")
                 "ld.relaxed.gpu.global.v4.u32 {%0,%1,%2,%3}, [%14];\n"
                 "ld.relaxed.gpu.global.v4.u32 {%4,%5,%6,%7}, [%15];\n"
                 "ld.relaxed.gpu.global.v2.u32 {%8,%9}, [%16];\n"
                 "add.u32 it, it, 1;\nsetp.ge.u32 q, it, %21;\n"
                 "mov.u32 m, 0;\nmma.sync.aligned.m16n8k8.row.col.f32.bf16.bf16.f32 {%10,%11,%12,%13}, {m,m}, {m}, {%10,%11,%12,%13};\n"
                 "st.shared.v4.u32 [%17], {%0,%1,%2,%3};\n"
                 "st.shared.v4.u32 [%17+512], {%4,%5,%6,%7};\n"
                 "st.shared.v2.u32 [%18], {%8,%9};\n"
                 "min.u32 m, %0, %1;\nmin.u32 m, m, %2;\nmin.u32 n, %3, %4;\nmin.u32 n, n, %5;\nmin.u32 m, m, %6;\nmin.u32 m, m, %7;\n"
                 "min.u32 n, n, m;\nmin.u32 m, %8, %9;\nmin.u32 m, m, n;\n"
                 "setp.ne.or.u32 p, m, 0, q;\n"
                 "vote.sync.all.pred p, p, 0xffffffff;\n"
                 "and.pred q, p, r;\n"
                 "bar.warp.sync 0xffffffff;\n"
                 "@q mbarrier.arrive.shared::cta.b64 _, [%22];\n"
                 "@p bra.uni DONE;\n"
                 "@s nanosleep.u32 500;\n"
                 "bra.uni POLL;\n"
                 "DONE:\n}"
                 : "=&r"(a.x), "=&r"(a.y), "=&r"(a.z), "=&r"(a.w), "=&r"(b.x), "=&r"(b.y), "=&r"(b.z), "=&r"(b.w), "=&r"(c.x), "=&r"(c.y),
                   "+f"(warm.c[0]), "+f"(warm.c[1]), "+f"(warm.c[2]), "+f"(warm.c[3])
                 : "l"(pa), "l"(pb), "l"(pc), "r"(sa), "r"(sc), "r"((uint32_t)arrive), "r"((uint32_t)nap), "n"(SPIN_MAX), "r"(bar),
                   "n"(slot_phase<PH_H>()), "n"(SLOT_K), "n"(SLOT_OPEN * SLOT_K) : "memory");
}
__device__ __forceinline__ void aux_sync() { asm volatile("bar.sync 1, 256;" ::: "memory"); }

__global__ void __launch_bounds__(NTHREADS, 1)
fused_decode_kernel(Scratch* const scr, const __nv_bfloat16* const x, const __nv_bfloat16* const w_r, __nv_bfloat16* const out_all,
                    const __grid_constant__ Params p) {
    extern __shared__ __align__(1024) unsigned char smem[];
    const uint32_t sb = s2u(smem);
    const int tid = threadIdx.x, cta = blockIdx.x;
    if (tid < 32 && cta < NQ_CTAS) {
        asm volatile("{\n.reg .pred p;\nelect.sync _|p, 0xffffffff;\n"
                     "@p mbarrier.init.shared::cta.b64 [%2], 1;\n"
                     "@p fence.mbarrier_init.release.cluster;\n"
                     "@p mbarrier.arrive.expect_tx.shared::cta.b64 _, [%2], 15360;\n"
                     "@p cp.async.bulk.tensor.2d.shared::cluster.global.mbarrier::complete_tx::bytes [%0], [%1, {%3, %4}], [%2];\n"
                     "@p mbarrier.init.shared::cta.b64 [%2+8], 1;\n@p mbarrier.init.shared::cta.b64 [%2+16], 1;\n"
                     "@p mbarrier.init.shared::cta.b64 [%2+24], 1;\n"
                     "@p fence.mbarrier_init.release.cluster;\n"
                     "@p mbarrier.arrive.expect_tx.shared::cta.b64 _, [%2+8], 15360;\n"
                     "@p cp.async.bulk.tensor.2d.shared::cluster.global.mbarrier::complete_tx::bytes [%0+15360], [%1, {%3, %5}], [%2+8];\n"
                     "@p mbarrier.arrive.expect_tx.shared::cta.b64 _, [%2+16], 15360;\n"
                     "@p cp.async.bulk.tensor.2d.shared::cluster.global.mbarrier::complete_tx::bytes [%0+30720], [%1, {%3, %6}], [%2+16];\n"
                     "@p mbarrier.arrive.expect_tx.shared::cta.b64 _, [%2+24], 15360;\n"
                     "@p cp.async.bulk.tensor.2d.shared::cluster.global.mbarrier::complete_tx::bytes [%0+46080], [%1, {%3, %7}], [%2+24];\n}"
                     :: "r"(sb + SM_W), "l"(&p.wq), "r"(sb + BAR_WQ), "r"(cta * 48), "r"(0), "r"(160), "r"(320), "r"(480) : "memory");
    }
    const int warp = __shfl_sync(0xffffffffu, tid >> 5, 0), lane = tid & 31;
    constexpr int grid = NCTAS;
    const int g = lane >> 2, j = lane & 3;
    uint32_t t_start;
    asm volatile("mov.u32 %0, %%globaltimer_lo;" : "=r"(t_start));
    TS(0);
    if (tid == 32) {
        mbar_init(sb + BAR_WO, 1);
        mbar_init(sb + BAR_H, 1);
#pragma unroll
        for (int i = 0; i < 8 + NWORK; i++) mbar_init(sb + BAR_FW + i * 8, 1);
        sts32f(sb + SM_SIDE, 0.f);
        asm volatile("fence.mbarrier_init.release.cluster;" ::: "memory");
        asm volatile("fence.proxy.async.shared::cta;" ::: "memory");
    }
    __syncthreads();
    if (warp >= NAUX + NWORK) {
        const int fw = warp - (NAUX + NWORK), fi = ffn_slice(cta);
        if (fw == 0) {
            wait_time(t_start + CLEAR_AT_NS);
            if (cta < NQ_CTAS) {
#pragma unroll
                for (int i = lane; i < STATE_V4; i += 32)
                    if (cta * STATE_V4 + i < (int)(sizeof(State) / 16)) reinterpret_cast<uint4*>(&g_st)[cta * STATE_V4 + i] = make_uint4(0u, 0u, 0u, 0u);
                __syncwarp();
                if (lane == 0) red_release(g_cnt_z);
            }
            TSW(2); wait_count(g_cnt_z, NQ_CTAS); TSW(29);
            asm volatile("bar.arrive 2, %0;" :: "n"((NWORK + 2) * 32) : "memory");
            fin_arrive<3>();
        } else {
#pragma unroll 1
            for (int n = cta < NE_CTAS ? 5 : 4, i = n - 1; i >= 0; i--) {
                const int head = cta < NE_CTAS ? cta >> 2 : 28 + i;
                wait_time(t_start + WO_AT_NS + (NH - 1 - head) * WO_STEP_NS);
                request_box(sb + SM_A + i * 12288, &p.wo, cta < NE_CTAS ? (cta & 3) * 160 + i * 32 : (cta - NE_CTAS) * 32,
                            head * DH, sb + BAR_WO, i == n - 1 ? n * 12288 : 0);
            }
            asm volatile("bar.sync 2, %0;" :: "n"((NWORK + 2) * 32) : "memory");
            uint32_t best[2] = {~0u, ~0u};
#pragma unroll 1
            for (int i = 0; i < NPROBE; i++) {
#pragma unroll
                for (int c = 0; c < 2; c++) {
                    uint32_t t0 = clock(), t1 = t0;
                    int v = 0;
                    draw(v, &g_st.hx.w[c][PROBE], lane == 0);
                    asm volatile("{\n.reg .pred p;\nsetp.ne.u32 p, %1, 0xffffffff;\n@p mov.u32 %0, %%clock;\n}" : "+r"(t1) : "r"(v) : "memory");
                    best[c] = min(best[c], t1 - t0);
                }
                __nanosleep(1000);
            }
            if (lane == 0) sts32f(sb + SM_SIDE, __uint_as_float(best[1] < best[0]));
        }
        int job = cta;
        auto sum_rows = [&](int row_end) {
#pragma unroll 1
            for (; job < 8 * min(row_end, RED0); job += NCTAS) {
                const int row = job >> 3, grp = (job & 7) * 8 + (lane & 7);
                wait_row(scr, row, UPB);
                const float4* src = &g_ring[row % RING][lane >> 3][grp];
                float sx = 0.f, sy = 0.f, sz = 0.f;
#pragma unroll 1
                for (int i = 0; i < 2; i++, src += 64 * 64) {
                    float4 v[16];
#pragma unroll 1
                    for (int it = 0; it < SPIN_MAX; it++) {
                        bool ok = true;
#pragma unroll
                        for (int k = 0; k < 16; k++) v[k] = ld_relaxed_b128(src + k * 4 * 64);
#pragma unroll
                        for (int k = 0; k < 16; k++) ok &= v[k].w == (float)(row + 1);
                        if (all(ok)) break;
                    }
#pragma unroll
                    for (int k = 0; k < 16; k++) { sx += v[k].x; sy += v[k].y; sz += v[k].z; }
                }
#pragma unroll
                for (int o = 8; o < 32; o <<= 1) {
                    sx += __shfl_xor_sync(0xffffffffu, sx, o); sy += __shfl_xor_sync(0xffffffffu, sy, o); sz += __shfl_xor_sync(0xffffffffu, sz, o);
                }
                if (lane < 8) st_relaxed_b128(&g_st.oacc[oidx(row, grp)], sx, sy, sz, UPB);
            }
        };
        const int ho0 = lane / 20 * 256 + lane % 20 * 4, ho1 = (lane + 32) / 20 * 256 + (lane + 32) % 20 * 4, ho2 = 3 * 256 + 16 + 2 * lane;
        uint32_t wr[10] = {};
        float wsum = 0.f;
        if (is_g(cta) && fw == 0) {
#pragma unroll
            for (int i = 0; i < 10; i++) {
                const int w = 4 * lane + 128 * (i >> 2) + (i & 3) - (i >= 8 ? 2 * lane : 0);
                wr[i] = *reinterpret_cast<const uint32_t*>(w_r + (w >> 4) * 32 + (w & 3) * 8 + ((w >> 1) & 6));
                wsum += lo_f(wr[i]) + hi_f(wr[i]);
            }
            wsum = warp_sum(wsum);
        }
        const int fb = lane >> 3, fg = lane & 7;
        if (fw == 0) {
#pragma unroll
            for (int i = lane; i < DM / 2; i += 32) sts32f(sb + SM_X + 4 * HPITCH + i * 4, __uint_as_float(0x3f803f80u));
        }
        Warm warm;
        float nmean = 0.f, rden = 0.f, sig = 0.f;
#pragma unroll 1
        for (int b = 0; b < NB; b++) {
            const bool ffn = b >= NB - 2;
            if (fw == 0) {
                sum_rows((b + 1) * NH);
                if (ffn) asm volatile("bar.arrive 8, 64;" ::: "memory");
            } else if (ffn) {
                asm volatile("bar.sync 8, 64;" ::: "memory");
                if (b == NB - 1 && (is_f(cta) || is_g(cta) || ALL_LOADERS)) {
                    uint32_t t0 = 0;
#pragma unroll 1
                    for (int it = 0; it < SPIN_MAX; it++) {
                        t0 = ld_relaxed_u32(g_st.fw_time);
                        if (all(t0 != 0)) break;
                        __nanosleep(150);
                    }
                    asm volatile("fence.proxy.async.shared::cta;" ::: "memory");
                    wait_time(t0 + FW_AT_NS);
                    TSW(9);
                    uint32_t t = clock() + (is_f(cta) ? ((fi & 1) * 24 + (fi >> 1)) * FW_GAP / 48 : FW_MID + ((fi & 3) * 10 + (fi >> 2)) * FW_GAP2 / 40);
#pragma unroll 1
                    for (int i = 0; i < 8; i++) {
                        const uint32_t bar = sb + BAR_FW + i * 8;
                        if (is_f(cta)) {
                            wait_clock(t, warm);
                            request_box(sb + SM_W + i * 10240, (i & 1) ? &p.wu : &p.wg, fi * 32, (i >> 1) * 160, bar, 10240);
                            t += FW_GAP;
                        } else if (is_g(cta)) {
                            wait_clock(t, warm);
                            asm volatile("{\n.reg .pred p;\nelect.sync _|p, 0xffffffff;\n"
                                         "@p mbarrier.arrive.expect_tx.shared::cta.b64 _, [%2], 6144;\n"
                                         "@p cp.async.bulk.tensor.4d.shared::cluster.global.mbarrier::complete_tx::bytes [%0], [%1, {%3, %4, %4, %5}], [%2];\n}"
                                         :: "r"(sb + SM_W + i * 6144), "l"(&p.wd), "r"(bar), "r"(fi * 16), "r"(0), "r"(i * 12) : "memory");
                            t += FW_GAP2;
                        }
                    }
                }
                if (is_f(cta)) {
                    const uint32_t* src = &g_st.hx.w[near_side(sb)][min(fb, b) * 256 + 96];
                    float4 m;
#pragma unroll 1
                    for (int it = 0; it < SPIN_MAX; it++) {
                        wait_slot<PH_M>();
                        m = ld_relaxed_f4(src);
                        warm();
                        if (all(m.y + m.w == 2 * (NCTAS - NE_CTAS))) break;
                        if (b < NB - 1) __nanosleep(500);
                    }
                    moments(m.x, m.z, m.x, m.z);
                    sts64f(sb + SM_RED + 5120 + fb * 8, m.x, m.z);
                }
            }
            if (fw == 0 && cta >= NE_CTAS) {
                const int lc = cta - NE_CTAS, col = lc * 32 + 2 * (lane & 15);
                const uint32_t xv = *reinterpret_cast<const uint32_t*>(x + b * DM + col);
                uint32_t* dst = &(ffn ? g_st.hx.w : g_st.lx.w + 2)[lane >> 4][(b & 1) * 128 + lc / 5 * 256 + lc % 5 * 16 + (col & 6) * 2 + ((col >> 3) & 3)];
                uint32_t part = sb + SM_RED + (lane & 15) * 8;
                wait_row(scr, b * NH + 28, 1);
                float4 early;
#pragma unroll 1
                for (int it = 0; it < SPIN_MAX; it++) {
                    early = ld_relaxed_f4(&g_st.attn[b][col]);
                    if (all(early.y == NE_CTAS / 4 && early.w == NE_CTAS / 4)) break;
                }
                if (early.x != 1.2345f && lane == 0) TS2(6);
                CK(1, __float_as_uint(early.x));
                const float x0 = -(lo_f(xv) + early.x), x1 = -(hi_f(xv) + early.z);
                fin_sync<4>(after(after(288, x0), x1));
                CK(2, lds32(sb + SM_RED));
                const float2 late = sum8(part, 128);
                const uint32_t hv = nonzero(pack_bf16(x0 - late.x, x1 - late.y));
                st_relaxed(dst, hv);
                if (ffn) st_relaxed(dst + 2048, hv);
                CK(3, 0);
                float m = lane < 16 ? lo_f(hv) + hi_f(hv) : fmaf(lo_f(hv), lo_f(hv), hi_f(hv) * hi_f(hv));
#pragma unroll
                for (int o = 1; o < 16; o <<= 1) m += __shfl_xor_sync(0xffffffffu, m, o);
                if ((lane & 14) == 0) red_f2(reinterpret_cast<float*>(&g_st.hx.w[lane & 1][b * 256 + 96 + (lane >> 4) * 2]), m, 1.f);
                fin_arrive<5>();
            }
            if (fw == 0 && (is_g(cta) || is_f(cta))) {
                const uint32_t* src = &(ffn ? g_st.hx.w : g_st.lx.w + 2)[near_side(sb) ^ (ffn && is_g(cta) ? 3 : 0)][(b & 1) * 128];
                const uint32_t hrow = sb + SM_X + b * HPITCH;
                wait_sum(b == NB - 1 ? (const void*)&g_st.lx.w[near_side(sb) ^ 1][3 * 256] : g_st.lsum[b * NH + NH - 1], UPB, 100);
                wait_clock(clock() + HGATE_NS * 2, warm);
                uint4 h0, h1;
                uint2 h2;
                poll_row(h0, h1, h2, src + ho0, src + ho1, src + ho2, hrow + lane * 16, hrow + 1024 + lane * 8, ffn && lane == 0, b < NB - 1, sb + BAR_H, warm);
                CK(4, h0.x);
                if (is_g(cta)) {
                    const uint32_t hw[10] = {h0.x, h0.y, h0.z, h0.w, h1.x, h1.y, h1.z, h1.w, h2.x, h2.y};
                    float m1 = 0.f, m2 = 0.f, rr = 0.f;
#pragma unroll
                    for (int i = 0; i < 10; i++) {
                        const float v0 = lo_f(hw[i]), v1 = hi_f(hw[i]);
                        m1 += v0 + v1;
                        m2 = fmaf(v0, v0, fmaf(v1, v1, m2));
                        rr = fmaf(v0, lo_f(wr[i]), fmaf(v1, hi_f(wr[i]), rr));
                    }
                    moments(warp_sum(m1), warp_sum(m2), m1, m2);
                    const float sg = bf16r(sigmoid_approx(bf16r((m1 * wsum - warp_sum(rr)) * m2)));
                    if (fb == b) { nmean = m1; rden = m2; sig = sg; }
                    __syncwarp();
                    if (ffn) {
                        const int yj = 2 * (fb & 1) + (fb >> 1);
                        uint32_t ypart = sb + SM_RED2 + yj * 128 + ((fg + 2 * yj) & 7) * 16;
                        __nv_bfloat16* out = out_all + fb * DM + fi * 16 + fg;
                        const float2 hw2 = lds64f(sb + SM_X + fb * HPITCH + ((fi >> 1) * 16 + (fg & 6) * 2 + (fi & 1) * 2) * 4);
                        const uint32_t w0 = __float_as_uint(hw2.x), w1 = __float_as_uint(hw2.y);
                        const float nh0 = (fg & 1) ? hi_f(w0) : lo_f(w0), nh1 = (fg & 1) ? hi_f(w1) : lo_f(w1);
                        const float ln0 = bf16r(bf16r(nmean - nh0) * rden) - nh0, ln1 = bf16r(bf16r(nmean - nh1) * rden) - nh1;
                        pin(ypart); pin(out);
                        fin_sync<6>(after(after(after(288, sig), ln0), ln1));
                        CK(10, lds32(ypart));
                        const float4 ya = sum4x4(ypart, 512), yb = sum4x4(ypart + 2048, 512);
                        const float4 y = make_float4(ya.x + yb.x, ya.y + yb.y, ya.z + yb.z, ya.w + yb.w);
                        const float y0 = -(((fb & 1) ? y.y : y.x) + __shfl_xor_sync(0xffffffffu, (fb & 1) ? y.x : y.y, 8));
                        const float y1 = -(((fb & 1) ? y.w : y.z) + __shfl_xor_sync(0xffffffffu, (fb & 1) ? y.z : y.w, 8));
                        const uint32_t ov = pack_bf16(fmaf(y0, sig, ln0), fmaf(y1, sig, ln1));
                        asm volatile("{\n.reg .pred p;\n.reg .b16 lo, hi;\nsetp.ne.u32 p, %2, 0;\nmov.b32 {lo, hi}, %1;\n"
                                     "@p st.global.u16 [%0], lo;\n@p st.global.u16 [%0+16], hi;\n"
                                     "@p exit;\n"
                                     "}" :: "l"(out), "r"(ov), "r"((uint32_t)(b == NB - 1)) : "memory");
                        CK(11, 0);
                        if (lane == 0) TS2(13);
                    }
                }
            }
            if (is_f(cta) && ffn) {
                const int ks = (2 * fi + fw) % 12;
                const int far = near_side(sb) ^ 1;
                uint32_t* dst = &g_st.ax[ks >> 2].w[(~b & 1) * 2 + far][(fi / 6) * 128 + (ks & 3) * 32 + fb * 8 + (fg & 1) * 4 + ((fg >> 1) ^ (ks & 1))];
                uint32_t* dst2 = dst + (far ? -1024 : 1024);
                uint32_t part = sb + SM_RED + fw * 2560 + fb * 128 + ((fg + (fb & 2)) & 7) * 16;
                uint32_t psum = sb + SM_RED + fw * 2560 + 4 * 128 + ((fg + 4) & 7) * 16;
                pin(dst); pin(part); pin(psum);
                asm volatile("bar.sync 4, 320;" ::: "memory");
                CK(6, lds32(part));
                const float4 d = sum4x4(part, 640), cs = sum4x4(psum, 640);
                const float2 mo = lds64f(sb + SM_RED + 5120 + fb * 8);
                nmean = mo.x; rden = mo.y;
                const float g0 = fmaf(nmean, cs.x, -d.x), g1 = fmaf(nmean, cs.y, -d.y), ke = rden * -1.4426950408889634f, r2 = rden * rden;
                const float p0 = g0 * fmaf(-nmean, cs.z, d.z) * r2, p1 = g1 * fmaf(-nmean, cs.w, d.w) * r2;
                const uint32_t av = nonzero(pack_bf16(p0 * rcp_approx(1.0f + ex2_approx(g0 * ke)), p1 * rcp_approx(1.0f + ex2_approx(g1 * ke))));
                st_relaxed(dst, av);
                st_relaxed(dst2, av);
                CK(7, 0);
            }
        }
        warm.done(sb + SM_SCRAP);
        if (cta == 0 && tid == (NAUX + NWORK) * 32) { g_work[0] = 0; g_work[32] = 0; g_cnt_z[0] = 0; }
        return;
    }
    if (warp >= NAUX) {
        const int wk = warp - NAUX;
        const uint32_t bar = sb + BAR_KV + wk * 8;
        const uint32_t buf = sb + SM_KV + wk * TILE_BYTES;
        uint64_t pol;
        asm volatile("createpolicy.fractional.L2::evict_first.b64 %0, 1.0;" : "=l"(pol));
        const int nstatic = NWORK * grid;
        constexpr int POOL0 = NUNITS - NPOOL;
        int uk = wk * grid + cta;
        wait_time(t_start + K0_AT_NS + uk * KSWEEP_NS / nstatic);
        request_tile(buf, &p.k, uk, bar, pol);
        uint32_t koff[3], voff[3];
        {
            const int r = lane & 7, hf = (lane >> 3) & 1;
            const int kkey = hf ? 8 + (r ^ 1) : r;
            const int vh = lane >> 4;
            const int vkey = ((r & 1) ? 8 : 0) + (vh ? (r ^ 1) : r);
#pragma unroll
            for (int b = 0; b < 3; b++) {
                const int rk = 3 * kkey + b, rv = 3 * vkey + b;
                koff[b] = buf + rk * 128 + (((lane >> 4) ^ (rk & 7)) << 4);
                voff[b] = buf + rv * 128 + ((hf ^ (rv & 7)) << 4);
            }
        }
        uint32_t phase = 0;
        uint32_t qf[12][2];
        auto load_q = [&](int u) {
            const uint32_t* q = g_early[u / UPB].q[0][j];
#pragma unroll
            for (int i = 0; i < 4; i++) {
                const uint4 a = ld_relaxed_v4(q + i * 32);
                const float2 c = ld_relaxed_f2(q + i * 32 + 4);
                qf[3 * i][0] = a.x; qf[3 * i][1] = a.y; qf[3 * i + 1][0] = a.z; qf[3 * i + 1][1] = a.w;
                qf[3 * i + 2][0] = __float_as_uint(c.x); qf[3 * i + 2][1] = __float_as_uint(c.y);
            }
        };
        load_q(uk);
        int uq[LAG];
        uint32_t sq[LAG];
#pragma unroll
        for (int i = 0; i < LAG; i++) { uq[i] = ~unit_of(uk + (i + 1) * nstatic); sq[i] = 0; }
        uint4 mv = make_uint4(0u, 0u, 0u, 0u);
        float freed = UPB;
        while (true) {
            const int uv = uq[0];
            uint32_t sv = sq[0];
#pragma unroll
            for (int i = 0; i + 1 < LAG; i++) { uq[i] = uq[i + 1]; sq[i] = sq[i + 1]; }
            uq[LAG - 1] = uk;
            if (uk < NUNITS) {
                PH(7);
#pragma unroll 1
                for (int it = 0; it < SPIN_MAX; it++) {
                    uint32_t lo = 0xffffffffu;
#pragma unroll
                    for (int i = 0; i < 12; i++) lo = min(lo, min(qf[i][0], qf[i][1]));
                    if (all(lo != 0)) break;
                    __nanosleep(250);
                    load_q(uk);
                }
                mbar_wait(bar, phase); phase ^= 1;
                PH(0); ARR();
                TSI(0, 16); TSI(1, 18);
                float acc[2][4][4] = {};
#pragma unroll
                for (int ks = 0; ks < 12; ks++) {
#pragma unroll
                    for (int mt = 0; mt < 4; mt++) {
                        uint32_t a[4];
                        ldsm4(a, (koff[ks >> 2] ^ ((ks & 3) << 5)) + mt * 6144);
                        mma16816(acc[ks & 1][mt], a, qf[ks][0], qf[ks][1]);
                    }
                }
                PH(1);
                TSI(0, 17); TSI(1, 19);
                if (uk < nstatic) wait_time(t_start + K1_AT_NS + uk * KSWEEP_NS / nstatic);
                if (uv < NUNITS) request_tile(buf, uv >= 0 ? &p.v : &p.k, uv >= 0 ? uv : ~uv, bar, pol);
                const float sa = sel4(j, acc[0][0][0], acc[0][1][0], acc[0][2][0], acc[0][3][0]) + sel4(j, acc[1][0][0], acc[1][1][0], acc[1][2][0], acc[1][3][0]);
                const float sc = sel4(j, acc[0][0][2], acc[0][1][2], acc[0][2][2], acc[0][3][2]) + sel4(j, acc[1][0][2], acc[1][1][2], acc[1][2][2], acc[1][3][2]);
                const uint32_t raw = pack_bf16(sa, sc);
                const float scale = -0.07216878364870322f;
                const uint32_t sk = pack_bf16(lo_f(raw) * scale, hi_f(raw) * scale);
                sq[LAG - 1] = sk;
                if (uk >= POOL0) st_relaxed(&g_st.score[uk - POOL0][lane], sk ? sk : 0x80008000u);
                int a = (int)(sk << 16), b = (int)(sk & 0xffff0000u);
                a ^= (a >> 31) & 0x7fff0000; b ^= (b >> 31) & 0x7fff0000;
                const int mx = __reduce_max_sync(0xffffffffu, max(a, b));
                if (lane == 0) st_relaxed(&g_early[uk / UPB].umax[uk % UPB], (uint32_t)mx | 1u);
            }
            if (uv < 0) {
                uk = ~uv;
                load_q(uk);
                continue;
            }
            if (uv >= NUNITS) break;
            const int bh = uv / UPB;
#pragma unroll 1
            for (int it = 0; it < SPIN_MAX; it++) {
                if (all((mv.x & mv.y & mv.z & mv.w & 1u) && (uv < POOL0 || sv != 0) && freed == UPB)) break;
                mv = ld_relaxed_v4(&g_early[bh].umax[lane * 4]);
                if (bh >= RING && bh < RED0) freed = __uint_as_float(ld_relaxed_u32(&g_st.oacc[oidx(bh - RING, (lane & 7) * 8)].w));
                if (uv >= POOL0) sv = ld_relaxed_u32(&g_st.score[uv - POOL0][lane]);
            }
            PH(2); CK(8, sv);
            int un = NUNITS, vn = 0;
            draw(un, g_work, uk < NUNITS && lane == 0);
            uint32_t tdraw;
            asm volatile("mov.u32 %0, %%globaltimer_lo;" : "=r"(tdraw));
            draw(vn, g_work + 32, uq[0] >= POOL0 && lane == 0);
            int mx = __reduce_max_sync(0xffffffffu, max(max((int)mv.x, (int)mv.y), max((int)mv.z, (int)mv.w))) & 0xffff0000;
            mx ^= (mx >> 31) & 0x7fff0000;
            const float m = __int_as_float(mx);
            const float l2e = 1.4426950408889634f;
            const uint32_t pp = pack_bf16(exp2f((lo_f(sv) - m) * l2e), exp2f((hi_f(sv) - m) * l2e));
            uint32_t pb[8];
#pragma unroll
            for (int t = 0; t < 4; t++) {
                pb[2 * t] = __shfl_sync(0xffffffffu, pp, 8 * j + t);
                pb[2 * t + 1] = __shfl_sync(0xffffffffu, pp, 8 * j + 4 + t);
            }
            float lacc[4] = {};
            const uint32_t ones[4] = {0x3f803f80u, 0x3f803f80u, 0x3f803f80u, 0x3f803f80u};
#pragma unroll
            for (int t = 0; t < 4; t++) mma16816(lacc, ones, pb[2 * t], pb[2 * t + 1]);
            if (uv < nstatic) {
                asm volatile("bar.sync 2, %0;" :: "n"((NWORK + 2) * 32) : "memory");
                TSW(3);
            }
            const int grp = 16 * j + 4 * (g & 1) + (g >> 1);
            uint32_t mode = (bh >= RED0) + (bh >= NBH - 4);
            float tag = mode ? 1.f : (float)(bh + 1), tag2 = fmaf(__uint_as_float(voff[0]), 0.f, tag);
            void* dst = mode == 0 ? (void*)&g_ring[bh % RING][uv % UPB][grp] :
                        mode == 1 ? (void*)&g_st.oacc[oidx(bh, grp)] : (void*)&g_st.ox[0].w[uv % OREP * 2 + (~(near_side(sb) ^ uv % OREP) & 1)][oidx(bh & 3, grp) * 4];
            if (mode == 2 && lane < 2) red_f2(reinterpret_cast<float*>(&g_st.lx.w[lane][(bh & 3) * 256]), lacc[0], 1.f);
            CK(10, __float_as_uint(lacc[0]));
            un = __shfl_sync(0xffffffffu, un, 0) + (LAG + 1) * nstatic;
            un = unit_of(un);
            vn = __shfl_sync(0xffffffffu, vn, 0);
            if (uq[0] >= POOL0) uq[0] = unit_of(POOL0 + vn);
            if (vn == FW_TICKET && lane == 0) st_relaxed(g_st.fw_time, tdraw | 1u);
            if (uq[0] < NUNITS && un >= NUNITS) {
                mv = ld_relaxed_v4(&g_early[uq[0] / UPB].umax[lane * 4]);
                if (uq[0] < RED0 * UPB) freed = 0.f;
                if (uq[0] >= POOL0) sq[0] = ld_relaxed_u32(&g_st.score[uq[0] - POOL0][lane]);
            }
            pin(dst); pin(mode); pin(tag); pin(tag2); pin(voff[0]); pin(voff[1]); pin(voff[2]);
            PH(3); CK(9, vn);
            mbar_wait(bar, phase); phase ^= 1;
            PH(4); ARR(); CK(12, lds32(buf));
            float acc[12][4] = {};
#pragma unroll
            for (int t = 0; t < 4; t++) {
#pragma unroll
                for (int mt = 0; mt < 12; mt++) {
                    uint32_t a[4];
                    ldsm4t(a, (voff[mt >> 2] ^ ((mt & 3) << 5)) + t * 6144);
                    mma16816(acc[mt], a, pb[2 * t], pb[2 * t + 1]);
                }
            }
            PH(5);
            if (lane == 0) PROG(un);
            if (un < NUNITS || uq[0] < NUNITS) request_tile(buf, un < NUNITS ? &p.k : &p.v, un < NUNITS ? un : uq[0], bar, pol);
            if (un < NUNITS || uq[0] < NUNITS) CK(11, 0);
            float o[6];
#pragma unroll
            for (int e = 0; e < 6; e++) {
                const int q = e % 3, c = (e / 3) * 2;
                o[e] = sel4(j, acc[q][c], acc[3 + q][c], acc[6 + q][c], acc[9 + q][c]);
            }
            put_groups(dst, mode, o, tag, tag2);
            CK(13, 0);
            if (un < NUNITS) load_q(un);
            if (lane == 0) red_f2(&g_st.lsum[bh][0].x, lacc[0], 1.f);
            PH(6);
            if (uq[0] >= NUNITS && un >= NUNITS) break;
            uk = un;
            if (uq[0] < NUNITS && un < NUNITS) {
                const int nb = uq[0] / UPB;
                mv = ld_relaxed_v4(&g_early[nb].umax[lane * 4]);
                freed = nb >= RING && nb < RED0 ? __uint_as_float(ld_relaxed_u32(&g_st.oacc[oidx(nb - RING, (lane & 7) * 8)].w)) : UPB;
                if (uq[0] >= POOL0) sq[0] = ld_relaxed_u32(&g_st.score[uq[0] - POOL0][lane]);
            }
        }
        TSW(4 + wk);
        return;
    }

    __nv_bfloat16* xs = reinterpret_cast<__nv_bfloat16*>(smem + SM_X);
    float* red = reinterpret_cast<float*>(smem + SM_RED);
    const int frow = (lane & 7) + ((lane >> 4) << 3), fcol = (lane >> 3) & 1;
    const uint32_t f64b = sb + (frow * 4 + (fcol ^ ((frow >> 1) & 3))) * 16;
    if (cta < NQ_CTAS) {
        TS(26);
        if (warp >= 4) {
            uint2 xr[5];
#pragma unroll
            for (int i = 0; i < 5; i++) xr[i] = *reinterpret_cast<const uint2*>(x + (warp - 4) * DM + i * 128 + lane * 4);
            float v[20];
#pragma unroll
            for (int i = 0; i < 5; i++) {
                v[4 * i] = lo_f(xr[i].x); v[4 * i + 1] = hi_f(xr[i].x); v[4 * i + 2] = lo_f(xr[i].y); v[4 * i + 3] = hi_f(xr[i].y);
            }
            layernorm20(v);
#pragma unroll
            for (int i = 0; i < 5; i++)
                *reinterpret_cast<uint2*>(xs + (warp - 4) * XPITCH + i * 128 + lane * 4) =
                    make_uint2(pack_bf16(v[4 * i], v[4 * i + 1]), pack_bf16(v[4 * i + 2], v[4 * i + 3]));
        }
        aux_sync();
        TS(27);
        mbar_wait(sb + BAR_WQ + (warp >> 1) * 8, 0);
        TS(1);
        const uint32_t xfrag = sb + SM_X + ((g & 3) * XPITCH + 2 * j) * 2;
        float acc[3][4] = {};
#pragma unroll
        for (int s = 0; s < 5; s++) {
            const int ks = warp * 5 + s;
            const uint32_t b0 = lds32(xfrag + ks * 32), b1 = lds32(xfrag + ks * 32 + 16);
            const int row = ks * 16 + frow;
#pragma unroll
            for (int mt = 0; mt < 3; mt++) {
                uint32_t a[4];
                ldsm4t(a, sb + SM_W + (row * 6 + 2 * mt + fcol) * 16);
                mma16816(acc[mt], a, b0, b1);
            }
        }
        if (j < 2) {
#pragma unroll
            for (int mt = 0; mt < 3; mt++) {
                *reinterpret_cast<float2*>(red + warp * 216 + mt * 72 + g * 4 + 2 * j) = make_float2(acc[mt][0], acc[mt][1]);
                *reinterpret_cast<float2*>(red + warp * 216 + mt * 72 + 36 + g * 4 + 2 * j) = make_float2(acc[mt][2], acc[mt][3]);
            }
        }
        aux_sync();
        if (warp < 4) {
            const float* src = red + min(g, 5) * 36 + warp * 8 + j;
            float s0 = 0.f, s1 = 0.f;
#pragma unroll
            for (int w = 0; w < 8; w++) { s0 += src[w * 216]; s1 += src[w * 216 + 4]; }
            st_relaxed(&g_early[j * NH + (cta >> 2)].q[cta & 3][warp][g], pack_neg(s0, s1));
        }
        TS(28);
    }
    fin_sync<3>();
    mbar_wait(sb + BAR_WO, 0);
    TS(7);
    uint32_t part = sb + SM_RED + (warp * 32 + 8 * j + g) * 4;

#pragma unroll 1
    for (int b = 0; b < NB; b++) {
        if (cta >= NE_CTAS) {
            uint32_t a[6][2][4];
#pragma unroll
            for (int s = 0; s < 6; s++) {
#pragma unroll
                for (int mt = 0; mt < 2; mt++) ldsm4t(a[s][mt], (f64b ^ (mt * 32)) + SM_A + (warp * 6 + s) * 1024);
            }
            const int bh = b * NH + 28 + (warp >> 1);
            const int side = near_side(sb) ^ 1;
            const void* osrc[OREP];
#pragma unroll
            for (int c = 0; c < OREP; c++)
                osrc[c] = b == NB - 1 ? (const void*)&g_st.ox[c >> 1].w[side ^ (c & 1) * 3][oidx(bh & 3, (warp & 1) * 32 + lane) * 4] : &g_st.oacc[oidx(bh, (warp & 1) * 32 + lane)];
            const void* lsrc = b == NB - 1 ? (const void*)&g_st.lx.w[side][(bh & 3) * 256] : g_st.lsum[bh];
            wait_row_o(scr, bh, 1);
            const float rl = rcp_approx(wait_sum(lsrc, UPB)) * (b == NB - 1 ? 1.f : 1.f / OREP), full = b == NB - 1 ? UPB : UPB * OREP;
            float4 ov;
            float px, py, pz;
            Warm warm;
#pragma unroll 1
            for (int it = 0; it < SPIN_MAX; it++) {
                wait_slot<PH_O>();
                float4 oc[OREP];
#pragma unroll
                for (int c = 0; c < OREP; c++) oc[c] = ld_relaxed_f4(osrc[c]);
                warm();
                ov = oc[0];
#pragma unroll
                for (int c = 1; c < OREP; c++) { ov.x += oc[c].x; ov.y += oc[c].y; ov.z += oc[c].z; ov.w += oc[c].w; }
                ov.x *= rl; ov.y *= rl; ov.z *= rl;
                px = __shfl_xor_sync(0xffffffffu, ov.x, 4); py = __shfl_xor_sync(0xffffffffu, ov.y, 4); pz = __shfl_xor_sync(0xffffffffu, ov.z, 4);
                if (all(ov.w == full)) break;
            }
            CK(0, __float_as_uint(ov.x));
            if (ov.x != 1.2345f && warp == 7) TSW(14);
            const uint32_t w[3] = {pack_bf16(ov.x, px), pack_bf16(ov.y, py), pack_bf16(ov.z, pz)};
            float acc[2][2][4] = {};
#pragma unroll
            for (int s = 0; s < 6; s++) {
                const uint32_t b0 = __shfl_sync(0xffffffffu, w[s % 3], (s / 3) * 16 + j);
                const uint32_t b1 = __shfl_sync(0xffffffffu, w[s % 3], (s / 3) * 16 + 8 + j);
#pragma unroll
                for (int mt = 0; mt < 2; mt++) mma16816(acc[mt][s & 1], a[s][mt], b0, b1);
            }
            sts32f(part, sel4(j, acc[0][0][0] + acc[0][1][0], acc[0][0][2] + acc[0][1][2], acc[1][0][0] + acc[1][1][0], acc[1][0][2] + acc[1][1][2]));
            CK(1, 0);
            fin_arrive<4>();
            warm.done(sb + SM_SCRAP);
            fin_sync<5>();
            if (cta < NE_CTAS + 4 && tid < 64) reinterpret_cast<uint4*>(&g_early[b * NH + 28 + cta - NE_CTAS])[tid] = make_uint4(0u, 0u, 0u, 0u);
        } else {
            const int bh = b * NH + (cta >> 2);
            if (warp == 0) wait_row_o(scr, bh, UPB);
            aux_sync();
            if (warp < 5) {
                uint32_t ob[12][2];
                load_o<4>(ob, scr, bh, 0, j);
                float acc[2][2][4] = {};
#pragma unroll
                for (int ks = 0; ks < 12; ks++) {
#pragma unroll
                    for (int mt = 0; mt < 2; mt++) {
                        uint32_t a[4];
                        ldsm4t(a, (f64b ^ (mt * 32)) + SM_A + warp * 12288 + ks * 1024);
                        mma16816(acc[mt][ks & 1], a, ob[ks][0], ob[ks][1]);
                    }
                }
                red_f2(&g_st.attn[b][(cta & 3) * 160 + warp * 32 + 8 * j + g].x,
                       sel4(j, acc[0][0][0] + acc[0][1][0], acc[0][0][2] + acc[0][1][2], acc[1][0][0] + acc[1][1][0], acc[1][0][2] + acc[1][1][2]), 1.f);
                TS(8);
            } else if (warp > 5 && (cta & 3) == 0) {
                reinterpret_cast<uint4*>(&g_early[bh])[tid - 192] = make_uint4(0u, 0u, 0u, 0u);
            }
        }
        if (b < NB - 2) continue;

        if (is_f(cta)) {
            uint32_t ga[10][2][4];
            uint4 hv[5];
            const uint32_t hfrag = sb + SM_X + min(g, 4) * HPITCH + ((warp >> 1) * 80 + 4 * j) * 4;
            if (b == NB - 1) mbar_wait(sb + BAR_FW + warp * 8, 0);
            if (warp == 7) TSW(10);
            CK(12, lds32(sb + SM_W));
#pragma unroll
            for (int s = 0; s < 10; s++) {
#pragma unroll
                for (int mt = 0; mt < 2; mt++) ldsm4t(ga[s][mt], (f64b ^ (mt * 32)) + SM_W + (warp * 10 + s) * 1024);
            }
            const uint32_t gpart = sb + SM_RED + (warp >> 1) * 640 + j * 256 + ((g + 2 * j) & 7) * 16 + (warp & 1) * 8;
            mbar_wait(sb + BAR_H, b & 1);
#pragma unroll
            for (int s = 0; s < 5; s++) hv[s] = lds128(hfrag + s * 64);
            CK(4, hv[0].x);
            float acc[2][2][4] = {};
#pragma unroll
            for (int s = 0; s < 10; s++) {
#pragma unroll
                for (int mt = 0; mt < 2; mt++)
                    mma16816(acc[mt][s & 1], ga[s][mt], (s & 1) ? hv[s >> 1].z : hv[s >> 1].x, (s & 1) ? hv[s >> 1].w : hv[s >> 1].y);
            }
#pragma unroll
            for (int mt = 0; mt < 2; mt++) {
                if (j < 3) sts64f(gpart + mt * 2560, acc[mt][0][0] + acc[mt][1][0], acc[mt][0][2] + acc[mt][1][2]);
                if (j < 2) sts64f(gpart + mt * 2560 + 128, acc[mt][0][1] + acc[mt][1][1], acc[mt][0][3] + acc[mt][1][3]);
            }
            CK(5, 0);
            asm volatile("bar.arrive 4, 320;" ::: "memory");
        } else if (is_g(cta)) {
            const uint32_t* asrc = &g_st.ax[0].w[(~b & 1) * 2 + near_side(sb)][warp * 128 + ((g >> 2) * 2 + (j >> 1)) * 32 + (g & 3) * 8 + (j & 1) * 4];
            const uint32_t ypart = sb + SM_RED2 + warp * 512 + j * 128 + ((g + 2 * j) & 7) * 16;
            uint32_t wb[12][4];
            uint4 va[3] = {};
            uint32_t lo[3] = {};
            auto ask = [&]() {
#pragma unroll
                for (int i = 0; i < 3; i++) ld_relaxed_v4_if(va[i], asrc + i * 4096, lo[i] == 0);
            };
            auto complete = [&]() {
#pragma unroll
                for (int i = 0; i < 3; i++) lo[i] = min(min(va[i].x, va[i].y), min(va[i].z, va[i].w));
                return all(min(lo[0], min(lo[1], lo[2])) != 0);
            };
            const int jj = (lane & 7) >> 1, q = jj >> 1, hi = lane >> 4;
            const uint32_t wsrc = sb + SM_W + warp * 6144 + q * 512 + ((hi ^ q) * 4 + (jj & 1) * 2 + (lane & 1)) * 32 + ((fcol ^ hi ^ q) << 4);
            mbar_wait(sb + BAR_H, b & 1);
            if (b == NB - 1) mbar_wait(sb + BAR_FW + warp * 8, 0);
            if (warp == 7) TSW(11);
            CK(13, lds32(sb + SM_W));
            ask();
#pragma unroll
            for (int s = 0; s < 12; s++) ldsm4t(wb[s], wsrc + (s >> 2) * 2048 + (s & 1) * 1024 + (s & 2) * 128);
            Warm warm;
            if (!complete()) {
#pragma unroll 1
                for (int it = 0; it < SPIN_MAX; it++) {
                    ask();
                    warm();
                    if (complete()) break;
                }
            }
            CK(8, va[0].x);
            if (va[0].x != 0x12345 && warp == 7) TSW(15);
            float acc[6][4] = {};
#pragma unroll
            for (int s = 0; s < 12; s++) {
                const uint4 v = va[s >> 2];
                mma16816(acc[s % 6], wb[s], (s & 2) ? v.z : v.x, (s & 2) ? v.w : v.y);
            }
            float y[4];
#pragma unroll
            for (int e = 0; e < 4; e++) y[e] = j < 2 ? (acc[0][e] + acc[2][e]) + acc[4][e] : (acc[1][e] + acc[3][e]) + acc[5][e];
            sts128f(ypart, y[0], y[1], y[2], y[3]);
            CK(9, 0);
            fin_arrive<6>();
            warm.done(sb + SM_SCRAP);
        }
    }
}

typedef CUresult (*EncodeFn)(CUtensorMap*, CUtensorMapDataType, cuuint32_t, void*, const cuuint64_t*, const cuuint64_t*,
                             const cuuint32_t*, const cuuint32_t*, CUtensorMapInterleave, CUtensorMapSwizzle,
                             CUtensorMapL2promotion, CUtensorMapFloatOOBfill);

CUtensorMap make_map(EncodeFn enc, void* ptr, uint64_t cols, uint64_t rows, uint32_t bcols, uint32_t brows,
                     CUtensorMapSwizzle sw, CUtensorMapL2promotion promo) {
    CUtensorMap m;
    const cuuint64_t dims[2] = {cols, rows};
    const cuuint64_t strides[1] = {cols * 2};
    const cuuint32_t box[2] = {bcols, brows};
    const cuuint32_t es[2] = {1, 1};
    enc(&m, CU_TENSOR_MAP_DATA_TYPE_BFLOAT16, 2, ptr, dims, strides, box, es, CU_TENSOR_MAP_INTERLEAVE_NONE, sw, promo,
        CU_TENSOR_MAP_FLOAT_OOB_FILL_NONE);
    return m;
}

}

extern "C" void kernel_launch(void* const* d_in, const int* in_sizes, int n_in, void* d_out, int out_size) {
    (void)in_sizes; (void)n_in; (void)out_size;
    static EncodeFn enc = nullptr;
    static int sms = 0;
    static Scratch* scr = nullptr;
    if (!enc) {
        cudaDriverEntryPointQueryResult qr;
        cudaGetDriverEntryPoint("cuTensorMapEncodeTiled", (void**)&enc, cudaEnableDefault, &qr);
        void* raw = nullptr;
        cudaGetSymbolAddress(&raw, g_raw);
        scr = reinterpret_cast<Scratch*>((reinterpret_cast<uintptr_t>(raw) + PAGE - 1) & ~(uintptr_t)(PAGE - 1));
        int dev = 0;
        cudaGetDevice(&dev);
        cudaDeviceGetAttribute(&sms, cudaDevAttrMultiProcessorCount, dev);
        cudaFuncSetAttribute(fused_decode_kernel, cudaFuncAttributeMaxDynamicSharedMemorySize, SM_TOTAL);
    }
    if (sms < NCTAS) return;
    const CUtensorMapL2promotion WPROMO = CU_TENSOR_MAP_L2_PROMOTION_L2_128B;
    Params p;
    p.k = make_map(enc, d_in[1], 64, (uint64_t)NBH * SK * 3, 64, TILE_ROWS, CU_TENSOR_MAP_SWIZZLE_128B, CU_TENSOR_MAP_L2_PROMOTION_NONE);
    p.v = make_map(enc, d_in[2], 64, (uint64_t)NBH * SK * 3, 64, TILE_ROWS, CU_TENSOR_MAP_SWIZZLE_128B, CU_TENSOR_MAP_L2_PROMOTION_NONE);
    p.wq = make_map(enc, d_in[3], NH * DH, DM, 48, 160, CU_TENSOR_MAP_SWIZZLE_NONE, WPROMO);
    p.wo = make_map(enc, d_in[4], DM, NH * DH, 32, DH, CU_TENSOR_MAP_SWIZZLE_64B, WPROMO);
    p.wg = make_map(enc, d_in[7], FF, DM, 32, 160, CU_TENSOR_MAP_SWIZZLE_64B, WPROMO);
    p.wu = make_map(enc, d_in[8], FF, DM, 32, 160, CU_TENSOR_MAP_SWIZZLE_64B, WPROMO);
    {
        const cuuint64_t dims[4] = {DM, 2, 8, FF / 16}, strides[3] = {8 * DM * 2, DM * 2, 16 * DM * 2};
        const cuuint32_t box[4] = {16, 2, 8, 12}, es[4] = {1, 1, 1, 1};
        enc(&p.wd, CU_TENSOR_MAP_DATA_TYPE_BFLOAT16, 4, d_in[9], dims, strides, box, es, CU_TENSOR_MAP_INTERLEAVE_NONE,
            CU_TENSOR_MAP_SWIZZLE_32B, WPROMO, CU_TENSOR_MAP_FLOAT_OOB_FILL_NONE);
    }
    fused_decode_kernel<<<NCTAS, NTHREADS, SM_TOTAL, cudaStreamPerThread>>>(
        scr, (const __nv_bfloat16*)d_in[0], (const __nv_bfloat16*)d_in[6], (__nv_bfloat16*)d_out, p);
}
```

```cpp
#include <cuda_runtime.h>
#include <cuda_bf16.h>
#include <cuda.h>
#include <stdint.h>

namespace {

constexpr int NB = 4, NH = 32, SK = 8192, DH = 192, DM = 640, FF = 1536;
constexpr int NBH = NB * NH;
constexpr int TILE = 64;
constexpr int UPB = SK / TILE;
constexpr int NUNITS = NBH * UPB;
constexpr int TILE_BYTES = TILE * DH * 2;
constexpr int TILE_ROWS = TILE * 3;
constexpr int NCTAS = 132;
constexpr int NQ_CTAS = 128;
constexpr int NE_CTAS = 112;
__host__ __device__ constexpr bool is_f(int cta) { return cta < NE_CTAS && cta % 14 < 11 && !(cta & 1); }
__host__ __device__ constexpr bool is_g(int cta) { return cta < NE_CTAS && cta % 14 < 11 && (cta & 1); }
__host__ __device__ constexpr int ffn_slice(int cta) { return cta / 14 * ((cta & 1) ? 5 : 6) + cta % 14 / 2; }

#define NWORK 2
#define LAG 3
#define NPOOL 896
#define RED0 116
#define RING 12
#define OREP 2
#define K0_AT_NS 1000
#define WO_AT_NS (K0_AT_NS + 2000)
#define K1_AT_NS (K0_AT_NS + 4400)
#define WO_STEP_NS 75
#define CLEAR_AT_NS 7000
constexpr int KSWEEP_NS = 2000;
#define FW_TICKET (NPOOL + 32)
#define FW_AT_NS 2090
#define FW_GAP 280
#define FW_MID 2100
#define FW_GAP2 200
#define HGATE_NS 700
#define SLOT_TICKS 9
#define SLOT_OPEN 3
#define PH_O 0
#define PH_H 8
#define PH_M 2
#define NPROBE 24
#define MIX_R 6
#define MIX_FROM 1
#define MIX_ROWS 3
constexpr int MIX = MIX_ROWS * UPB, MIX1 = (NBH - 4) * UPB, MIX0 = MIX1 - (MIX1 - MIX_FROM * NWORK * NCTAS) / MIX * MIX;
static_assert((MIX1 - (NUNITS - NPOOL)) % MIX == 0, "the pool starts with a group of rows");
__device__ __forceinline__ int unit_of(int t) {
    const unsigned r = (unsigned)(t - MIX0) % MIX, e = t - MIX1;
    if (e < 4 * UPB) return MIX1 + (e & 256) + (e & 3) * 64 + (e & 255) / 4;
    return t < MIX0 || t >= MIX1 ? t : t - r + r % MIX_R * (MIX / MIX_R) + r / MIX_R;
}
static_assert(FW_TICKET < NPOOL + NWORK * NCTAS, "every worker draws one ticket beyond the pool");
constexpr int NAUX = 8;
constexpr int NTHREADS = (NAUX + NWORK + 2) * 32;
constexpr int SPIN_MAX = 1 << 22;

constexpr int SM_KV = 0;
constexpr int SM_A = SM_KV + NWORK * TILE_BYTES;
constexpr int SM_W = SM_A + 61440;
constexpr int SM_X = SM_W + 81920;
constexpr int XPITCH = 648;
constexpr int HPITCH = 1344;
constexpr int SM_RED = SM_X + 5 * HPITCH + 64;
constexpr int SM_RED2 = SM_RED + 8 * 48 * 4 * 4;
constexpr int SM_MISC = SM_RED2 + 4096;
constexpr int BAR_WQ = SM_MISC, SM_SCRAP = SM_MISC + 32, BAR_WO = SM_MISC + 40, SM_SIDE = SM_MISC + 48, BAR_H = SM_MISC + 56, BAR_FW = SM_MISC + 64;
constexpr int BAR_KV = BAR_FW + 64;
constexpr int SM_TOTAL = BAR_KV + NWORK * 8;
static_assert(SM_W % 1024 == 0 && NB * XPITCH * 2 <= 4 * HPITCH && SM_RED % 128 == 0, "smem layout");

struct Params {
    CUtensorMap k, v;
    CUtensorMap wq;
    CUtensorMap wo;
    CUtensorMap wg, wu;
    CUtensorMap wd;
};

struct Early {
    uint32_t q[4][4][8];
    uint32_t umax[UPB];
};
struct Twin { uint32_t w[4][1024]; };
constexpr int PROBE = 1024 - 32;
#define LSTRIDE 16
struct State {
    Twin ax[3];
    Twin hx;
    Twin ox[(OREP + 1) / 2];
    Twin lx;
    float4 oacc[NBH * 64];
    float2 attn[NB][DM];
    uint32_t fw_time[32];
    float2 lsum[NBH][LSTRIDE];
    uint32_t score[NPOOL][32];
};
__host__ __device__ constexpr int oidx(int row, int grp) {
    return (row >> 2) * 256 + ((row & 1) * 2 + (grp >> 5)) * 64 + (row & 2) * 16 + (grp & 31);
}
constexpr int STATE_V4 = ((sizeof(State) / 32 + NQ_CTAS - 1) / NQ_CTAS) * 2;
static_assert(sizeof(State) % 32 == 0, "State is cleared in whole sectors");
static_assert(sizeof(Early) == 64 * 16, "an Early entry is cleared by 64 threads");
struct Scratch {
    State st;
    unsigned work[64];
    unsigned cnt_z[32];
    Early early[NBH];
    alignas(4096) float4 ring[RING][UPB][64];
};
constexpr size_t PAGE = 2u << 20;
static_assert(sizeof(Scratch) <= PAGE, "scratch must fit one page");
__device__ __align__(128) unsigned char g_raw[2 * PAGE];
#define g_early scr->early
#define g_st scr->st
#define g_ring scr->ring
#define g_cnt_z scr->cnt_z
#define g_work scr->work
#define ALL_LOADERS 0
#define TS(i)
#define TSW(i)
#define TS2(i)
#define TSI(n, i)
#define PH(i)
#define CK(i, dep)
#define ARR()
#define PROG(u)

__device__ __forceinline__ uint32_t s2u(const void* p) { return (uint32_t)__cvta_generic_to_shared(p); }
__device__ __forceinline__ void mbar_init(uint32_t bar, int cnt) {
    asm volatile("mbarrier.init.shared::cta.b64 [%0], %1;" :: "r"(bar), "r"(cnt) : "memory");
}
__device__ __forceinline__ void mbar_wait(uint32_t bar, uint32_t parity) {
    asm volatile("{\n.reg .pred p;\n.reg .u32 n;\nmov.u32 n, 0;\nWAIT_LOOP:\n"
                 "mbarrier.try_wait.parity.shared::cta.b64 p, [%0], %1;\n"
                 "@p bra WAIT_DONE;\nadd.u32 n, n, 1;\nsetp.lt.u32 p, n, %2;\n@p bra WAIT_LOOP;\nWAIT_DONE:\n}"
                 :: "r"(bar), "r"(parity), "n"(SPIN_MAX) : "memory");
}
__device__ __forceinline__ void request_tile(uint32_t dst, const CUtensorMap* tm, int unit, uint32_t bar, uint64_t pol) {
    asm volatile("{\n.reg .pred p;\nelect.sync _|p, 0xffffffff;\n"
                 "@p mbarrier.arrive.expect_tx.shared::cta.b64 _, [%2], %6;\n"
                 "@p cp.async.bulk.tensor.2d.shared::cluster.global.mbarrier::complete_tx::bytes.L2::cache_hint "
                 "[%0], [%1, {%3, %4}], [%2], %5;\n}"
                 :: "r"(dst), "l"(tm), "r"(bar), "r"(0), "r"(unit * TILE_ROWS), "l"(pol), "n"(TILE_BYTES) : "memory");
}
__device__ __forceinline__ void put_groups(void* dst, int mode, const float (&o)[6], float tag, float tag2) {
    asm volatile("{\n.reg .pred s, t;\n.reg .b128 u, v;\n.reg .b64 a, b;\n"
                 "setp.eq.s32 s, %1, 0;\nsetp.ne.s32 t, %1, 2;\nxor.b64 a, %0, 4096;\n"
                 "@t bra.uni SINGLE;\n"
                 "red.relaxed.gpu.global.add.v4.f32 [a], {%2,%3,%4,%8};\n"
                 "red.relaxed.gpu.global.add.v4.f32 [a+128], {%5,%6,%7,%9};\n"
                 "SINGLE:\n"
                 "@s bra.uni STORE;\n"
                 "red.relaxed.gpu.global.add.v4.f32 [%0], {%2,%3,%4,%8};\n"
                 "red.relaxed.gpu.global.add.v4.f32 [%0+128], {%5,%6,%7,%9};\n"
                 "STORE:\n"
                 "mov.b64 a, {%2, %3};\nmov.b64 b, {%4, %8};\nmov.b128 u, {a, b};\n"
                 "mov.b64 a, {%5, %6};\nmov.b64 b, {%7, %9};\nmov.b128 v, {a, b};\n"
                 "@s st.relaxed.gpu.global.b128 [%0], u;\n@s st.relaxed.gpu.global.b128 [%0+128], v;\n}"
                 :: "l"(dst), "r"(mode), "f"(o[0]), "f"(o[1]), "f"(o[2]), "f"(o[3]), "f"(o[4]), "f"(o[5]), "f"(tag), "f"(tag2) : "memory");
}
__device__ __forceinline__ void request_box(uint32_t dst, const CUtensorMap* tm, int col, int row, uint32_t bar, uint32_t bytes) {
    asm volatile("{\n.reg .pred p, q;\nelect.sync _|p, 0xffffffff;\nsetp.ne.and.u32 q, %5, 0, p;\n"
                 "@q mbarrier.arrive.expect_tx.shared::cta.b64 _, [%2], %5;\n"
                 "@p cp.async.bulk.tensor.2d.shared::cluster.global.mbarrier::complete_tx::bytes [%0], [%1, {%3, %4}], [%2];\n}"
                 :: "r"(dst), "l"(tm), "r"(bar), "r"(col), "r"(row), "r"(bytes) : "memory");
}
__device__ __forceinline__ uint32_t lds32(uint32_t addr) {
    uint32_t v;
    asm volatile("ld.shared.u32 %0, [%1];" : "=r"(v) : "r"(addr) : "memory");
    return v;
}
__device__ __forceinline__ void ldsm4(uint32_t (&r)[4], uint32_t addr) {
    asm volatile("ldmatrix.sync.aligned.m8n8.x4.shared.b16 {%0,%1,%2,%3}, [%4];"
                 : "=r"(r[0]), "=r"(r[1]), "=r"(r[2]), "=r"(r[3]) : "r"(addr) : "memory");
}
__device__ __forceinline__ void ldsm4t(uint32_t (&r)[4], uint32_t addr) {
    asm volatile("ldmatrix.sync.aligned.m8n8.x4.trans.shared.b16 {%0,%1,%2,%3}, [%4];"
                 : "=r"(r[0]), "=r"(r[1]), "=r"(r[2]), "=r"(r[3]) : "r"(addr) : "memory");
}
__device__ __forceinline__ void mma16816(float (&c)[4], const uint32_t (&a)[4], uint32_t b0, uint32_t b1) {
    asm volatile("mma.sync.aligned.m16n8k16.row.col.f32.bf16.bf16.f32 {%0,%1,%2,%3}, {%4,%5,%6,%7}, {%8,%9}, {%0,%1,%2,%3};"
                 : "+f"(c[0]), "+f"(c[1]), "+f"(c[2]), "+f"(c[3])
                 : "r"(a[0]), "r"(a[1]), "r"(a[2]), "r"(a[3]), "r"(b0), "r"(b1));
}
struct Warm {
    float c[4] = {};
    __device__ __forceinline__ void operator()() {
        asm volatile("mma.sync.aligned.m16n8k8.row.col.f32.bf16.bf16.f32 {%0,%1,%2,%3}, {%4,%4}, {%4}, {%0,%1,%2,%3};"
                     : "+f"(c[0]), "+f"(c[1]), "+f"(c[2]), "+f"(c[3]) : "r"(0));
    }
    __device__ __forceinline__ void done(uint32_t scrap) {
        asm volatile("{\n.reg .pred p;\nsetp.gt.f32 p, %1, 0f3f800000;\n@p st.shared.f32 [%0], %1;\n}" :: "r"(scrap), "f"(c[0]) : "memory");
    }
};
__device__ __forceinline__ uint4 ld_relaxed_v4(const void* p) {
    uint4 v;
    asm volatile("ld.relaxed.gpu.global.v4.u32 {%0,%1,%2,%3}, [%4];" : "=r"(v.x), "=r"(v.y), "=r"(v.z), "=r"(v.w) : "l"(p) : "memory");
    return v;
}
__device__ __forceinline__ float4 ld_relaxed_f4(const void* p) {
    float4 v;
    asm volatile("ld.relaxed.gpu.global.v4.f32 {%0,%1,%2,%3}, [%4];" : "=f"(v.x), "=f"(v.y), "=f"(v.z), "=f"(v.w) : "l"(p) : "memory");
    return v;
}
__device__ __forceinline__ float2 ld_relaxed_f2(const void* p) {
    float2 v;
    asm volatile("ld.relaxed.gpu.global.v2.f32 {%0,%1}, [%2];" : "=f"(v.x), "=f"(v.y) : "l"(p) : "memory");
    return v;
}
__device__ __forceinline__ float4 ld_relaxed_b128(const void* p) {
    float4 v;
    asm volatile("{\n.reg .b128 t;\n.reg .b64 a, b;\nld.relaxed.gpu.global.b128 t, [%4];\nmov.b128 {a, b}, t;\n"
                 "mov.b64 {%0, %1}, a;\nmov.b64 {%2, %3}, b;\n}" : "=f"(v.x), "=f"(v.y), "=f"(v.z), "=f"(v.w) : "l"(p) : "memory");
    return v;
}
__device__ __forceinline__ void st_relaxed_b128(void* p, float x, float y, float z, float w) {
    asm volatile("{\n.reg .b128 t;\n.reg .b64 a, b;\nmov.b64 a, {%1, %2};\nmov.b64 b, {%3, %4};\nmov.b128 t, {a, b};\n"
                 "st.relaxed.gpu.global.b128 [%0], t;\n}" :: "l"(p), "f"(x), "f"(y), "f"(z), "f"(w) : "memory");
}
__device__ __forceinline__ unsigned ld_acquire(const unsigned* p) {
    unsigned v;
    asm volatile("ld.acquire.gpu.global.u32 %0, [%1];" : "=r"(v) : "l"(p) : "memory");
    return v;
}
__device__ __forceinline__ void st_relaxed(void* p, uint32_t v) {
    asm volatile("st.relaxed.gpu.global.u32 [%0], %1;" :: "l"(p), "r"(v) : "memory");
}
__device__ __forceinline__ void red_f2(float* p, float a, float b) {
    asm volatile("red.relaxed.gpu.global.add.v2.f32 [%0], {%1,%2};" :: "l"(p), "f"(a), "f"(b) : "memory");
}
__device__ __forceinline__ void draw(int& ticket, unsigned* ctr, bool pred) {
    asm volatile("{\n.reg .pred p;\nsetp.ne.u32 p, %2, 0;\n@p atom.relaxed.gpu.global.inc.u32 %0, [%1], 0x7fffffff;\n}"
                 : "+r"(ticket) : "l"(ctr), "r"((uint32_t)pred) : "memory");
}
__device__ __forceinline__ void red_release(unsigned* p) {
    asm volatile("red.release.gpu.global.add.u32 [%0], 1;" :: "l"(p) : "memory");
}
__device__ __forceinline__ uint32_t ld_relaxed_u32(const void* p) {
    uint32_t v;
    asm volatile("ld.relaxed.gpu.global.u32 %0, [%1];" : "=r"(v) : "l"(p) : "memory");
    return v;
}
__device__ __forceinline__ float rcp_approx(float v) {
    float r;
    asm("rcp.approx.ftz.f32 %0, %1;" : "=f"(r) : "f"(v));
    return r;
}
__device__ __forceinline__ float ex2_approx(float v) {
    float e;
    asm("ex2.approx.ftz.f32 %0, %1;" : "=f"(e) : "f"(v));
    return e;
}
__device__ __forceinline__ float sigmoid_approx(float v) { return rcp_approx(1.0f + ex2_approx(v * -1.4426950408889634f)); }
__device__ __forceinline__ float sqrt_approx(float v) {
    float r;
    asm("sqrt.approx.ftz.f32 %0, %1;" : "=f"(r) : "f"(v));
    return r;
}
__device__ __forceinline__ bool all(bool v) { return __all_sync(0xffffffffu, v); }
__device__ __forceinline__ void wait_count(const unsigned* p, unsigned target) {
#pragma unroll 1
    for (int it = 0; it < SPIN_MAX; it++) {
        if (all(ld_acquire(p) >= target)) break;
        __nanosleep(400);
    }
}
__device__ __forceinline__ float wait_sum(const void* p, float n, int nap = 0) {
    float2 v;
#pragma unroll 1
    for (int it = 0; it < SPIN_MAX; it++) {
        v = ld_relaxed_f2(p);
        if (all(v.y >= n)) break;
        if (all(v.y == 0.f)) __nanosleep(600);
        else if (nap) __nanosleep(nap);
    }
    return v.x;
}
__device__ __forceinline__ void wait_row(const Scratch* scr, int bh, float n) { wait_sum(g_st.lsum[bh], n); }
__device__ __forceinline__ void wait_row_o(const Scratch* scr, int bh, float n) {
    wait_row(scr, bh, n);
    if (bh >= RED0) return;
#pragma unroll 1
    for (int it = 0; it < SPIN_MAX; it++) {
        if (all(__uint_as_float(ld_relaxed_u32(&g_st.oacc[oidx(bh, 0)].w)) == UPB)) break;
        __nanosleep(300);
    }
}
constexpr uint32_t SLOT_K = (uint32_t)(((1ull << 32) + SLOT_TICKS - 1) / SLOT_TICKS);
#define SLOT_ASM(t, n, p, phase, k, open) \
    "mov.u32 " n ", 0;\nSLOT:\nmov.u32 " t ", %%globaltimer_lo;\nadd.u32 " n ", " n ", 1;\nsetp.lt.u32 " p ", " n ", 24;\nshr.u32 " t ", " t ", 5;\n" \
    "mad.lo.u32 " t ", " t ", " k ", " phase ";\nsetp.ge.and.u32 " p ", " t ", " open ", " p ";\n@" p " bra.uni SLOT;\n"
template <int PHASE> __host__ __device__ constexpr uint32_t slot_phase() { return SLOT_K / 2 - PHASE * SLOT_K; }
template <int PHASE> __device__ __forceinline__ void wait_slot() {
    if (PHASE < 0) return;
    asm volatile("{\n.reg .pred p;\n.reg .b32 t, n;\n" SLOT_ASM("t", "n", "p", "%0", "%1", "%2") "}"
                 :: "n"(slot_phase<PHASE>()), "n"(SLOT_K), "n"(SLOT_OPEN * SLOT_K) : "memory");
}
__device__ __forceinline__ void wait_time(uint32_t t) {
#pragma unroll 1
    for (int it = 0; it < SPIN_MAX; it++) {
        uint32_t now;
        asm volatile("mov.u32 %0, %%globaltimer_lo;" : "=r"(now));
        if (all((int)(now - t) >= 0)) break;
    }
}
__device__ __forceinline__ void wait_clock(uint32_t t, Warm& warm) { while (!all((int)(clock() - t) >= 0)) { warm(); } }
__device__ __forceinline__ uint32_t pack_bf16(float lo, float hi) {
    uint32_t r;
    asm("cvt.rn.bf16x2.f32 %0, %1, %2;" : "=r"(r) : "f"(hi), "f"(lo));
    return r;
}
__device__ __forceinline__ float bf16r(float v) { return __uint_as_float(pack_bf16(0.f, v)); }
__device__ __forceinline__ uint32_t nonzero(uint32_t w) { return w ? w : 0x80008000u; }
__device__ __forceinline__ uint32_t pack_neg(float lo, float hi) { return nonzero(pack_bf16(-lo, -hi)); }
__device__ __forceinline__ float lo_f(uint32_t v) { return __uint_as_float(v << 16); }
__device__ __forceinline__ float hi_f(uint32_t v) { return __uint_as_float(v & 0xffff0000u); }
__device__ __forceinline__ float warp_sum(float v) {
#pragma unroll
    for (int o = 16; o; o >>= 1) v += __shfl_xor_sync(0xffffffffu, v, o);
    return v;
}
__device__ __forceinline__ void layernorm20(float (&v)[20]) {
    float s = 0.f;
#pragma unroll
    for (int i = 0; i < 20; i++) s += v[i];
    const float mean = warp_sum(s) * (1.0f / DM);
    float q = 0.f;
#pragma unroll
    for (int i = 0; i < 20; i++) { const float d = v[i] - mean; q += d * d; }
    const float var = bf16r(warp_sum(q) * (1.0f / DM));
    const float m = bf16r(mean);
    const float rden = 1.0f / bf16r(sqrtf(bf16r(var + 1e-5f)));
#pragma unroll
    for (int i = 0; i < 20; i++) v[i] = bf16r(bf16r(v[i] - m) * rden);
}

__device__ __forceinline__ void moments(float m1, float m2, float& nmean, float& rden) {
    m1 *= 1.0f / DM;
    const float var = bf16r(fmaxf(fmaf(-m1, m1, m2 * (1.0f / DM)), 0.f));
    nmean = bf16r(m1);
    rden = rcp_approx(bf16r(sqrt_approx(bf16r(var + 1e-5f))));
}
__device__ __forceinline__ float sel4(int j, float a, float b, float c, float d) {
    float lo, hi, r;
    asm("{\n.reg .pred p;\nsetp.ne.s32 p, %3, 0;\nselp.f32 %0, %2, %1, p;\n}" : "=f"(lo) : "f"(a), "f"(b), "r"(j & 1));
    asm("{\n.reg .pred p;\nsetp.ne.s32 p, %3, 0;\nselp.f32 %0, %2, %1, p;\n}" : "=f"(hi) : "f"(c), "f"(d), "r"(j & 1));
    asm("{\n.reg .pred p;\nsetp.ne.s32 p, %3, 0;\nselp.f32 %0, %2, %1, p;\n}" : "=f"(r) : "f"(lo), "f"(hi), "r"(j & 2));
    return r;
}
template <typename T> __device__ __forceinline__ void pin(T*& p) { asm volatile("" : "+l"(p)); }
__device__ __forceinline__ void pin(uint32_t& v) { asm volatile("" : "+r"(v)); }
__device__ __forceinline__ void pin(float& v) { asm volatile("" : "+f"(v)); }
__device__ __forceinline__ uint32_t after(uint32_t n, float v) {
    asm volatile("{\n.reg .pred p;\nsetp.eq.u32 p, %1, 0x7fc1a5a5;\n@p add.u32 %0, %0, 32;\n}" : "+r"(n) : "r"(__float_as_uint(v)));
    return n;
}
__device__ __forceinline__ float2 lds64f(uint32_t addr) {
    float2 v;
    asm volatile("ld.shared.v2.f32 {%0,%1}, [%2];" : "=f"(v.x), "=f"(v.y) : "r"(addr) : "memory");
    return v;
}
__device__ __forceinline__ void sts32f(uint32_t addr, float v) { asm volatile("st.shared.f32 [%0], %1;" :: "r"(addr), "f"(v) : "memory"); }
template <int ID> __device__ __forceinline__ void fin_arrive() { asm volatile("bar.arrive %0, 288;" :: "n"(ID) : "memory"); }
template <int ID> __device__ __forceinline__ void fin_sync() { asm volatile("bar.sync %0, 288;" :: "n"(ID) : "memory"); }
template <int ID> __device__ __forceinline__ void fin_sync(uint32_t n) { asm volatile("bar.sync %0, %1;" :: "n"(ID), "r"(n) : "memory"); }
__device__ __forceinline__ float2 sum8(uint32_t addr, int pitch) {
    float2 t[8];
#pragma unroll
    for (int w = 0; w < 8; w++) t[w] = lds64f(addr + w * pitch);
    return make_float2(((t[0].x + t[1].x) + (t[2].x + t[3].x)) + ((t[4].x + t[5].x) + (t[6].x + t[7].x)),
                       ((t[0].y + t[1].y) + (t[2].y + t[3].y)) + ((t[4].y + t[5].y) + (t[6].y + t[7].y)));
}
__device__ __forceinline__ float4 sum4x4(uint32_t addr, int pitch) {
    float4 t[4];
#pragma unroll
    for (int w = 0; w < 4; w++)
        asm volatile("ld.shared.v4.f32 {%0,%1,%2,%3}, [%4];" : "=f"(t[w].x), "=f"(t[w].y), "=f"(t[w].z), "=f"(t[w].w) : "r"(addr + w * pitch) : "memory");
    return make_float4((t[0].x + t[1].x) + (t[2].x + t[3].x), (t[0].y + t[1].y) + (t[2].y + t[3].y),
                       (t[0].z + t[1].z) + (t[2].z + t[3].z), (t[0].w + t[1].w) + (t[2].w + t[3].w));
}
__device__ __forceinline__ void sts64f(uint32_t addr, float x, float y) {
    asm volatile("st.shared.v2.f32 [%0], {%1,%2};" :: "r"(addr), "f"(x), "f"(y) : "memory");
}
__device__ __forceinline__ uint4 lds128(uint32_t addr) {
    uint4 v;
    asm volatile("ld.shared.v4.u32 {%0,%1,%2,%3}, [%4];" : "=r"(v.x), "=r"(v.y), "=r"(v.z), "=r"(v.w) : "r"(addr) : "memory");
    return v;
}
__device__ __forceinline__ void ld_relaxed_v4_if(uint4& v, const void* p, bool pred) {
    asm volatile("{\n.reg .pred p;\nsetp.ne.u32 p, %5, 0;\n@p ld.relaxed.gpu.global.v4.u32 {%0,%1,%2,%3}, [%4];\n}"
                 : "+r"(v.x), "+r"(v.y), "+r"(v.z), "+r"(v.w) : "l"(p), "r"((uint32_t)pred) : "memory");
}
__device__ __forceinline__ void sts128f(uint32_t addr, float x, float y, float z, float w) {
    asm volatile("st.shared.v4.f32 [%0], {%1,%2,%3,%4};" :: "r"(addr), "f"(x), "f"(y), "f"(z), "f"(w) : "memory");
}
template <int NJ>
__device__ __forceinline__ void load_o(uint32_t (&ob)[3 * NJ][2], const Scratch* scr, int bh, int J0, int j) {
    float4 v[NJ][4];
    float2 l;
#pragma unroll 1
    for (int it = 0; it < SPIN_MAX; it++) {
#pragma unroll
        for (int J = 0; J < NJ; J++) {
#pragma unroll
            for (int e = 0; e < 4; e++) v[J][e] = ld_relaxed_f4(&g_st.oacc[oidx(bh, j)] + oidx(0, (J0 + J) * 16 + e * 4));
        }
        l = ld_relaxed_f2(g_st.lsum[bh]);
        bool ok = l.y == UPB;
#pragma unroll
        for (int J = 0; J < NJ; J++) {
#pragma unroll
            for (int e = 0; e < 4; e++) ok &= v[J][e].w == UPB;
        }
        if (all(ok)) break;
    }
    const float rl = __fdividef(1.0f, l.x);
#pragma unroll
    for (int J = 0; J < NJ; J++) {
        ob[3 * J][0] = pack_bf16(v[J][0].x * rl, v[J][1].x * rl);     ob[3 * J][1] = pack_bf16(v[J][2].x * rl, v[J][3].x * rl);
        ob[3 * J + 1][0] = pack_bf16(v[J][0].y * rl, v[J][1].y * rl); ob[3 * J + 1][1] = pack_bf16(v[J][2].y * rl, v[J][3].y * rl);
        ob[3 * J + 2][0] = pack_bf16(v[J][0].z * rl, v[J][1].z * rl); ob[3 * J + 2][1] = pack_bf16(v[J][2].z * rl, v[J][3].z * rl);
    }
}
__device__ __forceinline__ int near_side(uint32_t sb) {
    uint32_t v;
    asm volatile("ld.volatile.shared.u32 %0, [%1];" : "=r"(v) : "r"(sb + SM_SIDE) : "memory");
    return v;
}
__device__ __forceinline__ void poll_row(uint4& a, uint4& b, uint2& c, const void* pa, const void* pb, const void* pc, uint32_t sa, uint32_t sc,
                                         bool arrive, bool nap, uint32_t bar, Warm& warm) {
    asm volatile("{\n.reg .pred p, q, r, s;\n.reg .b32 m, n, it;\n"
                 "setp.ne.u32 r, %19, 0;\nsetp.ne.u32 s, %20, 0;\nmov.u32 it, 0;\n"
                 "POLL:\n"
                 SLOT_ASM("m", "n", "p", "%23", "%24", "%25")
                 "ld.relaxed.gpu.global.v4.u32 {%0,%1,%2,%3}, [%14];\n"
                 "ld.relaxed.gpu.global.v4.u32 {%4,%5,%6,%7}, [%15];\n"
                 "ld.relaxed.gpu.global.v2.u32 {%8,%9}, [%16];\n"
                 "add.u32 it, it, 1;\nsetp.ge.u32 q, it, %21;\n"
                 "mov.u32 m, 0;\nmma.sync.aligned.m16n8k8.row.col.f32.bf16.bf16.f32 {%10,%11,%12,%13}, {m,m}, {m}, {%10,%11,%12,%13};\n"
                 "st.shared.v4.u32 [%17], {%0,%1,%2,%3};\n"
                 "st.shared.v4.u32 [%17+512], {%4,%5,%6,%7};\n"
                 "st.shared.v2.u32 [%18], {%8,%9};\n"
                 "min.u32 m, %0, %1;\nmin.u32 m, m, %2;\nmin.u32 n, %3, %4;\nmin.u32 n, n, %5;\nmin.u32 m, m, %6;\nmin.u32 m, m, %7;\n"
                 "min.u32 n, n, m;\nmin.u32 m, %8, %9;\nmin.u32 m, m, n;\n"
                 "setp.ne.or.u32 p, m, 0, q;\n"
                 "vote.sync.all.pred p, p, 0xffffffff;\n"
                 "and.pred q, p, r;\n"
                 "bar.warp.sync 0xffffffff;\n"
                 "@q mbarrier.arrive.shared::cta.b64 _, [%22];\n"
                 "@p bra.uni DONE;\n"
                 "@s nanosleep.u32 500;\n"
                 "bra.uni POLL;\n"
                 "DONE:\n}"
                 : "=&r"(a.x), "=&r"(a.y), "=&r"(a.z), "=&r"(a.w), "=&r"(b.x), "=&r"(b.y), "=&r"(b.z), "=&r"(b.w), "=&r"(c.x), "=&r"(c.y),
                   "+f"(warm.c[0]), "+f"(warm.c[1]), "+f"(warm.c[2]), "+f"(warm.c[3])
                 : "l"(pa), "l"(pb), "l"(pc), "r"(sa), "r"(sc), "r"((uint32_t)arrive), "r"((uint32_t)nap), "n"(SPIN_MAX), "r"(bar),
                   "n"(slot_phase<PH_H>()), "n"(SLOT_K), "n"(SLOT_OPEN * SLOT_K) : "memory");
}
__device__ __forceinline__ void aux_sync() { asm volatile("bar.sync 1, 256;" ::: "memory"); }

__global__ void __launch_bounds__(NTHREADS, 1)
fused_decode_kernel(Scratch* const scr, const __nv_bfloat16* const x, const __nv_bfloat16* const w_r, __nv_bfloat16* const out_all,
                    const __grid_constant__ Params p) {
    extern __shared__ __align__(1024) unsigned char smem[];
    const uint32_t sb = s2u(smem);
    const int tid = threadIdx.x, cta = blockIdx.x;
    asm volatile("{\n.reg .pred p;\nelect.sync _|p, 0xffffffff;\nsetp.ne.and.u32 p, %5, 0, p;\n"
                 "@p mbarrier.init.shared::cta.b64 [%2], 1;\n"
                 "@p fence.mbarrier_init.release.cluster;\n"
                 "@p mbarrier.arrive.expect_tx.shared::cta.b64 _, [%2], 15360;\n"
                 "@p cp.async.bulk.tensor.2d.shared::cluster.global.mbarrier::complete_tx::bytes [%0], [%1, {%3, %4}], [%2];\n}"
                 :: "r"(sb + SM_W), "l"(&p.wq), "r"(sb + BAR_WQ), "r"(cta * 48), "r"(0), "r"((uint32_t)(tid < 32 && cta < NQ_CTAS)) : "memory");
    if (tid < 32 && cta < NQ_CTAS) {
        asm volatile("{\n.reg .pred p;\nelect.sync _|p, 0xffffffff;\n"
                     "@p mbarrier.init.shared::cta.b64 [%2+8], 1;\n@p mbarrier.init.shared::cta.b64 [%2+16], 1;\n"
                     "@p mbarrier.init.shared::cta.b64 [%2+24], 1;\n"
                     "@p fence.mbarrier_init.release.cluster;\n"
                     "@p mbarrier.arrive.expect_tx.shared::cta.b64 _, [%2+8], 15360;\n"
                     "@p cp.async.bulk.tensor.2d.shared::cluster.global.mbarrier::complete_tx::bytes [%0+15360], [%1, {%3, %5}], [%2+8];\n"
                     "@p mbarrier.arrive.expect_tx.shared::cta.b64 _, [%2+16], 15360;\n"
                     "@p cp.async.bulk.tensor.2d.shared::cluster.global.mbarrier::complete_tx::bytes [%0+30720], [%1, {%3, %6}], [%2+16];\n"
                     "@p mbarrier.arrive.expect_tx.shared::cta.b64 _, [%2+24], 15360;\n"
                     "@p cp.async.bulk.tensor.2d.shared::cluster.global.mbarrier::complete_tx::bytes [%0+46080], [%1, {%3, %7}], [%2+24];\n}"
                     :: "r"(sb + SM_W), "l"(&p.wq), "r"(sb + BAR_WQ), "r"(cta * 48), "r"(0), "r"(160), "r"(320), "r"(480) : "memory");
    }
    const int warp = __shfl_sync(0xffffffffu, tid >> 5, 0), lane = tid & 31;
    constexpr int grid = NCTAS;
    const int g = lane >> 2, j = lane & 3;
    uint32_t t_start;
    asm volatile("mov.u32 %0, %%globaltimer_lo;" : "=r"(t_start));
    TS(0);
    if (tid == 32) {
        mbar_init(sb + BAR_WO, 1);
        mbar_init(sb + BAR_H, 1);
#pragma unroll
        for (int i = 0; i < 8 + NWORK; i++) mbar_init(sb + BAR_FW + i * 8, 1);
        sts32f(sb + SM_SIDE, 0.f);
        asm volatile("fence.mbarrier_init.release.cluster;" ::: "memory");
        asm volatile("fence.proxy.async.shared::cta;" ::: "memory");
    }
    __syncthreads();
    if (warp >= NAUX + NWORK) {
        const int fw = warp - (NAUX + NWORK), fi = ffn_slice(cta);
        if (fw == 0) {
            wait_time(t_start + CLEAR_AT_NS);
            if (cta < NQ_CTAS) {
#pragma unroll
                for (int i = lane; i < STATE_V4; i += 32)
                    if (cta * STATE_V4 + i < (int)(sizeof(State) / 16)) reinterpret_cast<uint4*>(&g_st)[cta * STATE_V4 + i] = make_uint4(0u, 0u, 0u, 0u);
                __syncwarp();
                if (lane == 0) red_release(g_cnt_z);
            }
            TSW(2); wait_count(g_cnt_z, NQ_CTAS); TSW(29);
            asm volatile("bar.arrive 2, %0;" :: "n"((NWORK + 2) * 32) : "memory");
            fin_arrive<3>();
        } else {
#pragma unroll 1
            for (int n = cta < NE_CTAS ? 5 : 4, i = n - 1; i >= 0; i--) {
                const int head = cta < NE_CTAS ? cta >> 2 : 28 + i;
                wait_time(t_start + WO_AT_NS + (NH - 1 - head) * WO_STEP_NS);
                request_box(sb + SM_A + i * 12288, &p.wo, cta < NE_CTAS ? (cta & 3) * 160 + i * 32 : (cta - NE_CTAS) * 32,
                            head * DH, sb + BAR_WO, i == n - 1 ? n * 12288 : 0);
            }
            asm volatile("bar.sync 2, %0;" :: "n"((NWORK + 2) * 32) : "memory");
            uint32_t best[2] = {~0u, ~0u};
#pragma unroll 1
            for (int i = 0; i < NPROBE; i++) {
#pragma unroll
                for (int c = 0; c < 2; c++) {
                    uint32_t t0 = clock(), t1 = t0;
                    int v = 0;
                    draw(v, &g_st.hx.w[c][PROBE], lane == 0);
                    asm volatile("{\n.reg .pred p;\nsetp.ne.u32 p, %1, 0xffffffff;\n@p mov.u32 %0, %%clock;\n}" : "+r"(t1) : "r"(v) : "memory");
                    best[c] = min(best[c], t1 - t0);
                }
                __nanosleep(1000);
            }
            if (lane == 0) sts32f(sb + SM_SIDE, __uint_as_float(best[1] < best[0]));
        }
        int job = cta;
        auto sum_rows = [&](int row_end) {
#pragma unroll 1
            for (; job < 8 * min(row_end, RED0); job += NCTAS) {
                const int row = job >> 3, grp = (job & 7) * 8 + (lane & 7);
                wait_row(scr, row, UPB);
                const float4* src = &g_ring[row % RING][lane >> 3][grp];
                float sx = 0.f, sy = 0.f, sz = 0.f;
#pragma unroll 1
                for (int i = 0; i < 2; i++, src += 64 * 64) {
                    float4 v[16];
#pragma unroll 1
                    for (int it = 0; it < SPIN_MAX; it++) {
                        bool ok = true;
#pragma unroll
                        for (int k = 0; k < 16; k++) v[k] = ld_relaxed_b128(src + k * 4 * 64);
#pragma unroll
                        for (int k = 0; k < 16; k++) ok &= v[k].w == (float)(row + 1);
                        if (all(ok)) break;
                    }
#pragma unroll
                    for (int k = 0; k < 16; k++) { sx += v[k].x; sy += v[k].y; sz += v[k].z; }
                }
#pragma unroll
                for (int o = 8; o < 32; o <<= 1) {
                    sx += __shfl_xor_sync(0xffffffffu, sx, o); sy += __shfl_xor_sync(0xffffffffu, sy, o); sz += __shfl_xor_sync(0xffffffffu, sz, o);
                }
                if (lane < 8) st_relaxed_b128(&g_st.oacc[oidx(row, grp)], sx, sy, sz, UPB);
            }
        };
        const int ho0 = lane / 20 * 256 + lane % 20 * 4, ho1 = (lane + 32) / 20 * 256 + (lane + 32) % 20 * 4, ho2 = 3 * 256 + 16 + 2 * lane;
        uint32_t wr[10] = {};
        float wsum = 0.f;
        if (is_g(cta) && fw == 0) {
#pragma unroll
            for (int i = 0; i < 10; i++) {
                const int w = 4 * lane + 128 * (i >> 2) + (i & 3) - (i >= 8 ? 2 * lane : 0);
                wr[i] = *reinterpret_cast<const uint32_t*>(w_r + (w >> 4) * 32 + (w & 3) * 8 + ((w >> 1) & 6));
                wsum += lo_f(wr[i]) + hi_f(wr[i]);
            }
            wsum = warp_sum(wsum);
        }
        const int fb = lane >> 3, fg = lane & 7;
        if (fw == 0) {
#pragma unroll
            for (int i = lane; i < DM / 2; i += 32) sts32f(sb + SM_X + 4 * HPITCH + i * 4, __uint_as_float(0x3f803f80u));
        }
        Warm warm;
        float nmean = 0.f, rden = 0.f, sig = 0.f;
#pragma unroll 1
        for (int b = 0; b < NB; b++) {
            const bool ffn = b >= NB - 2;
            if (fw == 0) {
                sum_rows((b + 1) * NH);
                if (ffn) asm volatile("bar.arrive 8, 64;" ::: "memory");
            } else if (ffn) {
                asm volatile("bar.sync 8, 64;" ::: "memory");
                if (b == NB - 1 && (is_f(cta) || is_g(cta) || ALL_LOADERS)) {
                    uint32_t t0 = 0;
#pragma unroll 1
                    for (int it = 0; it < SPIN_MAX; it++) {
                        t0 = ld_relaxed_u32(g_st.fw_time);
                        if (all(t0 != 0)) break;
                        __nanosleep(150);
                    }
                    asm volatile("fence.proxy.async.shared::cta;" ::: "memory");
                    wait_time(t0 + FW_AT_NS);
                    TSW(9);
                    uint32_t t = clock() + (is_f(cta) ? ((fi & 1) * 24 + (fi >> 1)) * FW_GAP / 48 : FW_MID + ((fi & 3) * 10 + (fi >> 2)) * FW_GAP2 / 40);
#pragma unroll 1
                    for (int i = 0; i < 8; i++) {
                        const uint32_t bar = sb + BAR_FW + i * 8;
                        if (is_f(cta)) {
                            wait_clock(t, warm);
                            request_box(sb + SM_W + i * 10240, (i & 1) ? &p.wu : &p.wg, fi * 32, (i >> 1) * 160, bar, 10240);
                            t += FW_GAP;
                        } else if (is_g(cta)) {
                            wait_clock(t, warm);
                            asm volatile("{\n.reg .pred p;\nelect.sync _|p, 0xffffffff;\n"
                                         "@p mbarrier.arrive.expect_tx.shared::cta.b64 _, [%2], 6144;\n"
                                         "@p cp.async.bulk.tensor.4d.shared::cluster.global.mbarrier::complete_tx::bytes [%0], [%1, {%3, %4, %4, %5}], [%2];\n}"
                                         :: "r"(sb + SM_W + i * 6144), "l"(&p.wd), "r"(bar), "r"(fi * 16), "r"(0), "r"(i * 12) : "memory");
                            t += FW_GAP2;
                        }
                    }
                }
                if (is_f(cta)) {
                    const uint32_t* src = &g_st.hx.w[near_side(sb)][min(fb, b) * 256 + 96];
                    float4 m;
#pragma unroll 1
                    for (int it = 0; it < SPIN_MAX; it++) {
                        wait_slot<PH_M>();
                        m = ld_relaxed_f4(src);
                        warm();
                        if (all(m.y + m.w == 2 * (NCTAS - NE_CTAS))) break;
                        if (b < NB - 1) __nanosleep(500);
                    }
                    moments(m.x, m.z, m.x, m.z);
                    sts64f(sb + SM_RED + 5120 + fb * 8, m.x, m.z);
                }
            }
            if (fw == 0 && cta >= NE_CTAS) {
                const int lc = cta - NE_CTAS, col = lc * 32 + 2 * (lane & 15);
                const uint32_t xv = *reinterpret_cast<const uint32_t*>(x + b * DM + col);
                uint32_t* dst = &(ffn ? g_st.hx.w : g_st.lx.w + 2)[lane >> 4][(b & 1) * 128 + lc / 5 * 256 + lc % 5 * 16 + (col & 6) * 2 + ((col >> 3) & 3)];
                uint32_t part = sb + SM_RED + (lane & 15) * 8;
                wait_row(scr, b * NH + 28, 1);
                float4 early;
#pragma unroll 1
                for (int it = 0; it < SPIN_MAX; it++) {
                    early = ld_relaxed_f4(&g_st.attn[b][col]);
                    if (all(early.y == NE_CTAS / 4 && early.w == NE_CTAS / 4)) break;
                }
                if (early.x != 1.2345f && lane == 0) TS2(6);
                CK(1, __float_as_uint(early.x));
                const float x0 = -(lo_f(xv) + early.x), x1 = -(hi_f(xv) + early.z);
                fin_sync<4>(after(after(288, x0), x1));
                CK(2, lds32(sb + SM_RED));
                const float2 late = sum8(part, 128);
                const uint32_t hv = nonzero(pack_bf16(x0 - late.x, x1 - late.y));
                st_relaxed(dst, hv);
                if (ffn) st_relaxed(dst + 2048, hv);
                CK(3, 0);
                float m = lane < 16 ? lo_f(hv) + hi_f(hv) : fmaf(lo_f(hv), lo_f(hv), hi_f(hv) * hi_f(hv));
#pragma unroll
                for (int o = 1; o < 16; o <<= 1) m += __shfl_xor_sync(0xffffffffu, m, o);
                if ((lane & 14) == 0) red_f2(reinterpret_cast<float*>(&g_st.hx.w[lane & 1][b * 256 + 96 + (lane >> 4) * 2]), m, 1.f);
                fin_arrive<5>();
            }
            if (fw == 0 && (is_g(cta) || is_f(cta))) {
                const uint32_t* src = &(ffn ? g_st.hx.w : g_st.lx.w + 2)[near_side(sb) ^ (ffn && is_g(cta) ? 3 : 0)][(b & 1) * 128];
                const uint32_t hrow = sb + SM_X + b * HPITCH;
                wait_sum(b == NB - 1 ? (const void*)&g_st.lx.w[near_side(sb) ^ 1][3 * 256] : g_st.lsum[b * NH + NH - 1], UPB, 100);
                wait_clock(clock() + HGATE_NS * 2, warm);
                uint4 h0, h1;
                uint2 h2;
                poll_row(h0, h1, h2, src + ho0, src + ho1, src + ho2, hrow + lane * 16, hrow + 1024 + lane * 8, ffn && lane == 0, b < NB - 1, sb + BAR_H, warm);
                CK(4, h0.x);
                if (is_g(cta)) {
                    const uint32_t hw[10] = {h0.x, h0.y, h0.z, h0.w, h1.x, h1.y, h1.z, h1.w, h2.x, h2.y};
                    float m1 = 0.f, m2 = 0.f, rr = 0.f;
#pragma unroll
                    for (int i = 0; i < 10; i++) {
                        const float v0 = lo_f(hw[i]), v1 = hi_f(hw[i]);
                        m1 += v0 + v1;
                        m2 = fmaf(v0, v0, fmaf(v1, v1, m2));
                        rr = fmaf(v0, lo_f(wr[i]), fmaf(v1, hi_f(wr[i]), rr));
                    }
                    moments(warp_sum(m1), warp_sum(m2), m1, m2);
                    const float sg = bf16r(sigmoid_approx(bf16r((m1 * wsum - warp_sum(rr)) * m2)));
                    if (fb == b) { nmean = m1; rden = m2; sig = sg; }
                    __syncwarp();
                    if (ffn) {
                        const int yj = 2 * (fb & 1) + (fb >> 1);
                        uint32_t ypart = sb + SM_RED2 + yj * 128 + ((fg + 2 * yj) & 7) * 16;
                        __nv_bfloat16* out = out_all + fb * DM + fi * 16 + fg;
                        const float2 hw2 = lds64f(sb + SM_X + fb * HPITCH + ((fi >> 1) * 16 + (fg & 6) * 2 + (fi & 1) * 2) * 4);
                        const uint32_t w0 = __float_as_uint(hw2.x), w1 = __float_as_uint(hw2.y);
                        const float nh0 = (fg & 1) ? hi_f(w0) : lo_f(w0), nh1 = (fg & 1) ? hi_f(w1) : lo_f(w1);
                        const float ln0 = bf16r(bf16r(nmean - nh0) * rden) - nh0, ln1 = bf16r(bf16r(nmean - nh1) * rden) - nh1;
                        pin(ypart); pin(out);
                        fin_sync<6>(after(after(after(288, sig), ln0), ln1));
                        CK(10, lds32(ypart));
                        const float4 ya = sum4x4(ypart, 512), yb = sum4x4(ypart + 2048, 512);
                        const float4 y = make_float4(ya.x + yb.x, ya.y + yb.y, ya.z + yb.z, ya.w + yb.w);
                        const float y0 = -(((fb & 1) ? y.y : y.x) + __shfl_xor_sync(0xffffffffu, (fb & 1) ? y.x : y.y, 8));
                        const float y1 = -(((fb & 1) ? y.w : y.z) + __shfl_xor_sync(0xffffffffu, (fb & 1) ? y.z : y.w, 8));
                        const uint32_t ov = pack_bf16(fmaf(y0, sig, ln0), fmaf(y1, sig, ln1));
                        asm volatile("{\n.reg .pred p;\n.reg .b16 lo, hi;\nsetp.ne.u32 p, %2, 0;\nmov.b32 {lo, hi}, %1;\n"
                                     "@p st.global.u16 [%0], lo;\n@p st.global.u16 [%0+16], hi;\n"
                                     "@p exit;\n"
                                     "}" :: "l"(out), "r"(ov), "r"((uint32_t)(b == NB - 1)) : "memory");
                        CK(11, 0);
                        if (lane == 0) TS2(13);
                    }
                }
            }
            if (is_f(cta) && ffn) {
                const int ks = (2 * fi + fw) % 12;
                const int far = near_side(sb) ^ 1;
                uint32_t* dst = &g_st.ax[ks >> 2].w[(~b & 1) * 2 + far][(fi / 6) * 128 + (ks & 3) * 32 + fb * 8 + (fg & 1) * 4 + ((fg >> 1) ^ (ks & 1))];
                uint32_t* dst2 = dst + (far ? -1024 : 1024);
                uint32_t part = sb + SM_RED + fw * 2560 + fb * 128 + ((fg + (fb & 2)) & 7) * 16;
                uint32_t psum = sb + SM_RED + fw * 2560 + 4 * 128 + ((fg + 4) & 7) * 16;
                pin(dst); pin(part); pin(psum);
                asm volatile("bar.sync 4, 320;" ::: "memory");
                CK(6, lds32(part));
                const float4 d = sum4x4(part, 640), cs = sum4x4(psum, 640);
                const float2 mo = lds64f(sb + SM_RED + 5120 + fb * 8);
                nmean = mo.x; rden = mo.y;
                const float g0 = fmaf(nmean, cs.x, -d.x), g1 = fmaf(nmean, cs.y, -d.y), ke = rden * -1.4426950408889634f, r2 = rden * rden;
                const float p0 = g0 * fmaf(-nmean, cs.z, d.z) * r2, p1 = g1 * fmaf(-nmean, cs.w, d.w) * r2;
                const uint32_t av = nonzero(pack_bf16(p0 * rcp_approx(1.0f + ex2_approx(g0 * ke)), p1 * rcp_approx(1.0f + ex2_approx(g1 * ke))));
                st_relaxed(dst, av);
                st_relaxed(dst2, av);
                CK(7, 0);
            }
        }
        warm.done(sb + SM_SCRAP);
        if (cta == 0 && tid == (NAUX + NWORK) * 32) { g_work[0] = 0; g_work[32] = 0; g_cnt_z[0] = 0; }
        return;
    }
    if (warp >= NAUX) {
        const int wk = warp - NAUX;
        const uint32_t bar = sb + BAR_KV + wk * 8;
        const uint32_t buf = sb + SM_KV + wk * TILE_BYTES;
        uint64_t pol;
        asm volatile("createpolicy.fractional.L2::evict_first.b64 %0, 1.0;" : "=l"(pol));
        const int nstatic = NWORK * grid;
        constexpr int POOL0 = NUNITS - NPOOL;
        int uk = wk * grid + cta;
        wait_time(t_start + K0_AT_NS + uk * KSWEEP_NS / nstatic);
        request_tile(buf, &p.k, uk, bar, pol);
        uint32_t koff[3], voff[3];
        {
            const int r = lane & 7, hf = (lane >> 3) & 1;
            const int kkey = hf ? 8 + (r ^ 1) : r;
            const int vh = lane >> 4;
            const int vkey = ((r & 1) ? 8 : 0) + (vh ? (r ^ 1) : r);
#pragma unroll
            for (int b = 0; b < 3; b++) {
                const int rk = 3 * kkey + b, rv = 3 * vkey + b;
                koff[b] = buf + rk * 128 + (((lane >> 4) ^ (rk & 7)) << 4);
                voff[b] = buf + rv * 128 + ((hf ^ (rv & 7)) << 4);
            }
        }
        uint32_t phase = 0;
        uint32_t qf[12][2];
        auto load_q = [&](int u) {
            const uint32_t* q = g_early[u / UPB].q[0][j];
#pragma unroll
            for (int i = 0; i < 4; i++) {
                const uint4 a = ld_relaxed_v4(q + i * 32);
                const float2 c = ld_relaxed_f2(q + i * 32 + 4);
                qf[3 * i][0] = a.x; qf[3 * i][1] = a.y; qf[3 * i + 1][0] = a.z; qf[3 * i + 1][1] = a.w;
                qf[3 * i + 2][0] = __float_as_uint(c.x); qf[3 * i + 2][1] = __float_as_uint(c.y);
            }
        };
        load_q(uk);
        int uq[LAG];
        uint32_t sq[LAG];
#pragma unroll
        for (int i = 0; i < LAG; i++) { uq[i] = ~unit_of(uk + (i + 1) * nstatic); sq[i] = 0; }
        uint4 mv = make_uint4(0u, 0u, 0u, 0u);
        float freed = UPB;
        while (true) {
            const int uv = uq[0];
            uint32_t sv = sq[0];
#pragma unroll
            for (int i = 0; i + 1 < LAG; i++) { uq[i] = uq[i + 1]; sq[i] = sq[i + 1]; }
            uq[LAG - 1] = uk;
            if (uk < NUNITS) {
                PH(7);
#pragma unroll 1
                for (int it = 0; it < SPIN_MAX; it++) {
                    uint32_t lo = 0xffffffffu;
#pragma unroll
                    for (int i = 0; i < 12; i++) lo = min(lo, min(qf[i][0], qf[i][1]));
                    if (all(lo != 0)) break;
                    __nanosleep(250);
                    load_q(uk);
                }
                mbar_wait(bar, phase); phase ^= 1;
                PH(0); ARR();
                TSI(0, 16); TSI(1, 18);
                float acc[2][4][4] = {};
#pragma unroll
                for (int ks = 0; ks < 12; ks++) {
#pragma unroll
                    for (int mt = 0; mt < 4; mt++) {
                        uint32_t a[4];
                        ldsm4(a, (koff[ks >> 2] ^ ((ks & 3) << 5)) + mt * 6144);
                        mma16816(acc[ks & 1][mt], a, qf[ks][0], qf[ks][1]);
                    }
                }
                PH(1);
                TSI(0, 17); TSI(1, 19);
                if (uk < nstatic) wait_time(t_start + K1_AT_NS + uk * KSWEEP_NS / nstatic);
                if (uv < NUNITS) request_tile(buf, uv >= 0 ? &p.v : &p.k, uv >= 0 ? uv : ~uv, bar, pol);
                const float sa = sel4(j, acc[0][0][0], acc[0][1][0], acc[0][2][0], acc[0][3][0]) + sel4(j, acc[1][0][0], acc[1][1][0], acc[1][2][0], acc[1][3][0]);
                const float sc = sel4(j, acc[0][0][2], acc[0][1][2], acc[0][2][2], acc[0][3][2]) + sel4(j, acc[1][0][2], acc[1][1][2], acc[1][2][2], acc[1][3][2]);
                const uint32_t raw = pack_bf16(sa, sc);
                const float scale = -0.07216878364870322f;
                const uint32_t sk = pack_bf16(lo_f(raw) * scale, hi_f(raw) * scale);
                sq[LAG - 1] = sk;
                if (uk >= POOL0) st_relaxed(&g_st.score[uk - POOL0][lane], sk ? sk : 0x80008000u);
                int a = (int)(sk << 16), b = (int)(sk & 0xffff0000u);
                a ^= (a >> 31) & 0x7fff0000; b ^= (b >> 31) & 0x7fff0000;
                const int mx = __reduce_max_sync(0xffffffffu, max(a, b));
                if (lane == 0) st_relaxed(&g_early[uk / UPB].umax[uk % UPB], (uint32_t)mx | 1u);
            }
            if (uv < 0) {
                uk = ~uv;
                load_q(uk);
                continue;
            }
            if (uv >= NUNITS) break;
            const int bh = uv / UPB;
#pragma unroll 1
            for (int it = 0; it < SPIN_MAX; it++) {
                if (all((mv.x & mv.y & mv.z & mv.w & 1u) && (uv < POOL0 || sv != 0) && freed == UPB)) break;
                mv = ld_relaxed_v4(&g_early[bh].umax[lane * 4]);
                if (bh >= RING && bh < RED0) freed = __uint_as_float(ld_relaxed_u32(&g_st.oacc[oidx(bh - RING, (lane & 7) * 8)].w));
                if (uv >= POOL0) sv = ld_relaxed_u32(&g_st.score[uv - POOL0][lane]);
            }
            PH(2); CK(8, sv);
            int un = NUNITS, vn = 0;
            draw(un, g_work, uk < NUNITS && lane == 0);
            uint32_t tdraw;
            asm volatile("mov.u32 %0, %%globaltimer_lo;" : "=r"(tdraw));
            draw(vn, g_work + 32, uq[0] >= POOL0 && lane == 0);
            int mx = __reduce_max_sync(0xffffffffu, max(max((int)mv.x, (int)mv.y), max((int)mv.z, (int)mv.w))) & 0xffff0000;
            mx ^= (mx >> 31) & 0x7fff0000;
            const float m = __int_as_float(mx);
            const float l2e = 1.4426950408889634f;
            const uint32_t pp = pack_bf16(exp2f((lo_f(sv) - m) * l2e), exp2f((hi_f(sv) - m) * l2e));
            uint32_t pb[8];
#pragma unroll
            for (int t = 0; t < 4; t++) {
                pb[2 * t] = __shfl_sync(0xffffffffu, pp, 8 * j + t);
                pb[2 * t + 1] = __shfl_sync(0xffffffffu, pp, 8 * j + 4 + t);
            }
            float lacc[4] = {};
            const uint32_t ones[4] = {0x3f803f80u, 0x3f803f80u, 0x3f803f80u, 0x3f803f80u};
#pragma unroll
            for (int t = 0; t < 4; t++) mma16816(lacc, ones, pb[2 * t], pb[2 * t + 1]);
            if (uv < nstatic) {
                asm volatile("bar.sync 2, %0;" :: "n"((NWORK + 2) * 32) : "memory");
                TSW(3);
            }
            const int grp = 16 * j + 4 * (g & 1) + (g >> 1);
            uint32_t mode = (bh >= RED0) + (bh >= NBH - 4);
            float tag = mode ? 1.f : (float)(bh + 1), tag2 = fmaf(__uint_as_float(voff[0]), 0.f, tag);
            void* dst = mode == 0 ? (void*)&g_ring[bh % RING][uv % UPB][grp] :
                        mode == 1 ? (void*)&g_st.oacc[oidx(bh, grp)] : (void*)&g_st.ox[0].w[uv % OREP * 2 + (~(near_side(sb) ^ uv % OREP) & 1)][oidx(bh & 3, grp) * 4];
            if (mode == 2 && lane < 2) red_f2(reinterpret_cast<float*>(&g_st.lx.w[lane][(bh & 3) * 256]), lacc[0], 1.f);
            CK(10, __float_as_uint(lacc[0]));
            un = __shfl_sync(0xffffffffu, un, 0) + (LAG + 1) * nstatic;
            un = unit_of(un);
            vn = __shfl_sync(0xffffffffu, vn, 0);
            if (uq[0] >= POOL0) uq[0] = unit_of(POOL0 + vn);
            if (vn == FW_TICKET && lane == 0) st_relaxed(g_st.fw_time, tdraw | 1u);
            if (uq[0] < NUNITS && un >= NUNITS) {
                mv = ld_relaxed_v4(&g_early[uq[0] / UPB].umax[lane * 4]);
                if (uq[0] < RED0 * UPB) freed = 0.f;
                if (uq[0] >= POOL0) sq[0] = ld_relaxed_u32(&g_st.score[uq[0] - POOL0][lane]);
            }
            pin(dst); pin(mode); pin(tag); pin(tag2); pin(voff[0]); pin(voff[1]); pin(voff[2]);
            PH(3); CK(9, vn);
            mbar_wait(bar, phase); phase ^= 1;
            PH(4); ARR(); CK(12, lds32(buf));
            float acc[12][4] = {};
#pragma unroll
            for (int t = 0; t < 4; t++) {
#pragma unroll
                for (int mt = 0; mt < 12; mt++) {
                    uint32_t a[4];
                    ldsm4t(a, (voff[mt >> 2] ^ ((mt & 3) << 5)) + t * 6144);
                    mma16816(acc[mt], a, pb[2 * t], pb[2 * t + 1]);
                }
            }
            PH(5);
            if (lane == 0) PROG(un);
            if (un < NUNITS || uq[0] < NUNITS) request_tile(buf, un < NUNITS ? &p.k : &p.v, un < NUNITS ? un : uq[0], bar, pol);
            if (un < NUNITS || uq[0] < NUNITS) CK(11, 0);
            float o[6];
#pragma unroll
            for (int e = 0; e < 6; e++) {
                const int q = e % 3, c = (e / 3) * 2;
                o[e] = sel4(j, acc[q][c], acc[3 + q][c], acc[6 + q][c], acc[9 + q][c]);
            }
            put_groups(dst, mode, o, tag, tag2);
            CK(13, 0);
            if (un < NUNITS) load_q(un);
            if (lane == 0) red_f2(&g_st.lsum[bh][0].x, lacc[0], 1.f);
            PH(6);
            if (uq[0] >= NUNITS && un >= NUNITS) break;
            uk = un;
            if (uq[0] < NUNITS && un < NUNITS) {
                const int nb = uq[0] / UPB;
                mv = ld_relaxed_v4(&g_early[nb].umax[lane * 4]);
                freed = nb >= RING && nb < RED0 ? __uint_as_float(ld_relaxed_u32(&g_st.oacc[oidx(nb - RING, (lane & 7) * 8)].w)) : UPB;
                if (uq[0] >= POOL0) sq[0] = ld_relaxed_u32(&g_st.score[uq[0] - POOL0][lane]);
            }
        }
        TSW(4 + wk);
        return;
    }

    __nv_bfloat16* xs = reinterpret_cast<__nv_bfloat16*>(smem + SM_X);
    float* red = reinterpret_cast<float*>(smem + SM_RED);
    const int frow = (lane & 7) + ((lane >> 4) << 3), fcol = (lane >> 3) & 1;
    const uint32_t f64b = sb + (frow * 4 + (fcol ^ ((frow >> 1) & 3))) * 16;
    if (cta < NQ_CTAS) {
        TS(26);
        if (warp >= 4) {
            uint2 xr[5];
#pragma unroll
            for (int i = 0; i < 5; i++) xr[i] = *reinterpret_cast<const uint2*>(x + (warp - 4) * DM + i * 128 + lane * 4);
            float v[20];
#pragma unroll
            for (int i = 0; i < 5; i++) {
                v[4 * i] = lo_f(xr[i].x); v[4 * i + 1] = hi_f(xr[i].x); v[4 * i + 2] = lo_f(xr[i].y); v[4 * i + 3] = hi_f(xr[i].y);
            }
            layernorm20(v);
#pragma unroll
            for (int i = 0; i < 5; i++)
                *reinterpret_cast<uint2*>(xs + (warp - 4) * XPITCH + i * 128 + lane * 4) =
                    make_uint2(pack_bf16(v[4 * i], v[4 * i + 1]), pack_bf16(v[4 * i + 2], v[4 * i + 3]));
        }
        aux_sync();
        TS(27);
        mbar_wait(sb + BAR_WQ + (warp >> 1) * 8, 0);
        TS(1);
        const uint32_t xfrag = sb + SM_X + ((g & 3) * XPITCH + 2 * j) * 2;
        float acc[3][4] = {};
#pragma unroll
        for (int s = 0; s < 5; s++) {
            const int ks = warp * 5 + s;
            const uint32_t b0 = lds32(xfrag + ks * 32), b1 = lds32(xfrag + ks * 32 + 16);
            const int row = ks * 16 + frow;
#pragma unroll
            for (int mt = 0; mt < 3; mt++) {
                uint32_t a[4];
                ldsm4t(a, sb + SM_W + (row * 6 + 2 * mt + fcol) * 16);
                mma16816(acc[mt], a, b0, b1);
            }
        }
        if (j < 2) {
#pragma unroll
            for (int mt = 0; mt < 3; mt++) {
                *reinterpret_cast<float2*>(red + warp * 216 + mt * 72 + g * 4 + 2 * j) = make_float2(acc[mt][0], acc[mt][1]);
                *reinterpret_cast<float2*>(red + warp * 216 + mt * 72 + 36 + g * 4 + 2 * j) = make_float2(acc[mt][2], acc[mt][3]);
            }
        }
        aux_sync();
        if (warp < 4) {
            const float* src = red + min(g, 5) * 36 + warp * 8 + j;
            float s0 = 0.f, s1 = 0.f;
#pragma unroll
            for (int w = 0; w < 8; w++) { s0 += src[w * 216]; s1 += src[w * 216 + 4]; }
            st_relaxed(&g_early[j * NH + (cta >> 2)].q[cta & 3][warp][g], pack_neg(s0, s1));
        }
        TS(28);
    }
    fin_sync<3>();
    mbar_wait(sb + BAR_WO, 0);
    TS(7);
    uint32_t part = sb + SM_RED + (warp * 32 + 8 * j + g) * 4;

#pragma unroll 1
    for (int b = 0; b < NB; b++) {
        if (cta >= NE_CTAS) {
            uint32_t a[6][2][4];
#pragma unroll
            for (int s = 0; s < 6; s++) {
#pragma unroll
                for (int mt = 0; mt < 2; mt++) ldsm4t(a[s][mt], (f64b ^ (mt * 32)) + SM_A + (warp * 6 + s) * 1024);
            }
            const int bh = b * NH + 28 + (warp >> 1);
            const int side = near_side(sb) ^ 1;
            const void* osrc[OREP];
#pragma unroll
            for (int c = 0; c < OREP; c++)
                osrc[c] = b == NB - 1 ? (const void*)&g_st.ox[c >> 1].w[side ^ (c & 1) * 3][oidx(bh & 3, (warp & 1) * 32 + lane) * 4] : &g_st.oacc[oidx(bh, (warp & 1) * 32 + lane)];
            const void* lsrc = b == NB - 1 ? (const void*)&g_st.lx.w[side][(bh & 3) * 256] : g_st.lsum[bh];
            wait_row_o(scr, bh, 1);
            const float rl = rcp_approx(wait_sum(lsrc, UPB)) * (b == NB - 1 ? 1.f : 1.f / OREP), full = b == NB - 1 ? UPB : UPB * OREP;
            float4 ov;
            float px, py, pz;
            Warm warm;
#pragma unroll 1
            for (int it = 0; it < SPIN_MAX; it++) {
                wait_slot<PH_O>();
                float4 oc[OREP];
#pragma unroll
                for (int c = 0; c < OREP; c++) oc[c] = ld_relaxed_f4(osrc[c]);
                warm();
                ov = oc[0];
#pragma unroll
                for (int c = 1; c < OREP; c++) { ov.x += oc[c].x; ov.y += oc[c].y; ov.z += oc[c].z; ov.w += oc[c].w; }
                ov.x *= rl; ov.y *= rl; ov.z *= rl;
                px = __shfl_xor_sync(0xffffffffu, ov.x, 4); py = __shfl_xor_sync(0xffffffffu, ov.y, 4); pz = __shfl_xor_sync(0xffffffffu, ov.z, 4);
                if (all(ov.w == full)) break;
            }
            CK(0, __float_as_uint(ov.x));
            if (ov.x != 1.2345f && warp == 7) TSW(14);
            const uint32_t w[3] = {pack_bf16(ov.x, px), pack_bf16(ov.y, py), pack_bf16(ov.z, pz)};
            float acc[2][2][4] = {};
#pragma unroll
            for (int s = 0; s < 6; s++) {
                const uint32_t b0 = __shfl_sync(0xffffffffu, w[s % 3], (s / 3) * 16 + j);
                const uint32_t b1 = __shfl_sync(0xffffffffu, w[s % 3], (s / 3) * 16 + 8 + j);
#pragma unroll
                for (int mt = 0; mt < 2; mt++) mma16816(acc[mt][s & 1], a[s][mt], b0, b1);
            }
            sts32f(part, sel4(j, acc[0][0][0] + acc[0][1][0], acc[0][0][2] + acc[0][1][2], acc[1][0][0] + acc[1][1][0], acc[1][0][2] + acc[1][1][2]));
            CK(1, 0);
            fin_arrive<4>();
            warm.done(sb + SM_SCRAP);
            fin_sync<5>();
            if (cta < NE_CTAS + 4 && tid < 64) reinterpret_cast<uint4*>(&g_early[b * NH + 28 + cta - NE_CTAS])[tid] = make_uint4(0u, 0u, 0u, 0u);
        } else {
            const int bh = b * NH + (cta >> 2);
            if (warp == 0) wait_row_o(scr, bh, UPB);
            aux_sync();
            if (warp < 5) {
                uint32_t ob[12][2];
                load_o<4>(ob, scr, bh, 0, j);
                float acc[2][2][4] = {};
#pragma unroll
                for (int ks = 0; ks < 12; ks++) {
#pragma unroll
                    for (int mt = 0; mt < 2; mt++) {
                        uint32_t a[4];
                        ldsm4t(a, (f64b ^ (mt * 32)) + SM_A + warp * 12288 + ks * 1024);
                        mma16816(acc[mt][ks & 1], a, ob[ks][0], ob[ks][1]);
                    }
                }
                red_f2(&g_st.attn[b][(cta & 3) * 160 + warp * 32 + 8 * j + g].x,
                       sel4(j, acc[0][0][0] + acc[0][1][0], acc[0][0][2] + acc[0][1][2], acc[1][0][0] + acc[1][1][0], acc[1][0][2] + acc[1][1][2]), 1.f);
                TS(8);
            } else if (warp > 5 && (cta & 3) == 0) {
                reinterpret_cast<uint4*>(&g_early[bh])[tid - 192] = make_uint4(0u, 0u, 0u, 0u);
            }
        }
        if (b < NB - 2) continue;

        if (is_f(cta)) {
            uint32_t ga[10][2][4];
            uint4 hv[5];
            const uint32_t hfrag = sb + SM_X + min(g, 4) * HPITCH + ((warp >> 1) * 80 + 4 * j) * 4;
            if (b == NB - 1) mbar_wait(sb + BAR_FW + warp * 8, 0);
            if (warp == 7) TSW(10);
            CK(12, lds32(sb + SM_W));
#pragma unroll
            for (int s = 0; s < 10; s++) {
#pragma unroll
                for (int mt = 0; mt < 2; mt++) ldsm4t(ga[s][mt], (f64b ^ (mt * 32)) + SM_W + (warp * 10 + s) * 1024);
            }
            const uint32_t gpart = sb + SM_RED + (warp >> 1) * 640 + j * 256 + ((g + 2 * j) & 7) * 16 + (warp & 1) * 8;
            mbar_wait(sb + BAR_H, b & 1);
#pragma unroll
            for (int s = 0; s < 5; s++) hv[s] = lds128(hfrag + s * 64);
            CK(4, hv[0].x);
            float acc[2][2][4] = {};
#pragma unroll
            for (int s = 0; s < 10; s++) {
#pragma unroll
                for (int mt = 0; mt < 2; mt++)
                    mma16816(acc[mt][s & 1], ga[s][mt], (s & 1) ? hv[s >> 1].z : hv[s >> 1].x, (s & 1) ? hv[s >> 1].w : hv[s >> 1].y);
            }
#pragma unroll
            for (int mt = 0; mt < 2; mt++) {
                if (j < 3) sts64f(gpart + mt * 2560, acc[mt][0][0] + acc[mt][1][0], acc[mt][0][2] + acc[mt][1][2]);
                if (j < 2) sts64f(gpart + mt * 2560 + 128, acc[mt][0][1] + acc[mt][1][1], acc[mt][0][3] + acc[mt][1][3]);
            }
            CK(5, 0);
            asm volatile("bar.arrive 4, 320;" ::: "memory");
        } else if (is_g(cta)) {
            const uint32_t* asrc = &g_st.ax[0].w[(~b & 1) * 2 + near_side(sb)][warp * 128 + ((g >> 2) * 2 + (j >> 1)) * 32 + (g & 3) * 8 + (j & 1) * 4];
            const uint32_t ypart = sb + SM_RED2 + warp * 512 + j * 128 + ((g + 2 * j) & 7) * 16;
            uint32_t wb[12][4];
            uint4 va[3] = {};
            uint32_t lo[3] = {};
            auto ask = [&]() {
#pragma unroll
                for (int i = 0; i < 3; i++) ld_relaxed_v4_if(va[i], asrc + i * 4096, lo[i] == 0);
            };
            auto complete = [&]() {
#pragma unroll
                for (int i = 0; i < 3; i++) lo[i] = min(min(va[i].x, va[i].y), min(va[i].z, va[i].w));
                return all(min(lo[0], min(lo[1], lo[2])) != 0);
            };
            const int jj = (lane & 7) >> 1, q = jj >> 1, hi = lane >> 4;
            const uint32_t wsrc = sb + SM_W + warp * 6144 + q * 512 + ((hi ^ q) * 4 + (jj & 1) * 2 + (lane & 1)) * 32 + ((fcol ^ hi ^ q) << 4);
            mbar_wait(sb + BAR_H, b & 1);
            if (b == NB - 1) mbar_wait(sb + BAR_FW + warp * 8, 0);
            if (warp == 7) TSW(11);
            CK(13, lds32(sb + SM_W));
            ask();
#pragma unroll
            for (int s = 0; s < 12; s++) ldsm4t(wb[s], wsrc + (s >> 2) * 2048 + (s & 1) * 1024 + (s & 2) * 128);
            Warm warm;
            if (!complete()) {
#pragma unroll 1
                for (int it = 0; it < SPIN_MAX; it++) {
                    ask();
                    warm();
                    if (complete()) break;
                }
            }
            CK(8, va[0].x);
            if (va[0].x != 0x12345 && warp == 7) TSW(15);
            float acc[6][4] = {};
#pragma unroll
            for (int s = 0; s < 12; s++) {
                const uint4 v = va[s >> 2];
                mma16816(acc[s % 6], wb[s], (s & 2) ? v.z : v.x, (s & 2) ? v.w : v.y);
            }
            float y[4];
#pragma unroll
            for (int e = 0; e < 4; e++) y[e] = j < 2 ? (acc[0][e] + acc[2][e]) + acc[4][e] : (acc[1][e] + acc[3][e]) + acc[5][e];
            sts128f(ypart, y[0], y[1], y[2], y[3]);
            CK(9, 0);
            fin_arrive<6>();
            warm.done(sb + SM_SCRAP);
        }
    }
}

typedef CUresult (*EncodeFn)(CUtensorMap*, CUtensorMapDataType, cuuint32_t, void*, const cuuint64_t*, const cuuint64_t*,
                             const cuuint32_t*, const cuuint32_t*, CUtensorMapInterleave, CUtensorMapSwizzle,
                             CUtensorMapL2promotion, CUtensorMapFloatOOBfill);

CUtensorMap make_map(EncodeFn enc, void* ptr, uint64_t cols, uint64_t rows, uint32_t bcols, uint32_t brows,
                     CUtensorMapSwizzle sw, CUtensorMapL2promotion promo) {
    CUtensorMap m;
    const cuuint64_t dims[2] = {cols, rows};
    const cuuint64_t strides[1] = {cols * 2};
    const cuuint32_t box[2] = {bcols, brows};
    const cuuint32_t es[2] = {1, 1};
    enc(&m, CU_TENSOR_MAP_DATA_TYPE_BFLOAT16, 2, ptr, dims, strides, box, es, CU_TENSOR_MAP_INTERLEAVE_NONE, sw, promo,
        CU_TENSOR_MAP_FLOAT_OOB_FILL_NONE);
    return m;
}

}

extern "C" void kernel_launch(void* const* d_in, const int* in_sizes, int n_in, void* d_out, int out_size) {
    (void)in_sizes; (void)n_in; (void)out_size;
    static EncodeFn enc = nullptr;
    static int sms = 0;
    static Scratch* scr = nullptr;
    if (!enc) {
        cudaDriverEntryPointQueryResult qr;
        cudaGetDriverEntryPoint("cuTensorMapEncodeTiled", (void**)&enc, cudaEnableDefault, &qr);
        void* raw = nullptr;
        cudaGetSymbolAddress(&raw, g_raw);
        scr = reinterpret_cast<Scratch*>((reinterpret_cast<uintptr_t>(raw) + PAGE - 1) & ~(uintptr_t)(PAGE - 1));
        int dev = 0;
        cudaGetDevice(&dev);
        cudaDeviceGetAttribute(&sms, cudaDevAttrMultiProcessorCount, dev);
        cudaFuncSetAttribute(fused_decode_kernel, cudaFuncAttributeMaxDynamicSharedMemorySize, SM_TOTAL);
    }
    if (sms < NCTAS) return;
    const CUtensorMapL2promotion WPROMO = CU_TENSOR_MAP_L2_PROMOTION_L2_128B;
    Params p;
    p.k = make_map(enc, d_in[1], 64, (uint64_t)NBH * SK * 3, 64, TILE_ROWS, CU_TENSOR_MAP_SWIZZLE_128B, CU_TENSOR_MAP_L2_PROMOTION_NONE);
    p.v = make_map(enc, d_in[2], 64, (uint64_t)NBH * SK * 3, 64, TILE_ROWS, CU_TENSOR_MAP_SWIZZLE_128B, CU_TENSOR_MAP_L2_PROMOTION_NONE);
    p.wq = make_map(enc, d_in[3], NH * DH, DM, 48, 160, CU_TENSOR_MAP_SWIZZLE_NONE, WPROMO);
    p.wo = make_map(enc, d_in[4], DM, NH * DH, 32, DH, CU_TENSOR_MAP_SWIZZLE_64B, WPROMO);
    p.wg = make_map(enc, d_in[7], FF, DM, 32, 160, CU_TENSOR_MAP_SWIZZLE_64B, WPROMO);
    p.wu = make_map(enc, d_in[8], FF, DM, 32, 160, CU_TENSOR_MAP_SWIZZLE_64B, WPROMO);
    {
        const cuuint64_t dims[4] = {DM, 2, 8, FF / 16}, strides[3] = {8 * DM * 2, DM * 2, 16 * DM * 2};
        const cuuint32_t box[4] = {16, 2, 8, 12}, es[4] = {1, 1, 1, 1};
        enc(&p.wd, CU_TENSOR_MAP_DATA_TYPE_BFLOAT16, 4, d_in[9], dims, strides, box, es, CU_TENSOR_MAP_INTERLEAVE_NONE,
            CU_TENSOR_MAP_SWIZZLE_32B, WPROMO, CU_TENSOR_MAP_FLOAT_OOB_FILL_NONE);
    }
    fused_decode_kernel<<<NCTAS, NTHREADS, SM_TOTAL, cudaStreamPerThread>>>(
        scr, (const __nv_bfloat16*)d_in[0], (const __nv_bfloat16*)d_in[6], (__nv_bfloat16*)d_out, p);
}
```

```cpp
#include <cuda_runtime.h>
#include <cuda_bf16.h>
#include <cuda.h>
#include <stdint.h>

namespace {

constexpr int NB = 4, NH = 32, SK = 8192, DH = 192, DM = 640, FF = 1536;
constexpr int NBH = NB * NH;
constexpr int TILE = 64;
constexpr int UPB = SK / TILE;
constexpr int NUNITS = NBH * UPB;
constexpr int TILE_BYTES = TILE * DH * 2;
constexpr int TILE_ROWS = TILE * 3;
constexpr int NCTAS = 132;
constexpr int NQ_CTAS = 128;
constexpr int NE_CTAS = 112;
__host__ __device__ constexpr bool is_f(int cta) { return cta < NE_CTAS && cta % 14 < 11 && !(cta & 1); }
__host__ __device__ constexpr bool is_g(int cta) { return cta < NE_CTAS && cta % 14 < 11 && (cta & 1); }
__host__ __device__ constexpr int ffn_slice(int cta) { return cta / 14 * ((cta & 1) ? 5 : 6) + cta % 14 / 2; }

#define NWORK 2
#define LAG 3
#define NPOOL 896
#define RED0 116
#define RING 12
#define OREP 2
#define WQ_LINES 128
#define K0_AT_NS 900
#define WO_AT_NS (K0_AT_NS + 2000)
#define K1_AT_NS (K0_AT_NS + 4400)
#define WO_STEP_NS 75
#define CLEAR_AT_NS 7000
constexpr int KSWEEP_NS = 2000;
#define FW_TICKET (NPOOL + 32)
#define FW_AT_NS 2090
#define FW_GAP 280
#define FW_MID 2100
#define FW_GAP2 200
#define HGATE_NS 700
#define SLOT_TICKS 9
#define SLOT_OPEN 3
#define PH_O 0
#define PH_H 8
#define PH_M 2
#define NPROBE 24
#define MIX_R 6
#define MIX_FROM 1
#define MIX_ROWS 3
constexpr int MIX = MIX_ROWS * UPB, MIX1 = (NBH - 4) * UPB, MIX0 = MIX1 - (MIX1 - MIX_FROM * NWORK * NCTAS) / MIX * MIX;
static_assert((MIX1 - (NUNITS - NPOOL)) % MIX == 0, "the pool starts with a group of rows");
__device__ __forceinline__ int unit_of(int t) {
    const unsigned r = (unsigned)(t - MIX0) % MIX, e = t - MIX1;
    if (e < 4 * UPB) return MIX1 + (e & 256) + (e & 3) * 64 + (e & 255) / 4;
    return t < MIX0 || t >= MIX1 ? t : t - r + r % MIX_R * (MIX / MIX_R) + r / MIX_R;
}
static_assert(FW_TICKET < NPOOL + NWORK * NCTAS, "every worker draws one ticket beyond the pool");
constexpr int NAUX = 8;
constexpr int NTHREADS = (NAUX + NWORK + 2) * 32;
constexpr int SPIN_MAX = 1 << 22;

constexpr int SM_KV = 0;
constexpr int SM_A = SM_KV + NWORK * TILE_BYTES;
constexpr int SM_W = SM_A + 61440;
constexpr int SM_X = SM_W + 81920;
constexpr int XPITCH = 648;
constexpr int HPITCH = 1344;
constexpr int SM_RED = SM_X + 5 * HPITCH + 64;
constexpr int SM_RED2 = SM_RED + 8 * 48 * 4 * 4;
constexpr int SM_MISC = SM_RED2 + 4096;
constexpr int BAR_WQ = SM_MISC, SM_SCRAP = SM_MISC + 32, BAR_WO = SM_MISC + 40, SM_SIDE = SM_MISC + 48, BAR_H = SM_MISC + 56, BAR_FW = SM_MISC + 64;
constexpr int BAR_KV = BAR_FW + 64;
constexpr int SM_TOTAL = BAR_KV + NWORK * 8;
static_assert(SM_W % 1024 == 0 && NB * XPITCH * 2 <= 4 * HPITCH && SM_RED % 128 == 0, "smem layout");

struct Params {
    CUtensorMap k, v;
    CUtensorMap wq;
    CUtensorMap wo;
    CUtensorMap wg, wu;
    CUtensorMap wd;
};

struct Early {
    uint32_t q[4][4][8];
    uint32_t umax[UPB];
};
struct Twin { uint32_t w[4][1024]; };
constexpr int PROBE = 1024 - 32;
#define LSTRIDE 16
struct State {
    Twin ax[3];
    Twin hx;
    Twin ox[(OREP + 1) / 2];
    Twin lx;
    float4 oacc[NBH * 64];
    float2 attn[NB][DM];
    uint32_t fw_time[32];
    float2 lsum[NBH][LSTRIDE];
    uint32_t score[NPOOL][32];
};
__host__ __device__ constexpr int oidx(int row, int grp) {
    return (row >> 2) * 256 + ((row & 1) * 2 + (grp >> 5)) * 64 + (row & 2) * 16 + (grp & 31);
}
constexpr int STATE_V4 = ((sizeof(State) / 32 + NQ_CTAS - 1) / NQ_CTAS) * 2;
static_assert(sizeof(State) % 32 == 0, "State is cleared in whole sectors");
static_assert(sizeof(Early) == 64 * 16, "an Early entry is cleared by 64 threads");
struct Scratch {
    State st;
    unsigned work[64];
    unsigned cnt_z[32];
    Early early[NBH];
    alignas(4096) float4 ring[RING][UPB][64];
};
constexpr size_t PAGE = 2u << 20;
static_assert(sizeof(Scratch) <= PAGE, "scratch must fit one page");
__device__ __align__(128) unsigned char g_raw[2 * PAGE];
#define g_early scr->early
#define g_st scr->st
#define g_ring scr->ring
#define g_cnt_z scr->cnt_z
#define g_work scr->work
#define ALL_LOADERS 0
#define TS(i)
#define TSW(i)
#define TS2(i)
#define TSI(n, i)
#define PH(i)
#define CK(i, dep)
#define ARR()
#define PROG(u)

__device__ __forceinline__ uint32_t s2u(const void* p) { return (uint32_t)__cvta_generic_to_shared(p); }
__device__ __forceinline__ void mbar_init(uint32_t bar, int cnt) {
    asm volatile("mbarrier.init.shared::cta.b64 [%0], %1;" :: "r"(bar), "r"(cnt) : "memory");
}
__device__ __forceinline__ void mbar_wait(uint32_t bar, uint32_t parity) {
    asm volatile("{\n.reg .pred p;\n.reg .u32 n;\nmov.u32 n, 0;\nWAIT_LOOP:\n"
                 "mbarrier.try_wait.parity.shared::cta.b64 p, [%0], %1;\n"
                 "@p bra WAIT_DONE;\nadd.u32 n, n, 1;\nsetp.lt.u32 p, n, %2;\n@p bra WAIT_LOOP;\nWAIT_DONE:\n}"
                 :: "r"(bar), "r"(parity), "n"(SPIN_MAX) : "memory");
}
__device__ __forceinline__ void request_tile(uint32_t dst, const CUtensorMap* tm, int unit, uint32_t bar, uint64_t pol) {
    asm volatile("{\n.reg .pred p;\nelect.sync _|p, 0xffffffff;\n"
                 "@p mbarrier.arrive.expect_tx.shared::cta.b64 _, [%2], %6;\n"
                 "@p cp.async.bulk.tensor.2d.shared::cluster.global.mbarrier::complete_tx::bytes.L2::cache_hint "
                 "[%0], [%1, {%3, %4}], [%2], %5;\n}"
                 :: "r"(dst), "l"(tm), "r"(bar), "r"(0), "r"(unit * TILE_ROWS), "l"(pol), "n"(TILE_BYTES) : "memory");
}
__device__ __forceinline__ void put_groups(void* dst, int mode, const float (&o)[6], float tag, float tag2) {
    asm volatile("{\n.reg .pred s, t;\n.reg .b128 u, v;\n.reg .b64 a, b;\n"
                 "setp.eq.s32 s, %1, 0;\nsetp.ne.s32 t, %1, 2;\nxor.b64 a, %0, 4096;\n"
                 "@t bra.uni SINGLE;\n"
                 "red.relaxed.gpu.global.add.v4.f32 [a], {%2,%3,%4,%8};\n"
                 "red.relaxed.gpu.global.add.v4.f32 [a+128], {%5,%6,%7,%9};\n"
                 "SINGLE:\n"
                 "@s bra.uni STORE;\n"
                 "red.relaxed.gpu.global.add.v4.f32 [%0], {%2,%3,%4,%8};\n"
                 "red.relaxed.gpu.global.add.v4.f32 [%0+128], {%5,%6,%7,%9};\n"
                 "STORE:\n"
                 "mov.b64 a, {%2, %3};\nmov.b64 b, {%4, %8};\nmov.b128 u, {a, b};\n"
                 "mov.b64 a, {%5, %6};\nmov.b64 b, {%7, %9};\nmov.b128 v, {a, b};\n"
                 "@s st.relaxed.gpu.global.b128 [%0], u;\n@s st.relaxed.gpu.global.b128 [%0+128], v;\n}"
                 :: "l"(dst), "r"(mode), "f"(o[0]), "f"(o[1]), "f"(o[2]), "f"(o[3]), "f"(o[4]), "f"(o[5]), "f"(tag), "f"(tag2) : "memory");
}
__device__ __forceinline__ void request_box(uint32_t dst, const CUtensorMap* tm, int col, int row, uint32_t bar, uint32_t bytes) {
    asm volatile("{\n.reg .pred p, q;\nelect.sync _|p, 0xffffffff;\nsetp.ne.and.u32 q, %5, 0, p;\n"
                 "@q mbarrier.arrive.expect_tx.shared::cta.b64 _, [%2], %5;\n"
                 "@p cp.async.bulk.tensor.2d.shared::cluster.global.mbarrier::complete_tx::bytes [%0], [%1, {%3, %4}], [%2];\n}"
                 :: "r"(dst), "l"(tm), "r"(bar), "r"(col), "r"(row), "r"(bytes) : "memory");
}
__device__ __forceinline__ uint32_t lds32(uint32_t addr) {
    uint32_t v;
    asm volatile("ld.shared.u32 %0, [%1];" : "=r"(v) : "r"(addr) : "memory");
    return v;
}
__device__ __forceinline__ void ldsm4(uint32_t (&r)[4], uint32_t addr) {
    asm volatile("ldmatrix.sync.aligned.m8n8.x4.shared.b16 {%0,%1,%2,%3}, [%4];"
                 : "=r"(r[0]), "=r"(r[1]), "=r"(r[2]), "=r"(r[3]) : "r"(addr) : "memory");
}
__device__ __forceinline__ void ldsm4t(uint32_t (&r)[4], uint32_t addr) {
    asm volatile("ldmatrix.sync.aligned.m8n8.x4.trans.shared.b16 {%0,%1,%2,%3}, [%4];"
                 : "=r"(r[0]), "=r"(r[1]), "=r"(r[2]), "=r"(r[3]) : "r"(addr) : "memory");
}
__device__ __forceinline__ void mma16816(float (&c)[4], const uint32_t (&a)[4], uint32_t b0, uint32_t b1) {
    asm volatile("mma.sync.aligned.m16n8k16.row.col.f32.bf16.bf16.f32 {%0,%1,%2,%3}, {%4,%5,%6,%7}, {%8,%9}, {%0,%1,%2,%3};"
                 : "+f"(c[0]), "+f"(c[1]), "+f"(c[2]), "+f"(c[3])
                 : "r"(a[0]), "r"(a[1]), "r"(a[2]), "r"(a[3]), "r"(b0), "r"(b1));
}
struct Warm {
    float c[4] = {};
    __device__ __forceinline__ void operator()() {
        asm volatile("mma.sync.aligned.m16n8k8.row.col.f32.bf16.bf16.f32 {%0,%1,%2,%3}, {%4,%4}, {%4}, {%0,%1,%2,%3};"
                     : "+f"(c[0]), "+f"(c[1]), "+f"(c[2]), "+f"(c[3]) : "r"(0));
    }
    __device__ __forceinline__ void done(uint32_t scrap) {
        asm volatile("{\n.reg .pred p;\nsetp.gt.f32 p, %1, 0f3f800000;\n@p st.shared.f32 [%0], %1;\n}" :: "r"(scrap), "f"(c[0]) : "memory");
    }
};
__device__ __forceinline__ uint4 ld_relaxed_v4(const void* p) {
    uint4 v;
    asm volatile("ld.relaxed.gpu.global.v4.u32 {%0,%1,%2,%3}, [%4];" : "=r"(v.x), "=r"(v.y), "=r"(v.z), "=r"(v.w) : "l"(p) : "memory");
    return v;
}
__device__ __forceinline__ float4 ld_relaxed_f4(const void* p) {
    float4 v;
    asm volatile("ld.relaxed.gpu.global.v4.f32 {%0,%1,%2,%3}, [%4];" : "=f"(v.x), "=f"(v.y), "=f"(v.z), "=f"(v.w) : "l"(p) : "memory");
    return v;
}
__device__ __forceinline__ float2 ld_relaxed_f2(const void* p) {
    float2 v;
    asm volatile("ld.relaxed.gpu.global.v2.f32 {%0,%1}, [%2];" : "=f"(v.x), "=f"(v.y) : "l"(p) : "memory");
    return v;
}
__device__ __forceinline__ float4 ld_relaxed_b128(const void* p) {
    float4 v;
    asm volatile("{\n.reg .b128 t;\n.reg .b64 a, b;\nld.relaxed.gpu.global.b128 t, [%4];\nmov.b128 {a, b}, t;\n"
                 "mov.b64 {%0, %1}, a;\nmov.b64 {%2, %3}, b;\n}" : "=f"(v.x), "=f"(v.y), "=f"(v.z), "=f"(v.w) : "l"(p) : "memory");
    return v;
}
__device__ __forceinline__ void st_relaxed_b128(void* p, float x, float y, float z, float w) {
    asm volatile("{\n.reg .b128 t;\n.reg .b64 a, b;\nmov.b64 a, {%1, %2};\nmov.b64 b, {%3, %4};\nmov.b128 t, {a, b};\n"
                 "st.relaxed.gpu.global.b128 [%0], t;\n}" :: "l"(p), "f"(x), "f"(y), "f"(z), "f"(w) : "memory");
}
__device__ __forceinline__ unsigned ld_acquire(const unsigned* p) {
    unsigned v;
    asm volatile("ld.acquire.gpu.global.u32 %0, [%1];" : "=r"(v) : "l"(p) : "memory");
    return v;
}
__device__ __forceinline__ void st_relaxed(void* p, uint32_t v) {
    asm volatile("st.relaxed.gpu.global.u32 [%0], %1;" :: "l"(p), "r"(v) : "memory");
}
__device__ __forceinline__ void red_f2(float* p, float a, float b) {
    asm volatile("red.relaxed.gpu.global.add.v2.f32 [%0], {%1,%2};" :: "l"(p), "f"(a), "f"(b) : "memory");
}
__device__ __forceinline__ void draw(int& ticket, unsigned* ctr, bool pred) {
    asm volatile("{\n.reg .pred p;\nsetp.ne.u32 p, %2, 0;\n@p atom.relaxed.gpu.global.inc.u32 %0, [%1], 0x7fffffff;\n}"
                 : "+r"(ticket) : "l"(ctr), "r"((uint32_t)pred) : "memory");
}
__device__ __forceinline__ void red_release(unsigned* p) {
    asm volatile("red.release.gpu.global.add.u32 [%0], 1;" :: "l"(p) : "memory");
}
__device__ __forceinline__ uint32_t ld_relaxed_u32(const void* p) {
    uint32_t v;
    asm volatile("ld.relaxed.gpu.global.u32 %0, [%1];" : "=r"(v) : "l"(p) : "memory");
    return v;
}
__device__ __forceinline__ float rcp_approx(float v) {
    float r;
    asm("rcp.approx.ftz.f32 %0, %1;" : "=f"(r) : "f"(v));
    return r;
}
__device__ __forceinline__ float ex2_approx(float v) {
    float e;
    asm("ex2.approx.ftz.f32 %0, %1;" : "=f"(e) : "f"(v));
    return e;
}
__device__ __forceinline__ float sigmoid_approx(float v) { return rcp_approx(1.0f + ex2_approx(v * -1.4426950408889634f)); }
__device__ __forceinline__ float sqrt_approx(float v) {
    float r;
    asm("sqrt.approx.ftz.f32 %0, %1;" : "=f"(r) : "f"(v));
    return r;
}
__device__ __forceinline__ bool all(bool v) { return __all_sync(0xffffffffu, v); }
__device__ __forceinline__ void wait_count(const unsigned* p, unsigned target) {
#pragma unroll 1
    for (int it = 0; it < SPIN_MAX; it++) {
        if (all(ld_acquire(p) >= target)) break;
        __nanosleep(400);
    }
}
__device__ __forceinline__ float wait_sum(const void* p, float n, int nap = 0) {
    float2 v;
#pragma unroll 1
    for (int it = 0; it < SPIN_MAX; it++) {
        v = ld_relaxed_f2(p);
        if (all(v.y >= n)) break;
        if (all(v.y == 0.f)) __nanosleep(600);
        else if (nap) __nanosleep(nap);
    }
    return v.x;
}
__device__ __forceinline__ void wait_row(const Scratch* scr, int bh, float n) { wait_sum(g_st.lsum[bh], n); }
__device__ __forceinline__ void wait_row_o(const Scratch* scr, int bh, float n) {
    wait_row(scr, bh, n);
    if (bh >= RED0) return;
#pragma unroll 1
    for (int it = 0; it < SPIN_MAX; it++) {
        if (all(__uint_as_float(ld_relaxed_u32(&g_st.oacc[oidx(bh, 0)].w)) == UPB)) break;
        __nanosleep(300);
    }
}
constexpr uint32_t SLOT_K = (uint32_t)(((1ull << 32) + SLOT_TICKS - 1) / SLOT_TICKS);
#define SLOT_ASM(t, n, p, phase, k, open) \
    "mov.u32 " n ", 0;\nSLOT:\nmov.u32 " t ", %%globaltimer_lo;\nadd.u32 " n ", " n ", 1;\nsetp.lt.u32 " p ", " n ", 24;\nshr.u32 " t ", " t ", 5;\n" \
    "mad.lo.u32 " t ", " t ", " k ", " phase ";\nsetp.ge.and.u32 " p ", " t ", " open ", " p ";\n@" p " bra.uni SLOT;\n"
template <int PHASE> __host__ __device__ constexpr uint32_t slot_phase() { return SLOT_K / 2 - PHASE * SLOT_K; }
template <int PHASE> __device__ __forceinline__ void wait_slot() {
    if (PHASE < 0) return;
    asm volatile("{\n.reg .pred p;\n.reg .b32 t, n;\n" SLOT_ASM("t", "n", "p", "%0", "%1", "%2") "}"
                 :: "n"(slot_phase<PHASE>()), "n"(SLOT_K), "n"(SLOT_OPEN * SLOT_K) : "memory");
}
__device__ __forceinline__ void wait_time(uint32_t t) {
#pragma unroll 1
    for (int it = 0; it < SPIN_MAX; it++) {
        uint32_t now;
        asm volatile("mov.u32 %0, %%globaltimer_lo;" : "=r"(now));
        if (all((int)(now - t) >= 0)) break;
    }
}
__device__ __forceinline__ void wait_clock(uint32_t t, Warm& warm) { while (!all((int)(clock() - t) >= 0)) { warm(); } }
__device__ __forceinline__ uint32_t pack_bf16(float lo, float hi) {
    uint32_t r;
    asm("cvt.rn.bf16x2.f32 %0, %1, %2;" : "=r"(r) : "f"(hi), "f"(lo));
    return r;
}
__device__ __forceinline__ float bf16r(float v) { return __uint_as_float(pack_bf16(0.f, v)); }
__device__ __forceinline__ uint32_t nonzero(uint32_t w) { return w ? w : 0x80008000u; }
__device__ __forceinline__ uint32_t pack_neg(float lo, float hi) { return nonzero(pack_bf16(-lo, -hi)); }
__device__ __forceinline__ float lo_f(uint32_t v) { return __uint_as_float(v << 16); }
__device__ __forceinline__ float hi_f(uint32_t v) { return __uint_as_float(v & 0xffff0000u); }
__device__ __forceinline__ float warp_sum(float v) {
#pragma unroll
    for (int o = 16; o; o >>= 1) v += __shfl_xor_sync(0xffffffffu, v, o);
    return v;
}
__device__ __forceinline__ void layernorm20(float (&v)[20]) {
    float s = 0.f;
#pragma unroll
    for (int i = 0; i < 20; i++) s += v[i];
    const float mean = warp_sum(s) * (1.0f / DM);
    float q = 0.f;
#pragma unroll
    for (int i = 0; i < 20; i++) { const float d = v[i] - mean; q += d * d; }
    const float var = bf16r(warp_sum(q) * (1.0f / DM));
    const float m = bf16r(mean);
    const float rden = 1.0f / bf16r(sqrtf(bf16r(var + 1e-5f)));
#pragma unroll
    for (int i = 0; i < 20; i++) v[i] = bf16r(bf16r(v[i] - m) * rden);
}

__device__ __forceinline__ void moments(float m1, float m2, float& nmean, float& rden) {
    m1 *= 1.0f / DM;
    const float var = bf16r(fmaxf(fmaf(-m1, m1, m2 * (1.0f / DM)), 0.f));
    nmean = bf16r(m1);
    rden = rcp_approx(bf16r(sqrt_approx(bf16r(var + 1e-5f))));
}
__device__ __forceinline__ float sel4(int j, float a, float b, float c, float d) {
    float lo, hi, r;
    asm("{\n.reg .pred p;\nsetp.ne.s32 p, %3, 0;\nselp.f32 %0, %2, %1, p;\n}" : "=f"(lo) : "f"(a), "f"(b), "r"(j & 1));
    asm("{\n.reg .pred p;\nsetp.ne.s32 p, %3, 0;\nselp.f32 %0, %2, %1, p;\n}" : "=f"(hi) : "f"(c), "f"(d), "r"(j & 1));
    asm("{\n.reg .pred p;\nsetp.ne.s32 p, %3, 0;\nselp.f32 %0, %2, %1, p;\n}" : "=f"(r) : "f"(lo), "f"(hi), "r"(j & 2));
    return r;
}
template <typename T> __device__ __forceinline__ void pin(T*& p) { asm volatile("" : "+l"(p)); }
__device__ __forceinline__ void pin(uint32_t& v) { asm volatile("" : "+r"(v)); }
__device__ __forceinline__ void pin(float& v) { asm volatile("" : "+f"(v)); }
__device__ __forceinline__ uint32_t after(uint32_t n, float v) {
    asm volatile("{\n.reg .pred p;\nsetp.eq.u32 p, %1, 0x7fc1a5a5;\n@p add.u32 %0, %0, 32;\n}" : "+r"(n) : "r"(__float_as_uint(v)));
    return n;
}
__device__ __forceinline__ float2 lds64f(uint32_t addr) {
    float2 v;
    asm volatile("ld.shared.v2.f32 {%0,%1}, [%2];" : "=f"(v.x), "=f"(v.y) : "r"(addr) : "memory");
    return v;
}
__device__ __forceinline__ void sts32f(uint32_t addr, float v) { asm volatile("st.shared.f32 [%0], %1;" :: "r"(addr), "f"(v) : "memory"); }
template <int ID> __device__ __forceinline__ void fin_arrive() { asm volatile("bar.arrive %0, 288;" :: "n"(ID) : "memory"); }
template <int ID> __device__ __forceinline__ void fin_sync() { asm volatile("bar.sync %0, 288;" :: "n"(ID) : "memory"); }
template <int ID> __device__ __forceinline__ void fin_sync(uint32_t n) { asm volatile("bar.sync %0, %1;" :: "n"(ID), "r"(n) : "memory"); }
__device__ __forceinline__ float2 sum8(uint32_t addr, int pitch) {
    float2 t[8];
#pragma unroll
    for (int w = 0; w < 8; w++) t[w] = lds64f(addr + w * pitch);
    return make_float2(((t[0].x + t[1].x) + (t[2].x + t[3].x)) + ((t[4].x + t[5].x) + (t[6].x + t[7].x)),
                       ((t[0].y + t[1].y) + (t[2].y + t[3].y)) + ((t[4].y + t[5].y) + (t[6].y + t[7].y)));
}
__device__ __forceinline__ float4 sum4x4(uint32_t addr, int pitch) {
    float4 t[4];
#pragma unroll
    for (int w = 0; w < 4; w++)
        asm volatile("ld.shared.v4.f32 {%0,%1,%2,%3}, [%4];" : "=f"(t[w].x), "=f"(t[w].y), "=f"(t[w].z), "=f"(t[w].w) : "r"(addr + w * pitch) : "memory");
    return make_float4((t[0].x + t[1].x) + (t[2].x + t[3].x), (t[0].y + t[1].y) + (t[2].y + t[3].y),
                       (t[0].z + t[1].z) + (t[2].z + t[3].z), (t[0].w + t[1].w) + (t[2].w + t[3].w));
}
__device__ __forceinline__ void sts64f(uint32_t addr, float x, float y) {
    asm volatile("st.shared.v2.f32 [%0], {%1,%2};" :: "r"(addr), "f"(x), "f"(y) : "memory");
}
__device__ __forceinline__ uint4 lds128(uint32_t addr) {
    uint4 v;
    asm volatile("ld.shared.v4.u32 {%0,%1,%2,%3}, [%4];" : "=r"(v.x), "=r"(v.y), "=r"(v.z), "=r"(v.w) : "r"(addr) : "memory");
    return v;
}
__device__ __forceinline__ void ld_relaxed_v4_if(uint4& v, const void* p, bool pred) {
    asm volatile("{\n.reg .pred p;\nsetp.ne.u32 p, %5, 0;\n@p ld.relaxed.gpu.global.v4.u32 {%0,%1,%2,%3}, [%4];\n}"
                 : "+r"(v.x), "+r"(v.y), "+r"(v.z), "+r"(v.w) : "l"(p), "r"((uint32_t)pred) : "memory");
}
__device__ __forceinline__ void sts128f(uint32_t addr, float x, float y, float z, float w) {
    asm volatile("st.shared.v4.f32 [%0], {%1,%2,%3,%4};" :: "r"(addr), "f"(x), "f"(y), "f"(z), "f"(w) : "memory");
}
template <int NJ>
__device__ __forceinline__ void load_o(uint32_t (&ob)[3 * NJ][2], const Scratch* scr, int bh, int J0, int j) {
    float4 v[NJ][4];
    float2 l;
#pragma unroll 1
    for (int it = 0; it < SPIN_MAX; it++) {
#pragma unroll
        for (int J = 0; J < NJ; J++) {
#pragma unroll
            for (int e = 0; e < 4; e++) v[J][e] = ld_relaxed_f4(&g_st.oacc[oidx(bh, j)] + oidx(0, (J0 + J) * 16 + e * 4));
        }
        l = ld_relaxed_f2(g_st.lsum[bh]);
        bool ok = l.y == UPB;
#pragma unroll
        for (int J = 0; J < NJ; J++) {
#pragma unroll
            for (int e = 0; e < 4; e++) ok &= v[J][e].w == UPB;
        }
        if (all(ok)) break;
    }
    const float rl = __fdividef(1.0f, l.x);
#pragma unroll
    for (int J = 0; J < NJ; J++) {
        ob[3 * J][0] = pack_bf16(v[J][0].x * rl, v[J][1].x * rl);     ob[3 * J][1] = pack_bf16(v[J][2].x * rl, v[J][3].x * rl);
        ob[3 * J + 1][0] = pack_bf16(v[J][0].y * rl, v[J][1].y * rl); ob[3 * J + 1][1] = pack_bf16(v[J][2].y * rl, v[J][3].y * rl);
        ob[3 * J + 2][0] = pack_bf16(v[J][0].z * rl, v[J][1].z * rl); ob[3 * J + 2][1] = pack_bf16(v[J][2].z * rl, v[J][3].z * rl);
    }
}
__device__ __forceinline__ int near_side(uint32_t sb) {
    uint32_t v;
    asm volatile("ld.volatile.shared.u32 %0, [%1];" : "=r"(v) : "r"(sb + SM_SIDE) : "memory");
    return v;
}
__device__ __forceinline__ void poll_row(uint4& a, uint4& b, uint2& c, const void* pa, const void* pb, const void* pc, uint32_t sa, uint32_t sc,
                                         bool arrive, bool nap, uint32_t bar, Warm& warm) {
    asm volatile("{\n.reg .pred p, q, r, s;\n.reg .b32 m, n, it;\n"
                 "setp.ne.u32 r, %19, 0;\nsetp.ne.u32 s, %20, 0;\nmov.u32 it, 0;\n"
                 "POLL:\n"
                 SLOT_ASM("m", "n", "p", "%23", "%24", "%25")
                 "ld.relaxed.gpu.global.v4.u32 {%0,%1,%2,%3}, [%14];\n"
                 "ld.relaxed.gpu.global.v4.u32 {%4,%5,%6,%7}, [%15];\n"
                 "ld.relaxed.gpu.global.v2.u32 {%8,%9}, [%16];\n"
                 "add.u32 it, it, 1;\nsetp.ge.u32 q, it, %21;\n"
                 "mov.u32 m, 0;\nmma.sync.aligned.m16n8k8.row.col.f32.bf16.bf16.f32 {%10,%11,%12,%13}, {m,m}, {m}, {%10,%11,%12,%13};\n"
                 "st.shared.v4.u32 [%17], {%0,%1,%2,%3};\n"
                 "st.shared.v4.u32 [%17+512], {%4,%5,%6,%7};\n"
                 "st.shared.v2.u32 [%18], {%8,%9};\n"
                 "min.u32 m, %0, %1;\nmin.u32 m, m, %2;\nmin.u32 n, %3, %4;\nmin.u32 n, n, %5;\nmin.u32 m, m, %6;\nmin.u32 m, m, %7;\n"
                 "min.u32 n, n, m;\nmin.u32 m, %8, %9;\nmin.u32 m, m, n;\n"
                 "setp.ne.or.u32 p, m, 0, q;\n"
                 "vote.sync.all.pred p, p, 0xffffffff;\n"
                 "and.pred q, p, r;\n"
                 "bar.warp.sync 0xffffffff;\n"
                 "@q mbarrier.arrive.shared::cta.b64 _, [%22];\n"
                 "@p bra.uni DONE;\n"
                 "@s nanosleep.u32 500;\n"
                 "bra.uni POLL;\n"
                 "DONE:\n}"
                 : "=&r"(a.x), "=&r"(a.y), "=&r"(a.z), "=&r"(a.w), "=&r"(b.x), "=&r"(b.y), "=&r"(b.z), "=&r"(b.w), "=&r"(c.x), "=&r"(c.y),
                   "+f"(warm.c[0]), "+f"(warm.c[1]), "+f"(warm.c[2]), "+f"(warm.c[3])
                 : "l"(pa), "l"(pb), "l"(pc), "r"(sa), "r"(sc), "r"((uint32_t)arrive), "r"((uint32_t)nap), "n"(SPIN_MAX), "r"(bar),
                   "n"(slot_phase<PH_H>()), "n"(SLOT_K), "n"(SLOT_OPEN * SLOT_K) : "memory");
}
__device__ __forceinline__ void aux_sync() { asm volatile("bar.sync 1, 256;" ::: "memory"); }

__global__ void __launch_bounds__(NTHREADS, 1)
fused_decode_kernel(Scratch* const scr, const __nv_bfloat16* const x, const __nv_bfloat16* const w_r, __nv_bfloat16* const out_all,
                    const __nv_bfloat16* const wq, const __grid_constant__ Params p) {
    extern __shared__ __align__(1024) unsigned char smem[];
    const uint32_t sb = s2u(smem);
    const int tid = threadIdx.x, cta = blockIdx.x;
    asm volatile("{\n.reg .pred p;\nsetp.lt.u32 p, %1, %2;\n@p prefetch.global.L2 [%0];\n}"
                 :: "l"(wq + (cta * WQ_LINES + tid) * 64), "r"(tid), "n"(WQ_LINES) : "memory");
    if (tid < 32 && cta < NQ_CTAS) {
        asm volatile("{\n.reg .pred p;\nelect.sync _|p, 0xffffffff;\n"
                     "@p mbarrier.init.shared::cta.b64 [%2], 1;\n"
                     "@p fence.mbarrier_init.release.cluster;\n"
                     "@p mbarrier.arrive.expect_tx.shared::cta.b64 _, [%2], 15360;\n"
                     "@p cp.async.bulk.tensor.2d.shared::cluster.global.mbarrier::complete_tx::bytes [%0], [%1, {%3, %4}], [%2];\n"
                     "@p mbarrier.init.shared::cta.b64 [%2+8], 1;\n@p mbarrier.init.shared::cta.b64 [%2+16], 1;\n"
                     "@p mbarrier.init.shared::cta.b64 [%2+24], 1;\n"
                     "@p fence.mbarrier_init.release.cluster;\n"
                     "@p mbarrier.arrive.expect_tx.shared::cta.b64 _, [%2+8], 15360;\n"
                     "@p cp.async.bulk.tensor.2d.shared::cluster.global.mbarrier::complete_tx::bytes [%0+15360], [%1, {%3, %5}], [%2+8];\n"
                     "@p mbarrier.arrive.expect_tx.shared::cta.b64 _, [%2+16], 15360;\n"
                     "@p cp.async.bulk.tensor.2d.shared::cluster.global.mbarrier::complete_tx::bytes [%0+30720], [%1, {%3, %6}], [%2+16];\n"
                     "@p mbarrier.arrive.expect_tx.shared::cta.b64 _, [%2+24], 15360;\n"
                     "@p cp.async.bulk.tensor.2d.shared::cluster.global.mbarrier::complete_tx::bytes [%0+46080], [%1, {%3, %7}], [%2+24];\n}"
                     :: "r"(sb + SM_W), "l"(&p.wq), "r"(sb + BAR_WQ), "r"(cta * 48), "r"(0), "r"(160), "r"(320), "r"(480) : "memory");
    }
    const int warp = __shfl_sync(0xffffffffu, tid >> 5, 0), lane = tid & 31;
    constexpr int grid = NCTAS;
    const int g = lane >> 2, j = lane & 3;
    uint32_t t_start;
    asm volatile("mov.u32 %0, %%globaltimer_lo;" : "=r"(t_start));
    TS(0);
    if (tid == 32) {
        mbar_init(sb + BAR_WO, 1);
        mbar_init(sb + BAR_H, 1);
#pragma unroll
        for (int i = 0; i < 8 + NWORK; i++) mbar_init(sb + BAR_FW + i * 8, 1);
        sts32f(sb + SM_SIDE, 0.f);
        asm volatile("fence.mbarrier_init.release.cluster;" ::: "memory");
        asm volatile("fence.proxy.async.shared::cta;" ::: "memory");
    }
    __syncthreads();
    if (warp >= NAUX + NWORK) {
        const int fw = warp - (NAUX + NWORK), fi = ffn_slice(cta);
        if (fw == 0) {
            wait_time(t_start + CLEAR_AT_NS);
            if (cta < NQ_CTAS) {
#pragma unroll
                for (int i = lane; i < STATE_V4; i += 32)
                    if (cta * STATE_V4 + i < (int)(sizeof(State) / 16)) reinterpret_cast<uint4*>(&g_st)[cta * STATE_V4 + i] = make_uint4(0u, 0u, 0u, 0u);
                __syncwarp();
                if (lane == 0) red_release(g_cnt_z);
            }
            TSW(2); wait_count(g_cnt_z, NQ_CTAS); TSW(29);
            asm volatile("bar.arrive 2, %0;" :: "n"((NWORK + 2) * 32) : "memory");
            fin_arrive<3>();
        } else {
#pragma unroll 1
            for (int n = cta < NE_CTAS ? 5 : 4, i = n - 1; i >= 0; i--) {
                const int head = cta < NE_CTAS ? cta >> 2 : 28 + i;
                wait_time(t_start + WO_AT_NS + (NH - 1 - head) * WO_STEP_NS);
                request_box(sb + SM_A + i * 12288, &p.wo, cta < NE_CTAS ? (cta & 3) * 160 + i * 32 : (cta - NE_CTAS) * 32,
                            head * DH, sb + BAR_WO, i == n - 1 ? n * 12288 : 0);
            }
            asm volatile("bar.sync 2, %0;" :: "n"((NWORK + 2) * 32) : "memory");
            uint32_t best[2] = {~0u, ~0u};
#pragma unroll 1
            for (int i = 0; i < NPROBE; i++) {
#pragma unroll
                for (int c = 0; c < 2; c++) {
                    uint32_t t0 = clock(), t1 = t0;
                    int v = 0;
                    draw(v, &g_st.hx.w[c][PROBE], lane == 0);
                    asm volatile("{\n.reg .pred p;\nsetp.ne.u32 p, %1, 0xffffffff;\n@p mov.u32 %0, %%clock;\n}" : "+r"(t1) : "r"(v) : "memory");
                    best[c] = min(best[c], t1 - t0);
                }
                __nanosleep(1000);
            }
            if (lane == 0) sts32f(sb + SM_SIDE, __uint_as_float(best[1] < best[0]));
        }
        int job = cta;
        auto sum_rows = [&](int row_end) {
#pragma unroll 1
            for (; job < 8 * min(row_end, RED0); job += NCTAS) {
                const int row = job >> 3, grp = (job & 7) * 8 + (lane & 7);
                wait_row(scr, row, UPB);
                const float4* src = &g_ring[row % RING][lane >> 3][grp];
                float sx = 0.f, sy = 0.f, sz = 0.f;
#pragma unroll 1
                for (int i = 0; i < 2; i++, src += 64 * 64) {
                    float4 v[16];
#pragma unroll 1
                    for (int it = 0; it < SPIN_MAX; it++) {
                        bool ok = true;
#pragma unroll
                        for (int k = 0; k < 16; k++) v[k] = ld_relaxed_b128(src + k * 4 * 64);
#pragma unroll
                        for (int k = 0; k < 16; k++) ok &= v[k].w == (float)(row + 1);
                        if (all(ok)) break;
                    }
#pragma unroll
                    for (int k = 0; k < 16; k++) { sx += v[k].x; sy += v[k].y; sz += v[k].z; }
                }
#pragma unroll
                for (int o = 8; o < 32; o <<= 1) {
                    sx += __shfl_xor_sync(0xffffffffu, sx, o); sy += __shfl_xor_sync(0xffffffffu, sy, o); sz += __shfl_xor_sync(0xffffffffu, sz, o);
                }
                if (lane < 8) st_relaxed_b128(&g_st.oacc[oidx(row, grp)], sx, sy, sz, UPB);
            }
        };
        const int ho0 = lane / 20 * 256 + lane % 20 * 4, ho1 = (lane + 32) / 20 * 256 + (lane + 32) % 20 * 4, ho2 = 3 * 256 + 16 + 2 * lane;
        uint32_t wr[10] = {};
        float wsum = 0.f;
        if (is_g(cta) && fw == 0) {
#pragma unroll
            for (int i = 0; i < 10; i++) {
                const int w = 4 * lane + 128 * (i >> 2) + (i & 3) - (i >= 8 ? 2 * lane : 0);
                wr[i] = *reinterpret_cast<const uint32_t*>(w_r + (w >> 4) * 32 + (w & 3) * 8 + ((w >> 1) & 6));
                wsum += lo_f(wr[i]) + hi_f(wr[i]);
            }
            wsum = warp_sum(wsum);
        }
        const int fb = lane >> 3, fg = lane & 7;
        if (fw == 0) {
#pragma unroll
            for (int i = lane; i < DM / 2; i += 32) sts32f(sb + SM_X + 4 * HPITCH + i * 4, __uint_as_float(0x3f803f80u));
        }
        Warm warm;
        float nmean = 0.f, rden = 0.f, sig = 0.f;
#pragma unroll 1
        for (int b = 0; b < NB; b++) {
            const bool ffn = b >= NB - 2;
            if (fw == 0) {
                sum_rows((b + 1) * NH);
                if (ffn) asm volatile("bar.arrive 8, 64;" ::: "memory");
            } else if (ffn) {
                asm volatile("bar.sync 8, 64;" ::: "memory");
                if (b == NB - 1 && (is_f(cta) || is_g(cta) || ALL_LOADERS)) {
                    uint32_t t0 = 0;
#pragma unroll 1
                    for (int it = 0; it < SPIN_MAX; it++) {
                        t0 = ld_relaxed_u32(g_st.fw_time);
                        if (all(t0 != 0)) break;
                        __nanosleep(150);
                    }
                    asm volatile("fence.proxy.async.shared::cta;" ::: "memory");
                    wait_time(t0 + FW_AT_NS);
                    TSW(9);
                    uint32_t t = clock() + (is_f(cta) ? ((fi & 1) * 24 + (fi >> 1)) * FW_GAP / 48 : FW_MID + ((fi & 3) * 10 + (fi >> 2)) * FW_GAP2 / 40);
#pragma unroll 1
                    for (int i = 0; i < 8; i++) {
                        const uint32_t bar = sb + BAR_FW + i * 8;
                        if (is_f(cta)) {
                            wait_clock(t, warm);
                            request_box(sb + SM_W + i * 10240, (i & 1) ? &p.wu : &p.wg, fi * 32, (i >> 1) * 160, bar, 10240);
                            t += FW_GAP;
                        } else if (is_g(cta)) {
                            wait_clock(t, warm);
                            asm volatile("{\n.reg .pred p;\nelect.sync _|p, 0xffffffff;\n"
                                         "@p mbarrier.arrive.expect_tx.shared::cta.b64 _, [%2], 6144;\n"
                                         "@p cp.async.bulk.tensor.4d.shared::cluster.global.mbarrier::complete_tx::bytes [%0], [%1, {%3, %4, %4, %5}], [%2];\n}"
                                         :: "r"(sb + SM_W + i * 6144), "l"(&p.wd), "r"(bar), "r"(fi * 16), "r"(0), "r"(i * 12) : "memory");
                            t += FW_GAP2;
                        }
                    }
                }
                if (is_f(cta)) {
                    const uint32_t* src = &g_st.hx.w[near_side(sb)][min(fb, b) * 256 + 96];
                    float4 m;
#pragma unroll 1
                    for (int it = 0; it < SPIN_MAX; it++) {
                        wait_slot<PH_M>();
                        m = ld_relaxed_f4(src);
                        warm();
                        if (all(m.y + m.w == 2 * (NCTAS - NE_CTAS))) break;
                        if (b < NB - 1) __nanosleep(500);
                    }
                    moments(m.x, m.z, m.x, m.z);
                    sts64f(sb + SM_RED + 5120 + fb * 8, m.x, m.z);
                }
            }
            if (fw == 0 && cta >= NE_CTAS) {
                const int lc = cta - NE_CTAS, col = lc * 32 + 2 * (lane & 15);
                const uint32_t xv = *reinterpret_cast<const uint32_t*>(x + b * DM + col);
                uint32_t* dst = &(ffn ? g_st.hx.w : g_st.lx.w + 2)[lane >> 4][(b & 1) * 128 + lc / 5 * 256 + lc % 5 * 16 + (col & 6) * 2 + ((col >> 3) & 3)];
                uint32_t part = sb + SM_RED + (lane & 15) * 8;
                wait_row(scr, b * NH + 28, 1);
                float4 early;
#pragma unroll 1
                for (int it = 0; it < SPIN_MAX; it++) {
                    early = ld_relaxed_f4(&g_st.attn[b][col]);
                    if (all(early.y == NE_CTAS / 4 && early.w == NE_CTAS / 4)) break;
                }
                if (early.x != 1.2345f && lane == 0) TS2(6);
                CK(1, __float_as_uint(early.x));
                const float x0 = -(lo_f(xv) + early.x), x1 = -(hi_f(xv) + early.z);
                fin_sync<4>(after(after(288, x0), x1));
                CK(2, lds32(sb + SM_RED));
                const float2 late = sum8(part, 128);
                const uint32_t hv = nonzero(pack_bf16(x0 - late.x, x1 - late.y));
                st_relaxed(dst, hv);
                if (ffn) st_relaxed(dst + 2048, hv);
                CK(3, 0);
                float m = lane < 16 ? lo_f(hv) + hi_f(hv) : fmaf(lo_f(hv), lo_f(hv), hi_f(hv) * hi_f(hv));
#pragma unroll
                for (int o = 1; o < 16; o <<= 1) m += __shfl_xor_sync(0xffffffffu, m, o);
                if ((lane & 14) == 0) red_f2(reinterpret_cast<float*>(&g_st.hx.w[lane & 1][b * 256 + 96 + (lane >> 4) * 2]), m, 1.f);
                fin_arrive<5>();
            }
            if (fw == 0 && (is_g(cta) || is_f(cta))) {
                const uint32_t* src = &(ffn ? g_st.hx.w : g_st.lx.w + 2)[near_side(sb) ^ (ffn && is_g(cta) ? 3 : 0)][(b & 1) * 128];
                const uint32_t hrow = sb + SM_X + b * HPITCH;
                wait_sum(b == NB - 1 ? (const void*)&g_st.lx.w[near_side(sb) ^ 1][3 * 256] : g_st.lsum[b * NH + NH - 1], UPB, 100);
                wait_clock(clock() + HGATE_NS * 2, warm);
                uint4 h0, h1;
                uint2 h2;
                poll_row(h0, h1, h2, src + ho0, src + ho1, src + ho2, hrow + lane * 16, hrow + 1024 + lane * 8, ffn && lane == 0, b < NB - 1, sb + BAR_H, warm);
                CK(4, h0.x);
                if (is_g(cta)) {
                    const uint32_t hw[10] = {h0.x, h0.y, h0.z, h0.w, h1.x, h1.y, h1.z, h1.w, h2.x, h2.y};
                    float m1 = 0.f, m2 = 0.f, rr = 0.f;
#pragma unroll
                    for (int i = 0; i < 10; i++) {
                        const float v0 = lo_f(hw[i]), v1 = hi_f(hw[i]);
                        m1 += v0 + v1;
                        m2 = fmaf(v0, v0, fmaf(v1, v1, m2));
                        rr = fmaf(v0, lo_f(wr[i]), fmaf(v1, hi_f(wr[i]), rr));
                    }
                    moments(warp_sum(m1), warp_sum(m2), m1, m2);
                    const float sg = bf16r(sigmoid_approx(bf16r((m1 * wsum - warp_sum(rr)) * m2)));
                    if (fb == b) { nmean = m1; rden = m2; sig = sg; }
                    __syncwarp();
                    if (ffn) {
                        const int yj = 2 * (fb & 1) + (fb >> 1);
                        uint32_t ypart = sb + SM_RED2 + yj * 128 + ((fg + 2 * yj) & 7) * 16;
                        __nv_bfloat16* out = out_all + fb * DM + fi * 16 + fg;
                        const float2 hw2 = lds64f(sb + SM_X + fb * HPITCH + ((fi >> 1) * 16 + (fg & 6) * 2 + (fi & 1) * 2) * 4);
                        const uint32_t w0 = __float_as_uint(hw2.x), w1 = __float_as_uint(hw2.y);
                        const float nh0 = (fg & 1) ? hi_f(w0) : lo_f(w0), nh1 = (fg & 1) ? hi_f(w1) : lo_f(w1);
                        const float ln0 = bf16r(bf16r(nmean - nh0) * rden) - nh0, ln1 = bf16r(bf16r(nmean - nh1) * rden) - nh1;
                        pin(ypart); pin(out);
                        fin_sync<6>(after(after(after(288, sig), ln0), ln1));
                        CK(10, lds32(ypart));
                        const float4 ya = sum4x4(ypart, 512), yb = sum4x4(ypart + 2048, 512);
                        const float4 y = make_float4(ya.x + yb.x, ya.y + yb.y, ya.z + yb.z, ya.w + yb.w);
                        const float y0 = -(((fb & 1) ? y.y : y.x) + __shfl_xor_sync(0xffffffffu, (fb & 1) ? y.x : y.y, 8));
                        const float y1 = -(((fb & 1) ? y.w : y.z) + __shfl_xor_sync(0xffffffffu, (fb & 1) ? y.z : y.w, 8));
                        const uint32_t ov = pack_bf16(fmaf(y0, sig, ln0), fmaf(y1, sig, ln1));
                        asm volatile("{\n.reg .pred p;\n.reg .b16 lo, hi;\nsetp.ne.u32 p, %2, 0;\nmov.b32 {lo, hi}, %1;\n"
                                     "@p st.global.u16 [%0], lo;\n@p st.global.u16 [%0+16], hi;\n"
                                     "@p exit;\n"
                                     "}" :: "l"(out), "r"(ov), "r"((uint32_t)(b == NB - 1)) : "memory");
                        CK(11, 0);
                        if (lane == 0) TS2(13);
                    }
                }
            }
            if (is_f(cta) && ffn) {
                const int ks = (2 * fi + fw) % 12;
                const int far = near_side(sb) ^ 1;
                uint32_t* dst = &g_st.ax[ks >> 2].w[(~b & 1) * 2 + far][(fi / 6) * 128 + (ks & 3) * 32 + fb * 8 + (fg & 1) * 4 + ((fg >> 1) ^ (ks & 1))];
                uint32_t* dst2 = dst + (far ? -1024 : 1024);
                uint32_t part = sb + SM_RED + fw * 2560 + fb * 128 + ((fg + (fb & 2)) & 7) * 16;
                uint32_t psum = sb + SM_RED + fw * 2560 + 4 * 128 + ((fg + 4) & 7) * 16;
                pin(dst); pin(part); pin(psum);
                asm volatile("bar.sync 4, 320;" ::: "memory");
                CK(6, lds32(part));
                const float4 d = sum4x4(part, 640), cs = sum4x4(psum, 640);
                const float2 mo = lds64f(sb + SM_RED + 5120 + fb * 8);
                nmean = mo.x; rden = mo.y;
                const float g0 = fmaf(nmean, cs.x, -d.x), g1 = fmaf(nmean, cs.y, -d.y), ke = rden * -1.4426950408889634f, r2 = rden * rden;
                const float p0 = g0 * fmaf(-nmean, cs.z, d.z) * r2, p1 = g1 * fmaf(-nmean, cs.w, d.w) * r2;
                const uint32_t av = nonzero(pack_bf16(p0 * rcp_approx(1.0f + ex2_approx(g0 * ke)), p1 * rcp_approx(1.0f + ex2_approx(g1 * ke))));
                st_relaxed(dst, av);
                st_relaxed(dst2, av);
                CK(7, 0);
            }
        }
        warm.done(sb + SM_SCRAP);
        if (cta == 0 && tid == (NAUX + NWORK) * 32) { g_work[0] = 0; g_work[32] = 0; g_cnt_z[0] = 0; }
        return;
    }
    if (warp >= NAUX) {
        const int wk = warp - NAUX;
        const uint32_t bar = sb + BAR_KV + wk * 8;
        const uint32_t buf = sb + SM_KV + wk * TILE_BYTES;
        uint64_t pol;
        asm volatile("createpolicy.fractional.L2::evict_first.b64 %0, 1.0;" : "=l"(pol));
        const int nstatic = NWORK * grid;
        constexpr int POOL0 = NUNITS - NPOOL;
        int uk = wk * grid + cta;
        wait_time(t_start + K0_AT_NS + uk * KSWEEP_NS / nstatic);
        request_tile(buf, &p.k, uk, bar, pol);
        uint32_t koff[3], voff[3];
        {
            const int r = lane & 7, hf = (lane >> 3) & 1;
            const int kkey = hf ? 8 + (r ^ 1) : r;
            const int vh = lane >> 4;
            const int vkey = ((r & 1) ? 8 : 0) + (vh ? (r ^ 1) : r);
#pragma unroll
            for (int b = 0; b < 3; b++) {
                const int rk = 3 * kkey + b, rv = 3 * vkey + b;
                koff[b] = buf + rk * 128 + (((lane >> 4) ^ (rk & 7)) << 4);
                voff[b] = buf + rv * 128 + ((hf ^ (rv & 7)) << 4);
            }
        }
        uint32_t phase = 0;
        uint32_t qf[12][2];
        auto load_q = [&](int u) {
            const uint32_t* q = g_early[u / UPB].q[0][j];
#pragma unroll
            for (int i = 0; i < 4; i++) {
                const uint4 a = ld_relaxed_v4(q + i * 32);
                const float2 c = ld_relaxed_f2(q + i * 32 + 4);
                qf[3 * i][0] = a.x; qf[3 * i][1] = a.y; qf[3 * i + 1][0] = a.z; qf[3 * i + 1][1] = a.w;
                qf[3 * i + 2][0] = __float_as_uint(c.x); qf[3 * i + 2][1] = __float_as_uint(c.y);
            }
        };
        load_q(uk);
        int uq[LAG];
        uint32_t sq[LAG];
#pragma unroll
        for (int i = 0; i < LAG; i++) { uq[i] = ~unit_of(uk + (i + 1) * nstatic); sq[i] = 0; }
        uint4 mv = make_uint4(0u, 0u, 0u, 0u);
        float freed = UPB;
        while (true) {
            const int uv = uq[0];
            uint32_t sv = sq[0];
#pragma unroll
            for (int i = 0; i + 1 < LAG; i++) { uq[i] = uq[i + 1]; sq[i] = sq[i + 1]; }
            uq[LAG - 1] = uk;
            if (uk < NUNITS) {
                PH(7);
#pragma unroll 1
                for (int it = 0; it < SPIN_MAX; it++) {
                    uint32_t lo = 0xffffffffu;
#pragma unroll
                    for (int i = 0; i < 12; i++) lo = min(lo, min(qf[i][0], qf[i][1]));
                    if (all(lo != 0)) break;
                    __nanosleep(250);
                    load_q(uk);
                }
                mbar_wait(bar, phase); phase ^= 1;
                PH(0); ARR();
                TSI(0, 16); TSI(1, 18);
                float acc[2][4][4] = {};
#pragma unroll
                for (int ks = 0; ks < 12; ks++) {
#pragma unroll
                    for (int mt = 0; mt < 4; mt++) {
                        uint32_t a[4];
                        ldsm4(a, (koff[ks >> 2] ^ ((ks & 3) << 5)) + mt * 6144);
                        mma16816(acc[ks & 1][mt], a, qf[ks][0], qf[ks][1]);
                    }
                }
                PH(1);
                TSI(0, 17); TSI(1, 19);
                if (uk < nstatic) wait_time(t_start + K1_AT_NS + uk * KSWEEP_NS / nstatic);
                if (uv < NUNITS) request_tile(buf, uv >= 0 ? &p.v : &p.k, uv >= 0 ? uv : ~uv, bar, pol);
                const float sa = sel4(j, acc[0][0][0], acc[0][1][0], acc[0][2][0], acc[0][3][0]) + sel4(j, acc[1][0][0], acc[1][1][0], acc[1][2][0], acc[1][3][0]);
                const float sc = sel4(j, acc[0][0][2], acc[0][1][2], acc[0][2][2], acc[0][3][2]) + sel4(j, acc[1][0][2], acc[1][1][2], acc[1][2][2], acc[1][3][2]);
                const uint32_t raw = pack_bf16(sa, sc);
                const float scale = -0.07216878364870322f;
                const uint32_t sk = pack_bf16(lo_f(raw) * scale, hi_f(raw) * scale);
                sq[LAG - 1] = sk;
                if (uk >= POOL0) st_relaxed(&g_st.score[uk - POOL0][lane], sk ? sk : 0x80008000u);
                int a = (int)(sk << 16), b = (int)(sk & 0xffff0000u);
                a ^= (a >> 31) & 0x7fff0000; b ^= (b >> 31) & 0x7fff0000;
                const int mx = __reduce_max_sync(0xffffffffu, max(a, b));
                if (lane == 0) st_relaxed(&g_early[uk / UPB].umax[uk % UPB], (uint32_t)mx | 1u);
            }
            if (uv < 0) {
                uk = ~uv;
                load_q(uk);
                continue;
            }
            if (uv >= NUNITS) break;
            const int bh = uv / UPB;
#pragma unroll 1
            for (int it = 0; it < SPIN_MAX; it++) {
                if (all((mv.x & mv.y & mv.z & mv.w & 1u) && (uv < POOL0 || sv != 0) && freed == UPB)) break;
                mv = ld_relaxed_v4(&g_early[bh].umax[lane * 4]);
                if (bh >= RING && bh < RED0) freed = __uint_as_float(ld_relaxed_u32(&g_st.oacc[oidx(bh - RING, (lane & 7) * 8)].w));
                if (uv >= POOL0) sv = ld_relaxed_u32(&g_st.score[uv - POOL0][lane]);
            }
            PH(2); CK(8, sv);
            int un = NUNITS, vn = 0;
            draw(un, g_work, uk < NUNITS && lane == 0);
            uint32_t tdraw;
            asm volatile("mov.u32 %0, %%globaltimer_lo;" : "=r"(tdraw));
            draw(vn, g_work + 32, uq[0] >= POOL0 && lane == 0);
            int mx = __reduce_max_sync(0xffffffffu, max(max((int)mv.x, (int)mv.y), max((int)mv.z, (int)mv.w))) & 0xffff0000;
            mx ^= (mx >> 31) & 0x7fff0000;
            const float m = __int_as_float(mx);
            const float l2e = 1.4426950408889634f;
            const uint32_t pp = pack_bf16(exp2f((lo_f(sv) - m) * l2e), exp2f((hi_f(sv) - m) * l2e));
            uint32_t pb[8];
#pragma unroll
            for (int t = 0; t < 4; t++) {
                pb[2 * t] = __shfl_sync(0xffffffffu, pp, 8 * j + t);
                pb[2 * t + 1] = __shfl_sync(0xffffffffu, pp, 8 * j + 4 + t);
            }
            float lacc[4] = {};
            const uint32_t ones[4] = {0x3f803f80u, 0x3f803f80u, 0x3f803f80u, 0x3f803f80u};
#pragma unroll
            for (int t = 0; t < 4; t++) mma16816(lacc, ones, pb[2 * t], pb[2 * t + 1]);
            if (uv < nstatic) {
                asm volatile("bar.sync 2, %0;" :: "n"((NWORK + 2) * 32) : "memory");
                TSW(3);
            }
            const int grp = 16 * j + 4 * (g & 1) + (g >> 1);
            uint32_t mode = (bh >= RED0) + (bh >= NBH - 4);
            float tag = mode ? 1.f : (float)(bh + 1), tag2 = fmaf(__uint_as_float(voff[0]), 0.f, tag);
            void* dst = mode == 0 ? (void*)&g_ring[bh % RING][uv % UPB][grp] :
                        mode == 1 ? (void*)&g_st.oacc[oidx(bh, grp)] : (void*)&g_st.ox[0].w[uv % OREP * 2 + (~(near_side(sb) ^ uv % OREP) & 1)][oidx(bh & 3, grp) * 4];
            if (mode == 2 && lane < 2) red_f2(reinterpret_cast<float*>(&g_st.lx.w[lane][(bh & 3) * 256]), lacc[0], 1.f);
            CK(10, __float_as_uint(lacc[0]));
            un = __shfl_sync(0xffffffffu, un, 0) + (LAG + 1) * nstatic;
            un = unit_of(un);
            vn = __shfl_sync(0xffffffffu, vn, 0);
            if (uq[0] >= POOL0) uq[0] = unit_of(POOL0 + vn);
            if (vn == FW_TICKET && lane == 0) st_relaxed(g_st.fw_time, tdraw | 1u);
            if (uq[0] < NUNITS && un >= NUNITS) {
                mv = ld_relaxed_v4(&g_early[uq[0] / UPB].umax[lane * 4]);
                if (uq[0] < RED0 * UPB) freed = 0.f;
                if (uq[0] >= POOL0) sq[0] = ld_relaxed_u32(&g_st.score[uq[0] - POOL0][lane]);
            }
            pin(dst); pin(mode); pin(tag); pin(tag2); pin(voff[0]); pin(voff[1]); pin(voff[2]);
            PH(3); CK(9, vn);
            mbar_wait(bar, phase); phase ^= 1;
            PH(4); ARR(); CK(12, lds32(buf));
            float acc[12][4] = {};
#pragma unroll
            for (int t = 0; t < 4; t++) {
#pragma unroll
                for (int mt = 0; mt < 12; mt++) {
                    uint32_t a[4];
                    ldsm4t(a, (voff[mt >> 2] ^ ((mt & 3) << 5)) + t * 6144);
                    mma16816(acc[mt], a, pb[2 * t], pb[2 * t + 1]);
                }
            }
            PH(5);
            if (lane == 0) PROG(un);
            if (un < NUNITS || uq[0] < NUNITS) request_tile(buf, un < NUNITS ? &p.k : &p.v, un < NUNITS ? un : uq[0], bar, pol);
            if (un < NUNITS || uq[0] < NUNITS) CK(11, 0);
            float o[6];
#pragma unroll
            for (int e = 0; e < 6; e++) {
                const int q = e % 3, c = (e / 3) * 2;
                o[e] = sel4(j, acc[q][c], acc[3 + q][c], acc[6 + q][c], acc[9 + q][c]);
            }
            put_groups(dst, mode, o, tag, tag2);
            CK(13, 0);
            if (un < NUNITS) load_q(un);
            if (lane == 0) red_f2(&g_st.lsum[bh][0].x, lacc[0], 1.f);
            PH(6);
            if (uq[0] >= NUNITS && un >= NUNITS) break;
            uk = un;
            if (uq[0] < NUNITS && un < NUNITS) {
                const int nb = uq[0] / UPB;
                mv = ld_relaxed_v4(&g_early[nb].umax[lane * 4]);
                freed = nb >= RING && nb < RED0 ? __uint_as_float(ld_relaxed_u32(&g_st.oacc[oidx(nb - RING, (lane & 7) * 8)].w)) : UPB;
                if (uq[0] >= POOL0) sq[0] = ld_relaxed_u32(&g_st.score[uq[0] - POOL0][lane]);
            }
        }
        TSW(4 + wk);
        return;
    }

    __nv_bfloat16* xs = reinterpret_cast<__nv_bfloat16*>(smem + SM_X);
    float* red = reinterpret_cast<float*>(smem + SM_RED);
    const int frow = (lane & 7) + ((lane >> 4) << 3), fcol = (lane >> 3) & 1;
    const uint32_t f64b = sb + (frow * 4 + (fcol ^ ((frow >> 1) & 3))) * 16;
    if (cta < NQ_CTAS) {
        TS(26);
        if (warp >= 4) {
            uint2 xr[5];
#pragma unroll
            for (int i = 0; i < 5; i++) xr[i] = *reinterpret_cast<const uint2*>(x + (warp - 4) * DM + i * 128 + lane * 4);
            float v[20];
#pragma unroll
            for (int i = 0; i < 5; i++) {
                v[4 * i] = lo_f(xr[i].x); v[4 * i + 1] = hi_f(xr[i].x); v[4 * i + 2] = lo_f(xr[i].y); v[4 * i + 3] = hi_f(xr[i].y);
            }
            layernorm20(v);
#pragma unroll
            for (int i = 0; i < 5; i++)
                *reinterpret_cast<uint2*>(xs + (warp - 4) * XPITCH + i * 128 + lane * 4) =
                    make_uint2(pack_bf16(v[4 * i], v[4 * i + 1]), pack_bf16(v[4 * i + 2], v[4 * i + 3]));
        }
        aux_sync();
        TS(27);
        mbar_wait(sb + BAR_WQ + (warp >> 1) * 8, 0);
        TS(1);
        const uint32_t xfrag = sb + SM_X + ((g & 3) * XPITCH + 2 * j) * 2;
        float acc[3][4] = {};
#pragma unroll
        for (int s = 0; s < 5; s++) {
            const int ks = warp * 5 + s;
            const uint32_t b0 = lds32(xfrag + ks * 32), b1 = lds32(xfrag + ks * 32 + 16);
            const int row = ks * 16 + frow;
#pragma unroll
            for (int mt = 0; mt < 3; mt++) {
                uint32_t a[4];
                ldsm4t(a, sb + SM_W + (row * 6 + 2 * mt + fcol) * 16);
                mma16816(acc[mt], a, b0, b1);
            }
        }
        if (j < 2) {
#pragma unroll
            for (int mt = 0; mt < 3; mt++) {
                *reinterpret_cast<float2*>(red + warp * 216 + mt * 72 + g * 4 + 2 * j) = make_float2(acc[mt][0], acc[mt][1]);
                *reinterpret_cast<float2*>(red + warp * 216 + mt * 72 + 36 + g * 4 + 2 * j) = make_float2(acc[mt][2], acc[mt][3]);
            }
        }
        aux_sync();
        if (warp < 4) {
            const float* src = red + min(g, 5) * 36 + warp * 8 + j;
            float s0 = 0.f, s1 = 0.f;
#pragma unroll
            for (int w = 0; w < 8; w++) { s0 += src[w * 216]; s1 += src[w * 216 + 4]; }
            st_relaxed(&g_early[j * NH + (cta >> 2)].q[cta & 3][warp][g], pack_neg(s0, s1));
        }
        TS(28);
    }
    fin_sync<3>();
    mbar_wait(sb + BAR_WO, 0);
    TS(7);
    uint32_t part = sb + SM_RED + (warp * 32 + 8 * j + g) * 4;

#pragma unroll 1
    for (int b = 0; b < NB; b++) {
        if (cta >= NE_CTAS) {
            uint32_t a[6][2][4];
#pragma unroll
            for (int s = 0; s < 6; s++) {
#pragma unroll
                for (int mt = 0; mt < 2; mt++) ldsm4t(a[s][mt], (f64b ^ (mt * 32)) + SM_A + (warp * 6 + s) * 1024);
            }
            const int bh = b * NH + 28 + (warp >> 1);
            const int side = near_side(sb) ^ 1;
            const void* osrc[OREP];
#pragma unroll
            for (int c = 0; c < OREP; c++)
                osrc[c] = b == NB - 1 ? (const void*)&g_st.ox[c >> 1].w[side ^ (c & 1) * 3][oidx(bh & 3, (warp & 1) * 32 + lane) * 4] : &g_st.oacc[oidx(bh, (warp & 1) * 32 + lane)];
            const void* lsrc = b == NB - 1 ? (const void*)&g_st.lx.w[side][(bh & 3) * 256] : g_st.lsum[bh];
            wait_row_o(scr, bh, 1);
            const float rl = rcp_approx(wait_sum(lsrc, UPB)) * (b == NB - 1 ? 1.f : 1.f / OREP), full = b == NB - 1 ? UPB : UPB * OREP;
            float4 ov;
            float px, py, pz;
            Warm warm;
#pragma unroll 1
            for (int it = 0; it < SPIN_MAX; it++) {
                wait_slot<PH_O>();
                float4 oc[OREP];
#pragma unroll
                for (int c = 0; c < OREP; c++) oc[c] = ld_relaxed_f4(osrc[c]);
                warm();
                ov = oc[0];
#pragma unroll
                for (int c = 1; c < OREP; c++) { ov.x += oc[c].x; ov.y += oc[c].y; ov.z += oc[c].z; ov.w += oc[c].w; }
                ov.x *= rl; ov.y *= rl; ov.z *= rl;
                px = __shfl_xor_sync(0xffffffffu, ov.x, 4); py = __shfl_xor_sync(0xffffffffu, ov.y, 4); pz = __shfl_xor_sync(0xffffffffu, ov.z, 4);
                if (all(ov.w == full)) break;
            }
            CK(0, __float_as_uint(ov.x));
            if (ov.x != 1.2345f && warp == 7) TSW(14);
            const uint32_t w[3] = {pack_bf16(ov.x, px), pack_bf16(ov.y, py), pack_bf16(ov.z, pz)};
            float acc[2][2][4] = {};
#pragma unroll
            for (int s = 0; s < 6; s++) {
                const uint32_t b0 = __shfl_sync(0xffffffffu, w[s % 3], (s / 3) * 16 + j);
                const uint32_t b1 = __shfl_sync(0xffffffffu, w[s % 3], (s / 3) * 16 + 8 + j);
#pragma unroll
                for (int mt = 0; mt < 2; mt++) mma16816(acc[mt][s & 1], a[s][mt], b0, b1);
            }
            sts32f(part, sel4(j, acc[0][0][0] + acc[0][1][0], acc[0][0][2] + acc[0][1][2], acc[1][0][0] + acc[1][1][0], acc[1][0][2] + acc[1][1][2]));
            CK(1, 0);
            fin_arrive<4>();
            warm.done(sb + SM_SCRAP);
            fin_sync<5>();
            if (cta < NE_CTAS + 4 && tid < 64) reinterpret_cast<uint4*>(&g_early[b * NH + 28 + cta - NE_CTAS])[tid] = make_uint4(0u, 0u, 0u, 0u);
        } else {
            const int bh = b * NH + (cta >> 2);
            if (warp == 0) wait_row_o(scr, bh, UPB);
            aux_sync();
            if (warp < 5) {
                uint32_t ob[12][2];
                load_o<4>(ob, scr, bh, 0, j);
                float acc[2][2][4] = {};
#pragma unroll
                for (int ks = 0; ks < 12; ks++) {
#pragma unroll
                    for (int mt = 0; mt < 2; mt++) {
                        uint32_t a[4];
                        ldsm4t(a, (f64b ^ (mt * 32)) + SM_A + warp * 12288 + ks * 1024);
                        mma16816(acc[mt][ks & 1], a, ob[ks][0], ob[ks][1]);
                    }
                }
                red_f2(&g_st.attn[b][(cta & 3) * 160 + warp * 32 + 8 * j + g].x,
                       sel4(j, acc[0][0][0] + acc[0][1][0], acc[0][0][2] + acc[0][1][2], acc[1][0][0] + acc[1][1][0], acc[1][0][2] + acc[1][1][2]), 1.f);
                TS(8);
            } else if (warp > 5 && (cta & 3) == 0) {
                reinterpret_cast<uint4*>(&g_early[bh])[tid - 192] = make_uint4(0u, 0u, 0u, 0u);
            }
        }
        if (b < NB - 2) continue;

        if (is_f(cta)) {
            uint32_t ga[10][2][4];
            uint4 hv[5];
            const uint32_t hfrag = sb + SM_X + min(g, 4) * HPITCH + ((warp >> 1) * 80 + 4 * j) * 4;
            if (b == NB - 1) mbar_wait(sb + BAR_FW + warp * 8, 0);
            if (warp == 7) TSW(10);
            CK(12, lds32(sb + SM_W));
#pragma unroll
            for (int s = 0; s < 10; s++) {
#pragma unroll
                for (int mt = 0; mt < 2; mt++) ldsm4t(ga[s][mt], (f64b ^ (mt * 32)) + SM_W + (warp * 10 + s) * 1024);
            }
            const uint32_t gpart = sb + SM_RED + (warp >> 1) * 640 + j * 256 + ((g + 2 * j) & 7) * 16 + (warp & 1) * 8;
            mbar_wait(sb + BAR_H, b & 1);
#pragma unroll
            for (int s = 0; s < 5; s++) hv[s] = lds128(hfrag + s * 64);
            CK(4, hv[0].x);
            float acc[2][2][4] = {};
#pragma unroll
            for (int s = 0; s < 10; s++) {
#pragma unroll
                for (int mt = 0; mt < 2; mt++)
                    mma16816(acc[mt][s & 1], ga[s][mt], (s & 1) ? hv[s >> 1].z : hv[s >> 1].x, (s & 1) ? hv[s >> 1].w : hv[s >> 1].y);
            }
#pragma unroll
            for (int mt = 0; mt < 2; mt++) {
                if (j < 3) sts64f(gpart + mt * 2560, acc[mt][0][0] + acc[mt][1][0], acc[mt][0][2] + acc[mt][1][2]);
                if (j < 2) sts64f(gpart + mt * 2560 + 128, acc[mt][0][1] + acc[mt][1][1], acc[mt][0][3] + acc[mt][1][3]);
            }
            CK(5, 0);
            asm volatile("bar.arrive 4, 320;" ::: "memory");
        } else if (is_g(cta)) {
            const uint32_t* asrc = &g_st.ax[0].w[(~b & 1) * 2 + near_side(sb)][warp * 128 + ((g >> 2) * 2 + (j >> 1)) * 32 + (g & 3) * 8 + (j & 1) * 4];
            const uint32_t ypart = sb + SM_RED2 + warp * 512 + j * 128 + ((g + 2 * j) & 7) * 16;
            uint32_t wb[12][4];
            uint4 va[3] = {};
            uint32_t lo[3] = {};
            auto ask = [&]() {
#pragma unroll
                for (int i = 0; i < 3; i++) ld_relaxed_v4_if(va[i], asrc + i * 4096, lo[i] == 0);
            };
            auto complete = [&]() {
#pragma unroll
                for (int i = 0; i < 3; i++) lo[i] = min(min(va[i].x, va[i].y), min(va[i].z, va[i].w));
                return all(min(lo[0], min(lo[1], lo[2])) != 0);
            };
            const int jj = (lane & 7) >> 1, q = jj >> 1, hi = lane >> 4;
            const uint32_t wsrc = sb + SM_W + warp * 6144 + q * 512 + ((hi ^ q) * 4 + (jj & 1) * 2 + (lane & 1)) * 32 + ((fcol ^ hi ^ q) << 4);
            mbar_wait(sb + BAR_H, b & 1);
            if (b == NB - 1) mbar_wait(sb + BAR_FW + warp * 8, 0);
            if (warp == 7) TSW(11);
            CK(13, lds32(sb + SM_W));
            ask();
#pragma unroll
            for (int s = 0; s < 12; s++) ldsm4t(wb[s], wsrc + (s >> 2) * 2048 + (s & 1) * 1024 + (s & 2) * 128);
            Warm warm;
            if (!complete()) {
#pragma unroll 1
                for (int it = 0; it < SPIN_MAX; it++) {
                    ask();
                    warm();
                    if (complete()) break;
                }
            }
            CK(8, va[0].x);
            if (va[0].x != 0x12345 && warp == 7) TSW(15);
            float acc[6][4] = {};
#pragma unroll
            for (int s = 0; s < 12; s++) {
                const uint4 v = va[s >> 2];
                mma16816(acc[s % 6], wb[s], (s & 2) ? v.z : v.x, (s & 2) ? v.w : v.y);
            }
            float y[4];
#pragma unroll
            for (int e = 0; e < 4; e++) y[e] = j < 2 ? (acc[0][e] + acc[2][e]) + acc[4][e] : (acc[1][e] + acc[3][e]) + acc[5][e];
            sts128f(ypart, y[0], y[1], y[2], y[3]);
            CK(9, 0);
            fin_arrive<6>();
            warm.done(sb + SM_SCRAP);
        }
    }
}

typedef CUresult (*EncodeFn)(CUtensorMap*, CUtensorMapDataType, cuuint32_t, void*, const cuuint64_t*, const cuuint64_t*,
                             const cuuint32_t*, const cuuint32_t*, CUtensorMapInterleave, CUtensorMapSwizzle,
                             CUtensorMapL2promotion, CUtensorMapFloatOOBfill);

CUtensorMap make_map(EncodeFn enc, void* ptr, uint64_t cols, uint64_t rows, uint32_t bcols, uint32_t brows,
                     CUtensorMapSwizzle sw, CUtensorMapL2promotion promo) {
    CUtensorMap m;
    const cuuint64_t dims[2] = {cols, rows};
    const cuuint64_t strides[1] = {cols * 2};
    const cuuint32_t box[2] = {bcols, brows};
    const cuuint32_t es[2] = {1, 1};
    enc(&m, CU_TENSOR_MAP_DATA_TYPE_BFLOAT16, 2, ptr, dims, strides, box, es, CU_TENSOR_MAP_INTERLEAVE_NONE, sw, promo,
        CU_TENSOR_MAP_FLOAT_OOB_FILL_NONE);
    return m;
}

}

extern "C" void kernel_launch(void* const* d_in, const int* in_sizes, int n_in, void* d_out, int out_size) {
    (void)in_sizes; (void)n_in; (void)out_size;
    static EncodeFn enc = nullptr;
    static int sms = 0;
    static Scratch* scr = nullptr;
    if (!enc) {
        cudaDriverEntryPointQueryResult qr;
        cudaGetDriverEntryPoint("cuTensorMapEncodeTiled", (void**)&enc, cudaEnableDefault, &qr);
        void* raw = nullptr;
        cudaGetSymbolAddress(&raw, g_raw);
        scr = reinterpret_cast<Scratch*>((reinterpret_cast<uintptr_t>(raw) + PAGE - 1) & ~(uintptr_t)(PAGE - 1));
        int dev = 0;
        cudaGetDevice(&dev);
        cudaDeviceGetAttribute(&sms, cudaDevAttrMultiProcessorCount, dev);
        cudaFuncSetAttribute(fused_decode_kernel, cudaFuncAttributeMaxDynamicSharedMemorySize, SM_TOTAL);
    }
    if (sms < NCTAS) return;
    const CUtensorMapL2promotion WPROMO = CU_TENSOR_MAP_L2_PROMOTION_L2_128B;
    Params p;
    p.k = make_map(enc, d_in[1], 64, (uint64_t)NBH * SK * 3, 64, TILE_ROWS, CU_TENSOR_MAP_SWIZZLE_128B, CU_TENSOR_MAP_L2_PROMOTION_NONE);
    p.v = make_map(enc, d_in[2], 64, (uint64_t)NBH * SK * 3, 64, TILE_ROWS, CU_TENSOR_MAP_SWIZZLE_128B, CU_TENSOR_MAP_L2_PROMOTION_NONE);
    p.wq = make_map(enc, d_in[3], NH * DH, DM, 48, 160, CU_TENSOR_MAP_SWIZZLE_NONE, WPROMO);
    p.wo = make_map(enc, d_in[4], DM, NH * DH, 32, DH, CU_TENSOR_MAP_SWIZZLE_64B, WPROMO);
    p.wg = make_map(enc, d_in[7], FF, DM, 32, 160, CU_TENSOR_MAP_SWIZZLE_64B, WPROMO);
    p.wu = make_map(enc, d_in[8], FF, DM, 32, 160, CU_TENSOR_MAP_SWIZZLE_64B, WPROMO);
    {
        const cuuint64_t dims[4] = {DM, 2, 8, FF / 16}, strides[3] = {8 * DM * 2, DM * 2, 16 * DM * 2};
        const cuuint32_t box[4] = {16, 2, 8, 12}, es[4] = {1, 1, 1, 1};
        enc(&p.wd, CU_TENSOR_MAP_DATA_TYPE_BFLOAT16, 4, d_in[9], dims, strides, box, es, CU_TENSOR_MAP_INTERLEAVE_NONE,
            CU_TENSOR_MAP_SWIZZLE_32B, WPROMO, CU_TENSOR_MAP_FLOAT_OOB_FILL_NONE);
    }
    fused_decode_kernel<<<NCTAS, NTHREADS, SM_TOTAL, cudaStreamPerThread>>>(
        scr, (const __nv_bfloat16*)d_in[0], (const __nv_bfloat16*)d_in[6], (__nv_bfloat16*)d_out, (const __nv_bfloat16*)d_in[3], p);
}
```

```cpp
#include <cuda_runtime.h>
#include <cuda_bf16.h>
#include <cuda.h>
#include <stdint.h>

namespace {

constexpr int NB = 4, NH = 32, SK = 8192, DH = 192, DM = 640, FF = 1536;
constexpr int NBH = NB * NH;
constexpr int TILE = 64;
constexpr int UPB = SK / TILE;
constexpr int NUNITS = NBH * UPB;
constexpr int TILE_BYTES = TILE * DH * 2;
constexpr int TILE_ROWS = TILE * 3;
constexpr int NCTAS = 132;
constexpr int NQ_CTAS = 128;
constexpr int NE_CTAS = 112;
__host__ __device__ constexpr bool is_f(int cta) { return cta < NE_CTAS && cta % 14 < 11 && !(cta & 1); }
__host__ __device__ constexpr bool is_g(int cta) { return cta < NE_CTAS && cta % 14 < 11 && (cta & 1); }
__host__ __device__ constexpr int ffn_slice(int cta) { return cta / 14 * ((cta & 1) ? 5 : 6) + cta % 14 / 2; }

#define NWORK 2
#define LAG 3
#define NPOOL 896
#define RED0 118
#define RING 12
#define OREP 2
#define WQ_LINES 128
#define K0_AT_NS 900
#define WO_AT_NS (K0_AT_NS + 2000)
#define K1_AT_NS (K0_AT_NS + 4400)
#define WO_STEP_NS 75
#define CLEAR_AT_NS 7000
constexpr int KSWEEP_NS = 2000;
#define FW_TICKET (NPOOL + 32)
#define FW_AT_NS 2090
#define FW_GAP 280
#define FW_MID 2100
#define FW_GAP2 200
#define HGATE_NS 700
#define SLOT_TICKS 9
#define SLOT_OPEN 3
#define PH_O 0
#define PH_H 8
#define PH_M 2
#define NPROBE 24
#define MIX_R 6
#define MIX_FROM 1
#define MIX_ROWS 3
constexpr int MIX = MIX_ROWS * UPB, MIX1 = (NBH - 4) * UPB, MIX0 = MIX1 - (MIX1 - MIX_FROM * NWORK * NCTAS) / MIX * MIX;
static_assert((MIX1 - (NUNITS - NPOOL)) % MIX == 0, "the pool starts with a group of rows");
__device__ __forceinline__ int unit_of(int t) {
    const unsigned r = (unsigned)(t - MIX0) % MIX, e = t - MIX1;
    if (e < 4 * UPB) return MIX1 + (e & 256) + (e & 3) * 64 + (e & 255) / 4;
    return t < MIX0 || t >= MIX1 ? t : t - r + r % MIX_R * (MIX / MIX_R) + r / MIX_R;
}
static_assert(FW_TICKET < NPOOL + NWORK * NCTAS, "every worker draws one ticket beyond the pool");
constexpr int NAUX = 8;
constexpr int NTHREADS = (NAUX + NWORK + 2) * 32;
constexpr int SPIN_MAX = 1 << 22;

constexpr int SM_KV = 0;
constexpr int SM_A = SM_KV + NWORK * TILE_BYTES;
constexpr int SM_W = SM_A + 61440;
constexpr int SM_X = SM_W + 81920;
constexpr int XPITCH = 648;
constexpr int HPITCH = 1344;
constexpr int SM_RED = SM_X + 5 * HPITCH + 64;
constexpr int SM_RED2 = SM_RED + 8 * 48 * 4 * 4;
constexpr int SM_MISC = SM_RED2 + 4096;
constexpr int BAR_WQ = SM_MISC, SM_SCRAP = SM_MISC + 32, BAR_WO = SM_MISC + 40, SM_SIDE = SM_MISC + 48, BAR_H = SM_MISC + 56, BAR_FW = SM_MISC + 64;
constexpr int BAR_KV = BAR_FW + 64;
constexpr int SM_TOTAL = BAR_KV + NWORK * 8;
static_assert(SM_W % 1024 == 0 && NB * XPITCH * 2 <= 4 * HPITCH && SM_RED % 128 == 0, "smem layout");

struct Params {
    CUtensorMap k, v;
    CUtensorMap wq;
    CUtensorMap wo;
    CUtensorMap wg, wu;
    CUtensorMap wd;
};

struct Early {
    uint32_t q[4][4][8];
    uint32_t umax[UPB];
};
struct Twin { uint32_t w[4][1024]; };
constexpr int PROBE = 1024 - 32;
#define LSTRIDE 16
struct State {
    Twin ax[3];
    Twin hx;
    Twin ox[(OREP + 1) / 2];
    Twin lx;
    float4 oacc[NBH * 64];
    float2 attn[NB][DM];
    uint32_t fw_time[32];
    float2 lsum[NBH][LSTRIDE];
    uint32_t score[NPOOL][32];
};
__host__ __device__ constexpr int oidx(int row, int grp) {
    return (row >> 2) * 256 + ((row & 1) * 2 + (grp >> 5)) * 64 + (row & 2) * 16 + (grp & 31);
}
constexpr int STATE_V4 = ((sizeof(State) / 32 + NQ_CTAS - 1) / NQ_CTAS) * 2;
static_assert(sizeof(State) % 32 == 0, "State is cleared in whole sectors");
static_assert(sizeof(Early) == 64 * 16, "an Early entry is cleared by 64 threads");
struct Scratch {
    State st;
    unsigned work[64];
    unsigned cnt_z[32];
    Early early[NBH];
    alignas(4096) float4 ring[RING][UPB][64];
};
constexpr size_t PAGE = 2u << 20;
static_assert(sizeof(Scratch) <= PAGE, "scratch must fit one page");
__device__ __align__(128) unsigned char g_raw[2 * PAGE];
#define g_early scr->early
#define g_st scr->st
#define g_ring scr->ring
#define g_cnt_z scr->cnt_z
#define g_work scr->work
#define ALL_LOADERS 0
#define TS(i)
#define TSW(i)
#define TS2(i)
#define TSI(n, i)
#define PH(i)
#define CK(i, dep)
#define ARR()
#define PROG(u)

__device__ __forceinline__ uint32_t s2u(const void* p) { return (uint32_t)__cvta_generic_to_shared(p); }
__device__ __forceinline__ void mbar_init(uint32_t bar, int cnt) {
    asm volatile("mbarrier.init.shared::cta.b64 [%0], %1;" :: "r"(bar), "r"(cnt) : "memory");
}
__device__ __forceinline__ void mbar_wait(uint32_t bar, uint32_t parity) {
    asm volatile("{\n.reg .pred p;\n.reg .u32 n;\nmov.u32 n, 0;\nWAIT_LOOP:\n"
                 "mbarrier.try_wait.parity.shared::cta.b64 p, [%0], %1;\n"
                 "@p bra WAIT_DONE;\nadd.u32 n, n, 1;\nsetp.lt.u32 p, n, %2;\n@p bra WAIT_LOOP;\nWAIT_DONE:\n}"
                 :: "r"(bar), "r"(parity), "n"(SPIN_MAX) : "memory");
}
__device__ __forceinline__ void request_tile(uint32_t dst, const CUtensorMap* tm, int unit, uint32_t bar, uint64_t pol) {
    asm volatile("{\n.reg .pred p;\nelect.sync _|p, 0xffffffff;\n"
                 "@p mbarrier.arrive.expect_tx.shared::cta.b64 _, [%2], %6;\n"
                 "@p cp.async.bulk.tensor.2d.shared::cluster.global.mbarrier::complete_tx::bytes.L2::cache_hint "
                 "[%0], [%1, {%3, %4}], [%2], %5;\n}"
                 :: "r"(dst), "l"(tm), "r"(bar), "r"(0), "r"(unit * TILE_ROWS), "l"(pol), "n"(TILE_BYTES) : "memory");
}
__device__ __forceinline__ void put_groups(void* dst, int mode, const float (&o)[6], float tag, float tag2) {
    asm volatile("{\n.reg .pred s, t;\n.reg .b128 u, v;\n.reg .b64 a, b;\n"
                 "setp.eq.s32 s, %1, 0;\nsetp.ne.s32 t, %1, 2;\nxor.b64 a, %0, 4096;\n"
                 "@t bra.uni SINGLE;\n"
                 "red.relaxed.gpu.global.add.v4.f32 [a], {%2,%3,%4,%8};\n"
                 "red.relaxed.gpu.global.add.v4.f32 [a+128], {%5,%6,%7,%9};\n"
                 "SINGLE:\n"
                 "@s bra.uni STORE;\n"
                 "red.relaxed.gpu.global.add.v4.f32 [%0], {%2,%3,%4,%8};\n"
                 "red.relaxed.gpu.global.add.v4.f32 [%0+128], {%5,%6,%7,%9};\n"
                 "STORE:\n"
                 "mov.b64 a, {%2, %3};\nmov.b64 b, {%4, %8};\nmov.b128 u, {a, b};\n"
                 "mov.b64 a, {%5, %6};\nmov.b64 b, {%7, %9};\nmov.b128 v, {a, b};\n"
                 "@s st.relaxed.gpu.global.b128 [%0], u;\n@s st.relaxed.gpu.global.b128 [%0+128], v;\n}"
                 :: "l"(dst), "r"(mode), "f"(o[0]), "f"(o[1]), "f"(o[2]), "f"(o[3]), "f"(o[4]), "f"(o[5]), "f"(tag), "f"(tag2) : "memory");
}
__device__ __forceinline__ void request_box(uint32_t dst, const CUtensorMap* tm, int col, int row, uint32_t bar, uint32_t bytes) {
    asm volatile("{\n.reg .pred p, q;\nelect.sync _|p, 0xffffffff;\nsetp.ne.and.u32 q, %5, 0, p;\n"
                 "@q mbarrier.arrive.expect_tx.shared::cta.b64 _, [%2], %5;\n"
                 "@p cp.async.bulk.tensor.2d.shared::cluster.global.mbarrier::complete_tx::bytes [%0], [%1, {%3, %4}], [%2];\n}"
                 :: "r"(dst), "l"(tm), "r"(bar), "r"(col), "r"(row), "r"(bytes) : "memory");
}
__device__ __forceinline__ uint32_t lds32(uint32_t addr) {
    uint32_t v;
    asm volatile("ld.shared.u32 %0, [%1];" : "=r"(v) : "r"(addr) : "memory");
    return v;
}
__device__ __forceinline__ void ldsm4(uint32_t (&r)[4], uint32_t addr) {
    asm volatile("ldmatrix.sync.aligned.m8n8.x4.shared.b16 {%0,%1,%2,%3}, [%4];"
                 : "=r"(r[0]), "=r"(r[1]), "=r"(r[2]), "=r"(r[3]) : "r"(addr) : "memory");
}
__device__ __forceinline__ void ldsm4t(uint32_t (&r)[4], uint32_t addr) {
    asm volatile("ldmatrix.sync.aligned.m8n8.x4.trans.shared.b16 {%0,%1,%2,%3}, [%4];"
                 : "=r"(r[0]), "=r"(r[1]), "=r"(r[2]), "=r"(r[3]) : "r"(addr) : "memory");
}
__device__ __forceinline__ void mma16816(float (&c)[4], const uint32_t (&a)[4], uint32_t b0, uint32_t b1) {
    asm volatile("mma.sync.aligned.m16n8k16.row.col.f32.bf16.bf16.f32 {%0,%1,%2,%3}, {%4,%5,%6,%7}, {%8,%9}, {%0,%1,%2,%3};"
                 : "+f"(c[0]), "+f"(c[1]), "+f"(c[2]), "+f"(c[3])
                 : "r"(a[0]), "r"(a[1]), "r"(a[2]), "r"(a[3]), "r"(b0), "r"(b1));
}
struct Warm {
    float c[4] = {};
    __device__ __forceinline__ void operator()() {
        asm volatile("mma.sync.aligned.m16n8k8.row.col.f32.bf16.bf16.f32 {%0,%1,%2,%3}, {%4,%4}, {%4}, {%0,%1,%2,%3};"
                     : "+f"(c[0]), "+f"(c[1]), "+f"(c[2]), "+f"(c[3]) : "r"(0));
    }
    __device__ __forceinline__ void done(uint32_t scrap) {
        asm volatile("{\n.reg .pred p;\nsetp.gt.f32 p, %1, 0f3f800000;\n@p st.shared.f32 [%0], %1;\n}" :: "r"(scrap), "f"(c[0]) : "memory");
    }
};
__device__ __forceinline__ uint4 ld_relaxed_v4(const void* p) {
    uint4 v;
    asm volatile("ld.relaxed.gpu.global.v4.u32 {%0,%1,%2,%3}, [%4];" : "=r"(v.x), "=r"(v.y), "=r"(v.z), "=r"(v.w) : "l"(p) : "memory");
    return v;
}
__device__ __forceinline__ float4 ld_relaxed_f4(const void* p) {
    float4 v;
    asm volatile("ld.relaxed.gpu.global.v4.f32 {%0,%1,%2,%3}, [%4];" : "=f"(v.x), "=f"(v.y), "=f"(v.z), "=f"(v.w) : "l"(p) : "memory");
    return v;
}
__device__ __forceinline__ float2 ld_relaxed_f2(const void* p) {
    float2 v;
    asm volatile("ld.relaxed.gpu.global.v2.f32 {%0,%1}, [%2];" : "=f"(v.x), "=f"(v.y) : "l"(p) : "memory");
    return v;
}
__device__ __forceinline__ float4 ld_relaxed_b128(const void* p) {
    float4 v;
    asm volatile("{\n.reg .b128 t;\n.reg .b64 a, b;\nld.relaxed.gpu.global.b128 t, [%4];\nmov.b128 {a, b}, t;\n"
                 "mov.b64 {%0, %1}, a;\nmov.b64 {%2, %3}, b;\n}" : "=f"(v.x), "=f"(v.y), "=f"(v.z), "=f"(v.w) : "l"(p) : "memory");
    return v;
}
__device__ __forceinline__ void st_relaxed_b128(void* p, float x, float y, float z, float w) {
    asm volatile("{\n.reg .b128 t;\n.reg .b64 a, b;\nmov.b64 a, {%1, %2};\nmov.b64 b, {%3, %4};\nmov.b128 t, {a, b};\n"
                 "st.relaxed.gpu.global.b128 [%0], t;\n}" :: "l"(p), "f"(x), "f"(y), "f"(z), "f"(w) : "memory");
}
__device__ __forceinline__ unsigned ld_acquire(const unsigned* p) {
    unsigned v;
    asm volatile("ld.acquire.gpu.global.u32 %0, [%1];" : "=r"(v) : "l"(p) : "memory");
    return v;
}
__device__ __forceinline__ void st_relaxed(void* p, uint32_t v) {
    asm volatile("st.relaxed.gpu.global.u32 [%0], %1;" :: "l"(p), "r"(v) : "memory");
}
__device__ __forceinline__ void red_f2(float* p, float a, float b) {
    asm volatile("red.relaxed.gpu.global.add.v2.f32 [%0], {%1,%2};" :: "l"(p), "f"(a), "f"(b) : "memory");
}
__device__ __forceinline__ void draw(int& ticket, unsigned* ctr, bool pred) {
    asm volatile("{\n.reg .pred p;\nsetp.ne.u32 p, %2, 0;\n@p atom.relaxed.gpu.global.inc.u32 %0, [%1], 0x7fffffff;\n}"
                 : "+r"(ticket) : "l"(ctr), "r"((uint32_t)pred) : "memory");
}
__device__ __forceinline__ void red_release(unsigned* p) {
    asm volatile("red.release.gpu.global.add.u32 [%0], 1;" :: "l"(p) : "memory");
}
__device__ __forceinline__ uint32_t ld_relaxed_u32(const void* p) {
    uint32_t v;
    asm volatile("ld.relaxed.gpu.global.u32 %0, [%1];" : "=r"(v) : "l"(p) : "memory");
    return v;
}
__device__ __forceinline__ float rcp_approx(float v) {
    float r;
    asm("rcp.approx.ftz.f32 %0, %1;" : "=f"(r) : "f"(v));
    return r;
}
__device__ __forceinline__ float ex2_approx(float v) {
    float e;
    asm("ex2.approx.ftz.f32 %0, %1;" : "=f"(e) : "f"(v));
    return e;
}
__device__ __forceinline__ float sigmoid_approx(float v) { return rcp_approx(1.0f + ex2_approx(v * -1.4426950408889634f)); }
__device__ __forceinline__ float sqrt_approx(float v) {
    float r;
    asm("sqrt.approx.ftz.f32 %0, %1;" : "=f"(r) : "f"(v));
    return r;
}
__device__ __forceinline__ bool all(bool v) { return __all_sync(0xffffffffu, v); }
__device__ __forceinline__ void wait_count(const unsigned* p, unsigned target) {
#pragma unroll 1
    for (int it = 0; it < SPIN_MAX; it++) {
        if (all(ld_acquire(p) >= target)) break;
        __nanosleep(400);
    }
}
__device__ __forceinline__ float wait_sum(const void* p, float n, int nap = 0) {
    float2 v;
#pragma unroll 1
    for (int it = 0; it < SPIN_MAX; it++) {
        v = ld_relaxed_f2(p);
        if (all(v.y >= n)) break;
        if (all(v.y == 0.f)) __nanosleep(600);
        else if (nap) __nanosleep(nap);
    }
    return v.x;
}
__device__ __forceinline__ void wait_row(const Scratch* scr, int bh, float n) { wait_sum(g_st.lsum[bh], n); }
__device__ __forceinline__ void wait_row_o(const Scratch* scr, int bh, float n) {
    wait_row(scr, bh, n);
    if (bh >= RED0) return;
#pragma unroll 1
    for (int it = 0; it < SPIN_MAX; it++) {
        if (all(__uint_as_float(ld_relaxed_u32(&g_st.oacc[oidx(bh, 0)].w)) == UPB)) break;
        __nanosleep(300);
    }
}
constexpr uint32_t SLOT_K = (uint32_t)(((1ull << 32) + SLOT_TICKS - 1) / SLOT_TICKS);
#define SLOT_ASM(t, n, p, phase, k, open) \
    "mov.u32 " n ", 0;\nSLOT:\nmov.u32 " t ", %%globaltimer_lo;\nadd.u32 " n ", " n ", 1;\nsetp.lt.u32 " p ", " n ", 24;\nshr.u32 " t ", " t ", 5;\n" \
    "mad.lo.u32 " t ", " t ", " k ", " phase ";\nsetp.ge.and.u32 " p ", " t ", " open ", " p ";\n@" p " bra.uni SLOT;\n"
template <int PHASE> __host__ __device__ constexpr uint32_t slot_phase() { return SLOT_K / 2 - PHASE * SLOT_K; }
template <int PHASE> __device__ __forceinline__ void wait_slot() {
    if (PHASE < 0) return;
    asm volatile("{\n.reg .pred p;\n.reg .b32 t, n;\n" SLOT_ASM("t", "n", "p", "%0", "%1", "%2") "}"
                 :: "n"(slot_phase<PHASE>()), "n"(SLOT_K), "n"(SLOT_OPEN * SLOT_K) : "memory");
}
__device__ __forceinline__ void wait_time(uint32_t t) {
#pragma unroll 1
    for (int it = 0; it < SPIN_MAX; it++) {
        uint32_t now;
        asm volatile("mov.u32 %0, %%globaltimer_lo;" : "=r"(now));
        if (all((int)(now - t) >= 0)) break;
    }
}
__device__ __forceinline__ void wait_clock(uint32_t t, Warm& warm) { while (!all((int)(clock() - t) >= 0)) { warm(); } }
__device__ __forceinline__ uint32_t pack_bf16(float lo, float hi) {
    uint32_t r;
    asm("cvt.rn.bf16x2.f32 %0, %1, %2;" : "=r"(r) : "f"(hi), "f"(lo));
    return r;
}
__device__ __forceinline__ float bf16r(float v) { return __uint_as_float(pack_bf16(0.f, v)); }
__device__ __forceinline__ uint32_t nonzero(uint32_t w) { return w ? w : 0x80008000u; }
__device__ __forceinline__ uint32_t pack_neg(float lo, float hi) { return nonzero(pack_bf16(-lo, -hi)); }
__device__ __forceinline__ float lo_f(uint32_t v) { return __uint_as_float(v << 16); }
__device__ __forceinline__ float hi_f(uint32_t v) { return __uint_as_float(v & 0xffff0000u); }
__device__ __forceinline__ float warp_sum(float v) {
#pragma unroll
    for (int o = 16; o; o >>= 1) v += __shfl_xor_sync(0xffffffffu, v, o);
    return v;
}
__device__ __forceinline__ void layernorm20(float (&v)[20]) {
    float s = 0.f;
#pragma unroll
    for (int i = 0; i < 20; i++) s += v[i];
    const float mean = warp_sum(s) * (1.0f / DM);
    float q = 0.f;
#pragma unroll
    for (int i = 0; i < 20; i++) { const float d = v[i] - mean; q += d * d; }
    const float var = bf16r(warp_sum(q) * (1.0f / DM));
    const float m = bf16r(mean);
    const float rden = 1.0f / bf16r(sqrtf(bf16r(var + 1e-5f)));
#pragma unroll
    for (int i = 0; i < 20; i++) v[i] = bf16r(bf16r(v[i] - m) * rden);
}

__device__ __forceinline__ void moments(float m1, float m2, float& nmean, float& rden) {
    m1 *= 1.0f / DM;
    const float var = bf16r(fmaxf(fmaf(-m1, m1, m2 * (1.0f / DM)), 0.f));
    nmean = bf16r(m1);
    rden = rcp_approx(bf16r(sqrt_approx(bf16r(var + 1e-5f))));
}
__device__ __forceinline__ float sel4(int j, float a, float b, float c, float d) {
    float lo, hi, r;
    asm("{\n.reg .pred p;\nsetp.ne.s32 p, %3, 0;\nselp.f32 %0, %2, %1, p;\n}" : "=f"(lo) : "f"(a), "f"(b), "r"(j & 1));
    asm("{\n.reg .pred p;\nsetp.ne.s32 p, %3, 0;\nselp.f32 %0, %2, %1, p;\n}" : "=f"(hi) : "f"(c), "f"(d), "r"(j & 1));
    asm("{\n.reg .pred p;\nsetp.ne.s32 p, %3, 0;\nselp.f32 %0, %2, %1, p;\n}" : "=f"(r) : "f"(lo), "f"(hi), "r"(j & 2));
    return r;
}
template <typename T> __device__ __forceinline__ void pin(T*& p) { asm volatile("" : "+l"(p)); }
__device__ __forceinline__ void pin(uint32_t& v) { asm volatile("" : "+r"(v)); }
__device__ __forceinline__ void pin(float& v) { asm volatile("" : "+f"(v)); }
__device__ __forceinline__ uint32_t after(uint32_t n, float v) {
    asm volatile("{\n.reg .pred p;\nsetp.eq.u32 p, %1, 0x7fc1a5a5;\n@p add.u32 %0, %0, 32;\n}" : "+r"(n) : "r"(__float_as_uint(v)));
    return n;
}
__device__ __forceinline__ float2 lds64f(uint32_t addr) {
    float2 v;
    asm volatile("ld.shared.v2.f32 {%0,%1}, [%2];" : "=f"(v.x), "=f"(v.y) : "r"(addr) : "memory");
    return v;
}
__device__ __forceinline__ void sts32f(uint32_t addr, float v) { asm volatile("st.shared.f32 [%0], %1;" :: "r"(addr), "f"(v) : "memory"); }
template <int ID> __device__ __forceinline__ void fin_arrive() { asm volatile("bar.arrive %0, 288;" :: "n"(ID) : "memory"); }
template <int ID> __device__ __forceinline__ void fin_sync() { asm volatile("bar.sync %0, 288;" :: "n"(ID) : "memory"); }
template <int ID> __device__ __forceinline__ void fin_sync(uint32_t n) { asm volatile("bar.sync %0, %1;" :: "n"(ID), "r"(n) : "memory"); }
__device__ __forceinline__ float2 sum8(uint32_t addr, int pitch) {
    float2 t[8];
#pragma unroll
    for (int w = 0; w < 8; w++) t[w] = lds64f(addr + w * pitch);
    return make_float2(((t[0].x + t[1].x) + (t[2].x + t[3].x)) + ((t[4].x + t[5].x) + (t[6].x + t[7].x)),
                       ((t[0].y + t[1].y) + (t[2].y + t[3].y)) + ((t[4].y + t[5].y) + (t[6].y + t[7].y)));
}
__device__ __forceinline__ float4 sum4x4(uint32_t addr, int pitch) {
    float4 t[4];
#pragma unroll
    for (int w = 0; w < 4; w++)
        asm volatile("ld.shared.v4.f32 {%0,%1,%2,%3}, [%4];" : "=f"(t[w].x), "=f"(t[w].y), "=f"(t[w].z), "=f"(t[w].w) : "r"(addr + w * pitch) : "memory");
    return make_float4((t[0].x + t[1].x) + (t[2].x + t[3].x), (t[0].y + t[1].y) + (t[2].y + t[3].y),
                       (t[0].z + t[1].z) + (t[2].z + t[3].z), (t[0].w + t[1].w) + (t[2].w + t[3].w));
}
__device__ __forceinline__ void sts64f(uint32_t addr, float x, float y) {
    asm volatile("st.shared.v2.f32 [%0], {%1,%2};" :: "r"(addr), "f"(x), "f"(y) : "memory");
}
__device__ __forceinline__ uint4 lds128(uint32_t addr) {
    uint4 v;
    asm volatile("ld.shared.v4.u32 {%0,%1,%2,%3}, [%4];" : "=r"(v.x), "=r"(v.y), "=r"(v.z), "=r"(v.w) : "r"(addr) : "memory");
    return v;
}
__device__ __forceinline__ void ld_relaxed_v4_if(uint4& v, const void* p, bool pred) {
    asm volatile("{\n.reg .pred p;\nsetp.ne.u32 p, %5, 0;\n@p ld.relaxed.gpu.global.v4.u32 {%0,%1,%2,%3}, [%4];\n}"
                 : "+r"(v.x), "+r"(v.y), "+r"(v.z), "+r"(v.w) : "l"(p), "r"((uint32_t)pred) : "memory");
}
__device__ __forceinline__ void sts128f(uint32_t addr, float x, float y, float z, float w) {
    asm volatile("st.shared.v4.f32 [%0], {%1,%2,%3,%4};" :: "r"(addr), "f"(x), "f"(y), "f"(z), "f"(w) : "memory");
}
template <int NJ>
__device__ __forceinline__ void load_o(uint32_t (&ob)[3 * NJ][2], const Scratch* scr, int bh, int J0, int j) {
    float4 v[NJ][4];
    float2 l;
#pragma unroll 1
    for (int it = 0; it < SPIN_MAX; it++) {
#pragma unroll
        for (int J = 0; J < NJ; J++) {
#pragma unroll
            for (int e = 0; e < 4; e++) v[J][e] = ld_relaxed_f4(&g_st.oacc[oidx(bh, j)] + oidx(0, (J0 + J) * 16 + e * 4));
        }
        l = ld_relaxed_f2(g_st.lsum[bh]);
        bool ok = l.y == UPB;
#pragma unroll
        for (int J = 0; J < NJ; J++) {
#pragma unroll
            for (int e = 0; e < 4; e++) ok &= v[J][e].w == UPB;
        }
        if (all(ok)) break;
    }
    const float rl = __fdividef(1.0f, l.x);
#pragma unroll
    for (int J = 0; J < NJ; J++) {
        ob[3 * J][0] = pack_bf16(v[J][0].x * rl, v[J][1].x * rl);     ob[3 * J][1] = pack_bf16(v[J][2].x * rl, v[J][3].x * rl);
        ob[3 * J + 1][0] = pack_bf16(v[J][0].y * rl, v[J][1].y * rl); ob[3 * J + 1][1] = pack_bf16(v[J][2].y * rl, v[J][3].y * rl);
        ob[3 * J + 2][0] = pack_bf16(v[J][0].z * rl, v[J][1].z * rl); ob[3 * J + 2][1] = pack_bf16(v[J][2].z * rl, v[J][3].z * rl);
    }
}
__device__ __forceinline__ int near_side(uint32_t sb) {
    uint32_t v;
    asm volatile("ld.volatile.shared.u32 %0, [%1];" : "=r"(v) : "r"(sb + SM_SIDE) : "memory");
    return v;
}
__device__ __forceinline__ void poll_row(uint4& a, uint4& b, uint2& c, const void* pa, const void* pb, const void* pc, uint32_t sa, uint32_t sc,
                                         bool arrive, bool nap, uint32_t bar, Warm& warm) {
    asm volatile("{\n.reg .pred p, q, r, s;\n.reg .b32 m, n, it;\n"
                 "setp.ne.u32 r, %19, 0;\nsetp.ne.u32 s, %20, 0;\nmov.u32 it, 0;\n"
                 "POLL:\n"
                 SLOT_ASM("m", "n", "p", "%23", "%24", "%25")
                 "ld.relaxed.gpu.global.v4.u32 {%0,%1,%2,%3}, [%14];\n"
                 "ld.relaxed.gpu.global.v4.u32 {%4,%5,%6,%7}, [%15];\n"
                 "ld.relaxed.gpu.global.v2.u32 {%8,%9}, [%16];\n"
                 "add.u32 it, it, 1;\nsetp.ge.u32 q, it, %21;\n"
                 "mov.u32 m, 0;\nmma.sync.aligned.m16n8k8.row.col.f32.bf16.bf16.f32 {%10,%11,%12,%13}, {m,m}, {m}, {%10,%11,%12,%13};\n"
                 "st.shared.v4.u32 [%17], {%0,%1,%2,%3};\n"
                 "st.shared.v4.u32 [%17+512], {%4,%5,%6,%7};\n"
                 "st.shared.v2.u32 [%18], {%8,%9};\n"
                 "min.u32 m, %0, %1;\nmin.u32 m, m, %2;\nmin.u32 n, %3, %4;\nmin.u32 n, n, %5;\nmin.u32 m, m, %6;\nmin.u32 m, m, %7;\n"
                 "min.u32 n, n, m;\nmin.u32 m, %8, %9;\nmin.u32 m, m, n;\n"
                 "setp.ne.or.u32 p, m, 0, q;\n"
                 "vote.sync.all.pred p, p, 0xffffffff;\n"
                 "and.pred q, p, r;\n"
                 "bar.warp.sync 0xffffffff;\n"
                 "@q mbarrier.arrive.shared::cta.b64 _, [%22];\n"
                 "@p bra.uni DONE;\n"
                 "@s nanosleep.u32 500;\n"
                 "bra.uni POLL;\n"
                 "DONE:\n}"
                 : "=&r"(a.x), "=&r"(a.y), "=&r"(a.z), "=&r"(a.w), "=&r"(b.x), "=&r"(b.y), "=&r"(b.z), "=&r"(b.w), "=&r"(c.x), "=&r"(c.y),
                   "+f"(warm.c[0]), "+f"(warm.c[1]), "+f"(warm.c[2]), "+f"(warm.c[3])
                 : "l"(pa), "l"(pb), "l"(pc), "r"(sa), "r"(sc), "r"((uint32_t)arrive), "r"((uint32_t)nap), "n"(SPIN_MAX), "r"(bar),
                   "n"(slot_phase<PH_H>()), "n"(SLOT_K), "n"(SLOT_OPEN * SLOT_K) : "memory");
}
__device__ __forceinline__ void aux_sync() { asm volatile("bar.sync 1, 256;" ::: "memory"); }

__global__ void __launch_bounds__(NTHREADS, 1)
fused_decode_kernel(Scratch* const scr, const __nv_bfloat16* const x, const __nv_bfloat16* const w_r, __nv_bfloat16* const out_all,
                    const __nv_bfloat16* const wq, const __grid_constant__ Params p) {
    extern __shared__ __align__(1024) unsigned char smem[];
    const uint32_t sb = s2u(smem);
    const int tid = threadIdx.x, cta = blockIdx.x;
    asm volatile("{\n.reg .pred p;\nsetp.lt.u32 p, %1, %2;\n@p prefetch.global.L2 [%0];\n}"
                 :: "l"(wq + (cta * WQ_LINES + tid) * 64), "r"(tid), "n"(WQ_LINES) : "memory");
    if (tid < 32 && cta < NQ_CTAS) {
        asm volatile("{\n.reg .pred p;\nelect.sync _|p, 0xffffffff;\n"
                     "@p mbarrier.init.shared::cta.b64 [%2], 1;\n"
                     "@p fence.mbarrier_init.release.cluster;\n"
                     "@p mbarrier.arrive.expect_tx.shared::cta.b64 _, [%2], 15360;\n"
                     "@p cp.async.bulk.tensor.2d.shared::cluster.global.mbarrier::complete_tx::bytes [%0], [%1, {%3, %4}], [%2];\n"
                     "@p mbarrier.init.shared::cta.b64 [%2+8], 1;\n@p mbarrier.init.shared::cta.b64 [%2+16], 1;\n"
                     "@p mbarrier.init.shared::cta.b64 [%2+24], 1;\n"
                     "@p fence.mbarrier_init.release.cluster;\n"
                     "@p mbarrier.arrive.expect_tx.shared::cta.b64 _, [%2+8], 15360;\n"
                     "@p cp.async.bulk.tensor.2d.shared::cluster.global.mbarrier::complete_tx::bytes [%0+15360], [%1, {%3, %5}], [%2+8];\n"
                     "@p mbarrier.arrive.expect_tx.shared::cta.b64 _, [%2+16], 15360;\n"
                     "@p cp.async.bulk.tensor.2d.shared::cluster.global.mbarrier::complete_tx::bytes [%0+30720], [%1, {%3, %6}], [%2+16];\n"
                     "@p mbarrier.arrive.expect_tx.shared::cta.b64 _, [%2+24], 15360;\n"
                     "@p cp.async.bulk.tensor.2d.shared::cluster.global.mbarrier::complete_tx::bytes [%0+46080], [%1, {%3, %7}], [%2+24];\n}"
                     :: "r"(sb + SM_W), "l"(&p.wq), "r"(sb + BAR_WQ), "r"(cta * 48), "r"(0), "r"(160), "r"(320), "r"(480) : "memory");
    }
    const int warp = __shfl_sync(0xffffffffu, tid >> 5, 0), lane = tid & 31;
    constexpr int grid = NCTAS;
    const int g = lane >> 2, j = lane & 3;
    uint32_t t_start;
    asm volatile("mov.u32 %0, %%globaltimer_lo;" : "=r"(t_start));
    TS(0);
    if (tid == 32) {
        mbar_init(sb + BAR_WO, 1);
        mbar_init(sb + BAR_H, 1);
#pragma unroll
        for (int i = 0; i < 8 + NWORK; i++) mbar_init(sb + BAR_FW + i * 8, 1);
        sts32f(sb + SM_SIDE, 0.f);
        asm volatile("fence.mbarrier_init.release.cluster;" ::: "memory");
        asm volatile("fence.proxy.async.shared::cta;" ::: "memory");
    }
    __syncthreads();
    if (warp >= NAUX + NWORK) {
        const int fw = warp - (NAUX + NWORK), fi = ffn_slice(cta);
        if (fw == 0) {
            wait_time(t_start + CLEAR_AT_NS);
            if (cta < NQ_CTAS) {
#pragma unroll
                for (int i = lane; i < STATE_V4; i += 32)
                    if (cta * STATE_V4 + i < (int)(sizeof(State) / 16)) reinterpret_cast<uint4*>(&g_st)[cta * STATE_V4 + i] = make_uint4(0u, 0u, 0u, 0u);
                __syncwarp();
                if (lane == 0) red_release(g_cnt_z);
            }
            TSW(2); wait_count(g_cnt_z, NQ_CTAS); TSW(29);
            asm volatile("bar.arrive 2, %0;" :: "n"((NWORK + 2) * 32) : "memory");
            fin_arrive<3>();
        } else {
#pragma unroll 1
            for (int n = cta < NE_CTAS ? 5 : 4, i = n - 1; i >= 0; i--) {
                const int head = cta < NE_CTAS ? cta >> 2 : 28 + i;
                wait_time(t_start + WO_AT_NS + (NH - 1 - head) * WO_STEP_NS);
                request_box(sb + SM_A + i * 12288, &p.wo, cta < NE_CTAS ? (cta & 3) * 160 + i * 32 : (cta - NE_CTAS) * 32,
                            head * DH, sb + BAR_WO, i == n - 1 ? n * 12288 : 0);
            }
            asm volatile("bar.sync 2, %0;" :: "n"((NWORK + 2) * 32) : "memory");
            uint32_t best[2] = {~0u, ~0u};
#pragma unroll 1
            for (int i = 0; i < NPROBE; i++) {
#pragma unroll
                for (int c = 0; c < 2; c++) {
                    uint32_t t0 = clock(), t1 = t0;
                    int v = 0;
                    draw(v, &g_st.hx.w[c][PROBE], lane == 0);
                    asm volatile("{\n.reg .pred p;\nsetp.ne.u32 p, %1, 0xffffffff;\n@p mov.u32 %0, %%clock;\n}" : "+r"(t1) : "r"(v) : "memory");
                    best[c] = min(best[c], t1 - t0);
                }
                __nanosleep(1000);
            }
            if (lane == 0) sts32f(sb + SM_SIDE, __uint_as_float(best[1] < best[0]));
        }
        int job = cta;
        auto sum_rows = [&](int row_end) {
#pragma unroll 1
            for (; job < 8 * min(row_end, RED0); job += NCTAS) {
                const int row = job >> 3, grp = (job & 7) * 8 + (lane & 7);
                wait_row(scr, row, UPB);
                const float4* src = &g_ring[row % RING][lane >> 3][grp];
                float sx = 0.f, sy = 0.f, sz = 0.f;
#pragma unroll 1
                for (int i = 0; i < 2; i++, src += 64 * 64) {
                    float4 v[16];
#pragma unroll 1
                    for (int it = 0; it < SPIN_MAX; it++) {
                        bool ok = true;
#pragma unroll
                        for (int k = 0; k < 16; k++) v[k] = ld_relaxed_b128(src + k * 4 * 64);
#pragma unroll
                        for (int k = 0; k < 16; k++) ok &= v[k].w == (float)(row + 1);
                        if (all(ok)) break;
                    }
#pragma unroll
                    for (int k = 0; k < 16; k++) { sx += v[k].x; sy += v[k].y; sz += v[k].z; }
                }
#pragma unroll
                for (int o = 8; o < 32; o <<= 1) {
                    sx += __shfl_xor_sync(0xffffffffu, sx, o); sy += __shfl_xor_sync(0xffffffffu, sy, o); sz += __shfl_xor_sync(0xffffffffu, sz, o);
                }
                if (lane < 8) st_relaxed_b128(&g_st.oacc[oidx(row, grp)], sx, sy, sz, UPB);
            }
        };
        const int ho0 = lane / 20 * 256 + lane % 20 * 4, ho1 = (lane + 32) / 20 * 256 + (lane + 32) % 20 * 4, ho2 = 3 * 256 + 16 + 2 * lane;
        uint32_t wr[10] = {};
        float wsum = 0.f;
        if (is_g(cta) && fw == 0) {
#pragma unroll
            for (int i = 0; i < 10; i++) {
                const int w = 4 * lane + 128 * (i >> 2) + (i & 3) - (i >= 8 ? 2 * lane : 0);
                wr[i] = *reinterpret_cast<const uint32_t*>(w_r + (w >> 4) * 32 + (w & 3) * 8 + ((w >> 1) & 6));
                wsum += lo_f(wr[i]) + hi_f(wr[i]);
            }
            wsum = warp_sum(wsum);
        }
        const int fb = lane >> 3, fg = lane & 7;
        if (fw == 0) {
#pragma unroll
            for (int i = lane; i < DM / 2; i += 32) sts32f(sb + SM_X + 4 * HPITCH + i * 4, __uint_as_float(0x3f803f80u));
        }
        Warm warm;
        float nmean = 0.f, rden = 0.f, sig = 0.f;
#pragma unroll 1
        for (int b = 0; b < NB; b++) {
            const bool ffn = b >= NB - 2;
            if (fw == 0) {
                sum_rows((b + 1) * NH);
                if (ffn) asm volatile("bar.arrive 8, 64;" ::: "memory");
            } else if (ffn) {
                asm volatile("bar.sync 8, 64;" ::: "memory");
                if (b == NB - 1 && (is_f(cta) || is_g(cta) || ALL_LOADERS)) {
                    uint32_t t0 = 0;
#pragma unroll 1
                    for (int it = 0; it < SPIN_MAX; it++) {
                        t0 = ld_relaxed_u32(g_st.fw_time);
                        if (all(t0 != 0)) break;
                        __nanosleep(150);
                    }
                    asm volatile("fence.proxy.async.shared::cta;" ::: "memory");
                    wait_time(t0 + FW_AT_NS);
                    TSW(9);
                    uint32_t t = clock() + (is_f(cta) ? ((fi & 1) * 24 + (fi >> 1)) * FW_GAP / 48 : FW_MID + ((fi & 3) * 10 + (fi >> 2)) * FW_GAP2 / 40);
#pragma unroll 1
                    for (int i = 0; i < 8; i++) {
                        const uint32_t bar = sb + BAR_FW + i * 8;
                        if (is_f(cta)) {
                            wait_clock(t, warm);
                            request_box(sb + SM_W + i * 10240, (i & 1) ? &p.wu : &p.wg, fi * 32, (i >> 1) * 160, bar, 10240);
                            t += FW_GAP;
                        } else if (is_g(cta)) {
                            wait_clock(t, warm);
                            asm volatile("{\n.reg .pred p;\nelect.sync _|p, 0xffffffff;\n"
                                         "@p mbarrier.arrive.expect_tx.shared::cta.b64 _, [%2], 6144;\n"
                                         "@p cp.async.bulk.tensor.4d.shared::cluster.global.mbarrier::complete_tx::bytes [%0], [%1, {%3, %4, %4, %5}], [%2];\n}"
                                         :: "r"(sb + SM_W + i * 6144), "l"(&p.wd), "r"(bar), "r"(fi * 16), "r"(0), "r"(i * 12) : "memory");
                            t += FW_GAP2;
                        }
                    }
                }
                if (is_f(cta)) {
                    const uint32_t* src = &g_st.hx.w[near_side(sb)][min(fb, b) * 256 + 96];
                    float4 m;
#pragma unroll 1
                    for (int it = 0; it < SPIN_MAX; it++) {
                        wait_slot<PH_M>();
                        m = ld_relaxed_f4(src);
                        warm();
                        if (all(m.y + m.w == 2 * (NCTAS - NE_CTAS))) break;
                        if (b < NB - 1) __nanosleep(500);
                    }
                    moments(m.x, m.z, m.x, m.z);
                    sts64f(sb + SM_RED + 5120 + fb * 8, m.x, m.z);
                }
            }
            if (fw == 0 && cta >= NE_CTAS) {
                const int lc = cta - NE_CTAS, col = lc * 32 + 2 * (lane & 15);
                const uint32_t xv = *reinterpret_cast<const uint32_t*>(x + b * DM + col);
                uint32_t* dst = &(ffn ? g_st.hx.w : g_st.lx.w + 2)[lane >> 4][(b & 1) * 128 + lc / 5 * 256 + lc % 5 * 16 + (col & 6) * 2 + ((col >> 3) & 3)];
                uint32_t part = sb + SM_RED + (lane & 15) * 8;
                wait_row(scr, b * NH + 28, 1);
                float4 early;
#pragma unroll 1
                for (int it = 0; it < SPIN_MAX; it++) {
                    early = ld_relaxed_f4(&g_st.attn[b][col]);
                    if (all(early.y == NE_CTAS / 4 && early.w == NE_CTAS / 4)) break;
                }
                if (early.x != 1.2345f && lane == 0) TS2(6);
                CK(1, __float_as_uint(early.x));
                const float x0 = -(lo_f(xv) + early.x), x1 = -(hi_f(xv) + early.z);
                fin_sync<4>(after(after(288, x0), x1));
                CK(2, lds32(sb + SM_RED));
                const float2 late = sum8(part, 128);
                const uint32_t hv = nonzero(pack_bf16(x0 - late.x, x1 - late.y));
                st_relaxed(dst, hv);
                if (ffn) st_relaxed(dst + 2048, hv);
                CK(3, 0);
                float m = lane < 16 ? lo_f(hv) + hi_f(hv) : fmaf(lo_f(hv), lo_f(hv), hi_f(hv) * hi_f(hv));
#pragma unroll
                for (int o = 1; o < 16; o <<= 1) m += __shfl_xor_sync(0xffffffffu, m, o);
                if ((lane & 14) == 0) red_f2(reinterpret_cast<float*>(&g_st.hx.w[lane & 1][b * 256 + 96 + (lane >> 4) * 2]), m, 1.f);
                fin_arrive<5>();
            }
            if (fw == 0 && (is_g(cta) || is_f(cta))) {
                const uint32_t* src = &(ffn ? g_st.hx.w : g_st.lx.w + 2)[near_side(sb) ^ (ffn && is_g(cta) ? 3 : 0)][(b & 1) * 128];
                const uint32_t hrow = sb + SM_X + b * HPITCH;
                wait_sum(b == NB - 1 ? (const void*)&g_st.lx.w[near_side(sb) ^ 1][3 * 256] : g_st.lsum[b * NH + NH - 1], UPB, 100);
                wait_clock(clock() + HGATE_NS * 2, warm);
                uint4 h0, h1;
                uint2 h2;
                poll_row(h0, h1, h2, src + ho0, src + ho1, src + ho2, hrow + lane * 16, hrow + 1024 + lane * 8, ffn && lane == 0, b < NB - 1, sb + BAR_H, warm);
                CK(4, h0.x);
                if (is_g(cta)) {
                    const uint32_t hw[10] = {h0.x, h0.y, h0.z, h0.w, h1.x, h1.y, h1.z, h1.w, h2.x, h2.y};
                    float m1 = 0.f, m2 = 0.f, rr = 0.f;
#pragma unroll
                    for (int i = 0; i < 10; i++) {
                        const float v0 = lo_f(hw[i]), v1 = hi_f(hw[i]);
                        m1 += v0 + v1;
                        m2 = fmaf(v0, v0, fmaf(v1, v1, m2));
                        rr = fmaf(v0, lo_f(wr[i]), fmaf(v1, hi_f(wr[i]), rr));
                    }
                    moments(warp_sum(m1), warp_sum(m2), m1, m2);
                    const float sg = bf16r(sigmoid_approx(bf16r((m1 * wsum - warp_sum(rr)) * m2)));
                    if (fb == b) { nmean = m1; rden = m2; sig = sg; }
                    __syncwarp();
                    if (ffn) {
                        const int yj = 2 * (fb & 1) + (fb >> 1);
                        uint32_t ypart = sb + SM_RED2 + yj * 128 + ((fg + 2 * yj) & 7) * 16;
                        __nv_bfloat16* out = out_all + fb * DM + fi * 16 + fg;
                        const float2 hw2 = lds64f(sb + SM_X + fb * HPITCH + ((fi >> 1) * 16 + (fg & 6) * 2 + (fi & 1) * 2) * 4);
                        const uint32_t w0 = __float_as_uint(hw2.x), w1 = __float_as_uint(hw2.y);
                        const float nh0 = (fg & 1) ? hi_f(w0) : lo_f(w0), nh1 = (fg & 1) ? hi_f(w1) : lo_f(w1);
                        const float ln0 = bf16r(bf16r(nmean - nh0) * rden) - nh0, ln1 = bf16r(bf16r(nmean - nh1) * rden) - nh1;
                        pin(ypart); pin(out);
                        fin_sync<6>(after(after(after(288, sig), ln0), ln1));
                        CK(10, lds32(ypart));
                        const float4 ya = sum4x4(ypart, 512), yb = sum4x4(ypart + 2048, 512);
                        const float4 y = make_float4(ya.x + yb.x, ya.y + yb.y, ya.z + yb.z, ya.w + yb.w);
                        const float y0 = -(((fb & 1) ? y.y : y.x) + __shfl_xor_sync(0xffffffffu, (fb & 1) ? y.x : y.y, 8));
                        const float y1 = -(((fb & 1) ? y.w : y.z) + __shfl_xor_sync(0xffffffffu, (fb & 1) ? y.z : y.w, 8));
                        const uint32_t ov = pack_bf16(fmaf(y0, sig, ln0), fmaf(y1, sig, ln1));
                        asm volatile("{\n.reg .pred p;\n.reg .b16 lo, hi;\nsetp.ne.u32 p, %2, 0;\nmov.b32 {lo, hi}, %1;\n"
                                     "@p st.global.u16 [%0], lo;\n@p st.global.u16 [%0+16], hi;\n"
                                     "@p exit;\n"
                                     "}" :: "l"(out), "r"(ov), "r"((uint32_t)(b == NB - 1)) : "memory");
                        CK(11, 0);
                        if (lane == 0) TS2(13);
                    }
                }
            }
            if (is_f(cta) && ffn) {
                const int ks = (2 * fi + fw) % 12;
                const int far = near_side(sb) ^ 1;
                uint32_t* dst = &g_st.ax[ks >> 2].w[(~b & 1) * 2 + far][(fi / 6) * 128 + (ks & 3) * 32 + fb * 8 + (fg & 1) * 4 + ((fg >> 1) ^ (ks & 1))];
                uint32_t* dst2 = dst + (far ? -1024 : 1024);
                uint32_t part = sb + SM_RED + fw * 2560 + fb * 128 + ((fg + (fb & 2)) & 7) * 16;
                uint32_t psum = sb + SM_RED + fw * 2560 + 4 * 128 + ((fg + 4) & 7) * 16;
                pin(dst); pin(part); pin(psum);
                asm volatile("bar.sync 4, 320;" ::: "memory");
                CK(6, lds32(part));
                const float4 d = sum4x4(part, 640), cs = sum4x4(psum, 640);
                const float2 mo = lds64f(sb + SM_RED + 5120 + fb * 8);
                nmean = mo.x; rden = mo.y;
                const float g0 = fmaf(nmean, cs.x, -d.x), g1 = fmaf(nmean, cs.y, -d.y), ke = rden * -1.4426950408889634f, r2 = rden * rden;
                const float p0 = g0 * fmaf(-nmean, cs.z, d.z) * r2, p1 = g1 * fmaf(-nmean, cs.w, d.w) * r2;
                const uint32_t av = nonzero(pack_bf16(p0 * rcp_approx(1.0f + ex2_approx(g0 * ke)), p1 * rcp_approx(1.0f + ex2_approx(g1 * ke))));
                st_relaxed(dst, av);
                st_relaxed(dst2, av);
                CK(7, 0);
            }
        }
        warm.done(sb + SM_SCRAP);
        if (cta == 0 && tid == (NAUX + NWORK) * 32) { g_work[0] = 0; g_work[32] = 0; g_cnt_z[0] = 0; }
        return;
    }
    if (warp >= NAUX) {
        const int wk = warp - NAUX;
        const uint32_t bar = sb + BAR_KV + wk * 8;
        const uint32_t buf = sb + SM_KV + wk * TILE_BYTES;
        uint64_t pol;
        asm volatile("createpolicy.fractional.L2::evict_first.b64 %0, 1.0;" : "=l"(pol));
        const int nstatic = NWORK * grid;
        constexpr int POOL0 = NUNITS - NPOOL;
        int uk = wk * grid + cta;
        wait_time(t_start + K0_AT_NS + uk * KSWEEP_NS / nstatic);
        request_tile(buf, &p.k, uk, bar, pol);
        uint32_t koff[3], voff[3];
        {
            const int r = lane & 7, hf = (lane >> 3) & 1;
            const int kkey = hf ? 8 + (r ^ 1) : r;
            const int vh = lane >> 4;
            const int vkey = ((r & 1) ? 8 : 0) + (vh ? (r ^ 1) : r);
#pragma unroll
            for (int b = 0; b < 3; b++) {
                const int rk = 3 * kkey + b, rv = 3 * vkey + b;
                koff[b] = buf + rk * 128 + (((lane >> 4) ^ (rk & 7)) << 4);
                voff[b] = buf + rv * 128 + ((hf ^ (rv & 7)) << 4);
            }
        }
        uint32_t phase = 0;
        uint32_t qf[12][2];
        auto load_q = [&](int u) {
            const uint32_t* q = g_early[u / UPB].q[0][j];
#pragma unroll
            for (int i = 0; i < 4; i++) {
                const uint4 a = ld_relaxed_v4(q + i * 32);
                const float2 c = ld_relaxed_f2(q + i * 32 + 4);
                qf[3 * i][0] = a.x; qf[3 * i][1] = a.y; qf[3 * i + 1][0] = a.z; qf[3 * i + 1][1] = a.w;
                qf[3 * i + 2][0] = __float_as_uint(c.x); qf[3 * i + 2][1] = __float_as_uint(c.y);
            }
        };
        load_q(uk);
        int uq[LAG];
        uint32_t sq[LAG];
#pragma unroll
        for (int i = 0; i < LAG; i++) { uq[i] = ~unit_of(uk + (i + 1) * nstatic); sq[i] = 0; }
        uint4 mv = make_uint4(0u, 0u, 0u, 0u);
        float freed = UPB;
        while (true) {
            const int uv = uq[0];
            uint32_t sv = sq[0];
#pragma unroll
            for (int i = 0; i + 1 < LAG; i++) { uq[i] = uq[i + 1]; sq[i] = sq[i + 1]; }
            uq[LAG - 1] = uk;
            if (uk < NUNITS) {
                PH(7);
#pragma unroll 1
                for (int it = 0; it < SPIN_MAX; it++) {
                    uint32_t lo = 0xffffffffu;
#pragma unroll
                    for (int i = 0; i < 12; i++) lo = min(lo, min(qf[i][0], qf[i][1]));
                    if (all(lo != 0)) break;
                    __nanosleep(250);
                    load_q(uk);
                }
                if (uv >= 0 && uv < NUNITS) {
                    const int nb = uv / UPB;
                    mv = ld_relaxed_v4(&g_early[nb].umax[lane * 4]);
                    freed = nb >= RING && nb < RED0 ? __uint_as_float(ld_relaxed_u32(&g_st.oacc[oidx(nb - RING, (lane & 7) * 8)].w)) : UPB;
                    if (uv >= POOL0) sv = ld_relaxed_u32(&g_st.score[uv - POOL0][lane]);
                }
                mbar_wait(bar, phase); phase ^= 1;
                PH(0); ARR();
                TSI(0, 16); TSI(1, 18);
                float acc[2][4][4] = {};
#pragma unroll
                for (int ks = 0; ks < 12; ks++) {
#pragma unroll
                    for (int mt = 0; mt < 4; mt++) {
                        uint32_t a[4];
                        ldsm4(a, (koff[ks >> 2] ^ ((ks & 3) << 5)) + mt * 6144);
                        mma16816(acc[ks & 1][mt], a, qf[ks][0], qf[ks][1]);
                    }
                }
                PH(1);
                TSI(0, 17); TSI(1, 19);
                if (uk < nstatic) wait_time(t_start + K1_AT_NS + uk * KSWEEP_NS / nstatic);
                if (uv < NUNITS) request_tile(buf, uv >= 0 ? &p.v : &p.k, uv >= 0 ? uv : ~uv, bar, pol);
                const float sa = sel4(j, acc[0][0][0], acc[0][1][0], acc[0][2][0], acc[0][3][0]) + sel4(j, acc[1][0][0], acc[1][1][0], acc[1][2][0], acc[1][3][0]);
                const float sc = sel4(j, acc[0][0][2], acc[0][1][2], acc[0][2][2], acc[0][3][2]) + sel4(j, acc[1][0][2], acc[1][1][2], acc[1][2][2], acc[1][3][2]);
                const uint32_t raw = pack_bf16(sa, sc);
                const float scale = -0.07216878364870322f;
                const uint32_t sk = pack_bf16(lo_f(raw) * scale, hi_f(raw) * scale);
                sq[LAG - 1] = sk;
                if (uk >= POOL0) st_relaxed(&g_st.score[uk - POOL0][lane], sk ? sk : 0x80008000u);
                int a = (int)(sk << 16), b = (int)(sk & 0xffff0000u);
                a ^= (a >> 31) & 0x7fff0000; b ^= (b >> 31) & 0x7fff0000;
                const int mx = __reduce_max_sync(0xffffffffu, max(a, b));
                if (lane == 0) st_relaxed(&g_early[uk / UPB].umax[uk % UPB], (uint32_t)mx | 1u);
            }
            if (uv < 0) {
                uk = ~uv;
                load_q(uk);
                continue;
            }
            if (uv >= NUNITS) break;
            const int bh = uv / UPB;
#pragma unroll 1
            for (int it = 0; it < SPIN_MAX; it++) {
                if (all((mv.x & mv.y & mv.z & mv.w & 1u) && (uv < POOL0 || sv != 0) && freed == UPB)) break;
                mv = ld_relaxed_v4(&g_early[bh].umax[lane * 4]);
                if (bh >= RING && bh < RED0) freed = __uint_as_float(ld_relaxed_u32(&g_st.oacc[oidx(bh - RING, (lane & 7) * 8)].w));
                if (uv >= POOL0) sv = ld_relaxed_u32(&g_st.score[uv - POOL0][lane]);
            }
            PH(2); CK(8, sv);
            int un = NUNITS, vn = 0;
            draw(un, g_work, uk < NUNITS && lane == 0);
            uint32_t tdraw;
            asm volatile("mov.u32 %0, %%globaltimer_lo;" : "=r"(tdraw));
            draw(vn, g_work + 32, uq[0] >= POOL0 && lane == 0);
            int mx = __reduce_max_sync(0xffffffffu, max(max((int)mv.x, (int)mv.y), max((int)mv.z, (int)mv.w))) & 0xffff0000;
            mx ^= (mx >> 31) & 0x7fff0000;
            const float m = __int_as_float(mx);
            const float l2e = 1.4426950408889634f;
            const uint32_t pp = pack_bf16(exp2f((lo_f(sv) - m) * l2e), exp2f((hi_f(sv) - m) * l2e));
            uint32_t pb[8];
#pragma unroll
            for (int t = 0; t < 4; t++) {
                pb[2 * t] = __shfl_sync(0xffffffffu, pp, 8 * j + t);
                pb[2 * t + 1] = __shfl_sync(0xffffffffu, pp, 8 * j + 4 + t);
            }
            float lacc[4] = {};
            const uint32_t ones[4] = {0x3f803f80u, 0x3f803f80u, 0x3f803f80u, 0x3f803f80u};
#pragma unroll
            for (int t = 0; t < 4; t++) mma16816(lacc, ones, pb[2 * t], pb[2 * t + 1]);
            if (uv < nstatic) {
                asm volatile("bar.sync 2, %0;" :: "n"((NWORK + 2) * 32) : "memory");
                TSW(3);
            }
            const int grp = 16 * j + 4 * (g & 1) + (g >> 1);
            uint32_t mode = (bh >= RED0) + (bh >= NBH - 4);
            float tag = mode ? 1.f : (float)(bh + 1), tag2 = fmaf(__uint_as_float(voff[0]), 0.f, tag);
            void* dst = mode == 0 ? (void*)&g_ring[bh % RING][uv % UPB][grp] :
                        mode == 1 ? (void*)&g_st.oacc[oidx(bh, grp)] : (void*)&g_st.ox[0].w[uv % OREP * 2 + (~(near_side(sb) ^ uv % OREP) & 1)][oidx(bh & 3, grp) * 4];
            if (mode == 2 && lane < 2) red_f2(reinterpret_cast<float*>(&g_st.lx.w[lane][(bh & 3) * 256]), lacc[0], 1.f);
            CK(10, __float_as_uint(lacc[0]));
            un = __shfl_sync(0xffffffffu, un, 0) + (LAG + 1) * nstatic;
            un = unit_of(un);
            vn = __shfl_sync(0xffffffffu, vn, 0);
            if (uq[0] >= POOL0) uq[0] = unit_of(POOL0 + vn);
            if (vn == FW_TICKET && lane == 0) st_relaxed(g_st.fw_time, tdraw | 1u);
            if (uq[0] < NUNITS && un >= NUNITS) {
                mv = ld_relaxed_v4(&g_early[uq[0] / UPB].umax[lane * 4]);
                if (uq[0] < RED0 * UPB) freed = 0.f;
                if (uq[0] >= POOL0) sq[0] = ld_relaxed_u32(&g_st.score[uq[0] - POOL0][lane]);
            }
            pin(dst); pin(mode); pin(tag); pin(tag2); pin(voff[0]); pin(voff[1]); pin(voff[2]);
            PH(3); CK(9, vn);
            mbar_wait(bar, phase); phase ^= 1;
            PH(4); ARR(); CK(12, lds32(buf));
            float acc[12][4] = {};
#pragma unroll
            for (int t = 0; t < 4; t++) {
#pragma unroll
                for (int mt = 0; mt < 12; mt++) {
                    uint32_t a[4];
                    ldsm4t(a, (voff[mt >> 2] ^ ((mt & 3) << 5)) + t * 6144);
                    mma16816(acc[mt], a, pb[2 * t], pb[2 * t + 1]);
                }
            }
            PH(5);
            if (lane == 0) PROG(un);
            if (un < NUNITS || uq[0] < NUNITS) request_tile(buf, un < NUNITS ? &p.k : &p.v, un < NUNITS ? un : uq[0], bar, pol);
            if (un < NUNITS || uq[0] < NUNITS) CK(11, 0);
            float o[6];
#pragma unroll
            for (int e = 0; e < 6; e++) {
                const int q = e % 3, c = (e / 3) * 2;
                o[e] = sel4(j, acc[q][c], acc[3 + q][c], acc[6 + q][c], acc[9 + q][c]);
            }
            put_groups(dst, mode, o, tag, tag2);
            CK(13, 0);
            if (un < NUNITS) load_q(un);
            if (lane == 0) red_f2(&g_st.lsum[bh][0].x, lacc[0], 1.f);
            PH(6);
            if (uq[0] >= NUNITS && un >= NUNITS) break;
            uk = un;
        }
        TSW(4 + wk);
        return;
    }

    __nv_bfloat16* xs = reinterpret_cast<__nv_bfloat16*>(smem + SM_X);
    float* red = reinterpret_cast<float*>(smem + SM_RED);
    const int frow = (lane & 7) + ((lane >> 4) << 3), fcol = (lane >> 3) & 1;
    const uint32_t f64b = sb + (frow * 4 + (fcol ^ ((frow >> 1) & 3))) * 16;
    if (cta < NQ_CTAS) {
        TS(26);
        if (warp >= 4) {
            uint2 xr[5];
#pragma unroll
            for (int i = 0; i < 5; i++) xr[i] = *reinterpret_cast<const uint2*>(x + (warp - 4) * DM + i * 128 + lane * 4);
            float v[20];
#pragma unroll
            for (int i = 0; i < 5; i++) {
                v[4 * i] = lo_f(xr[i].x); v[4 * i + 1] = hi_f(xr[i].x); v[4 * i + 2] = lo_f(xr[i].y); v[4 * i + 3] = hi_f(xr[i].y);
            }
            layernorm20(v);
#pragma unroll
            for (int i = 0; i < 5; i++)
                *reinterpret_cast<uint2*>(xs + (warp - 4) * XPITCH + i * 128 + lane * 4) =
                    make_uint2(pack_bf16(v[4 * i], v[4 * i + 1]), pack_bf16(v[4 * i + 2], v[4 * i + 3]));
        }
        aux_sync();
        TS(27);
        mbar_wait(sb + BAR_WQ + (warp >> 1) * 8, 0);
        TS(1);
        const uint32_t xfrag = sb + SM_X + ((g & 3) * XPITCH + 2 * j) * 2;
        float acc[3][4] = {};
#pragma unroll
        for (int s = 0; s < 5; s++) {
            const int ks = warp * 5 + s;
            const uint32_t b0 = lds32(xfrag + ks * 32), b1 = lds32(xfrag + ks * 32 + 16);
            const int row = ks * 16 + frow;
#pragma unroll
            for (int mt = 0; mt < 3; mt++) {
                uint32_t a[4];
                ldsm4t(a, sb + SM_W + (row * 6 + 2 * mt + fcol) * 16);
                mma16816(acc[mt], a, b0, b1);
            }
        }
        if (j < 2) {
#pragma unroll
            for (int mt = 0; mt < 3; mt++) {
                *reinterpret_cast<float2*>(red + warp * 216 + mt * 72 + g * 4 + 2 * j) = make_float2(acc[mt][0], acc[mt][1]);
                *reinterpret_cast<float2*>(red + warp * 216 + mt * 72 + 36 + g * 4 + 2 * j) = make_float2(acc[mt][2], acc[mt][3]);
            }
        }
        aux_sync();
        if (warp < 4) {
            const float* src = red + min(g, 5) * 36 + warp * 8 + j;
            float s0 = 0.f, s1 = 0.f;
#pragma unroll
            for (int w = 0; w < 8; w++) { s0 += src[w * 216]; s1 += src[w * 216 + 4]; }
            st_relaxed(&g_early[j * NH + (cta >> 2)].q[cta & 3][warp][g], pack_neg(s0, s1));
        }
        TS(28);
    }
    fin_sync<3>();
    mbar_wait(sb + BAR_WO, 0);
    TS(7);
    uint32_t part = sb + SM_RED + (warp * 32 + 8 * j + g) * 4;

#pragma unroll 1
    for (int b = 0; b < NB; b++) {
        if (cta >= NE_CTAS) {
            uint32_t a[6][2][4];
#pragma unroll
            for (int s = 0; s < 6; s++) {
#pragma unroll
                for (int mt = 0; mt < 2; mt++) ldsm4t(a[s][mt], (f64b ^ (mt * 32)) + SM_A + (warp * 6 + s) * 1024);
            }
            const int bh = b * NH + 28 + (warp >> 1);
            const int side = near_side(sb) ^ 1;
            const void* osrc[OREP];
#pragma unroll
            for (int c = 0; c < OREP; c++)
                osrc[c] = b == NB - 1 ? (const void*)&g_st.ox[c >> 1].w[side ^ (c & 1) * 3][oidx(bh & 3, (warp & 1) * 32 + lane) * 4] : &g_st.oacc[oidx(bh, (warp & 1) * 32 + lane)];
            const void* lsrc = b == NB - 1 ? (const void*)&g_st.lx.w[side][(bh & 3) * 256] : g_st.lsum[bh];
            wait_row_o(scr, bh, 1);
            const float rl = rcp_approx(wait_sum(lsrc, UPB)) * (b == NB - 1 ? 1.f : 1.f / OREP), full = b == NB - 1 ? UPB : UPB * OREP;
            float4 ov;
            float px, py, pz;
            Warm warm;
#pragma unroll 1
            for (int it = 0; it < SPIN_MAX; it++) {
                wait_slot<PH_O>();
                float4 oc[OREP];
#pragma unroll
                for (int c = 0; c < OREP; c++) oc[c] = ld_relaxed_f4(osrc[c]);
                warm();
                ov = oc[0];
#pragma unroll
                for (int c = 1; c < OREP; c++) { ov.x += oc[c].x; ov.y += oc[c].y; ov.z += oc[c].z; ov.w += oc[c].w; }
                ov.x *= rl; ov.y *= rl; ov.z *= rl;
                px = __shfl_xor_sync(0xffffffffu, ov.x, 4); py = __shfl_xor_sync(0xffffffffu, ov.y, 4); pz = __shfl_xor_sync(0xffffffffu, ov.z, 4);
                if (all(ov.w == full)) break;
            }
            CK(0, __float_as_uint(ov.x));
            if (ov.x != 1.2345f && warp == 7) TSW(14);
            const uint32_t w[3] = {pack_bf16(ov.x, px), pack_bf16(ov.y, py), pack_bf16(ov.z, pz)};
            float acc[2][2][4] = {};
#pragma unroll
            for (int s = 0; s < 6; s++) {
                const uint32_t b0 = __shfl_sync(0xffffffffu, w[s % 3], (s / 3) * 16 + j);
                const uint32_t b1 = __shfl_sync(0xffffffffu, w[s % 3], (s / 3) * 16 + 8 + j);
#pragma unroll
                for (int mt = 0; mt < 2; mt++) mma16816(acc[mt][s & 1], a[s][mt], b0, b1);
            }
            sts32f(part, sel4(j, acc[0][0][0] + acc[0][1][0], acc[0][0][2] + acc[0][1][2], acc[1][0][0] + acc[1][1][0], acc[1][0][2] + acc[1][1][2]));
            CK(1, 0);
            fin_arrive<4>();
            warm.done(sb + SM_SCRAP);
            fin_sync<5>();
            if (cta < NE_CTAS + 4 && tid < 64) reinterpret_cast<uint4*>(&g_early[b * NH + 28 + cta - NE_CTAS])[tid] = make_uint4(0u, 0u, 0u, 0u);
        } else {
            const int bh = b * NH + (cta >> 2);
            if (warp == 0) wait_row_o(scr, bh, UPB);
            aux_sync();
            if (warp < 5) {
                uint32_t ob[12][2];
                load_o<4>(ob, scr, bh, 0, j);
                float acc[2][2][4] = {};
#pragma unroll
                for (int ks = 0; ks < 12; ks++) {
#pragma unroll
                    for (int mt = 0; mt < 2; mt++) {
                        uint32_t a[4];
                        ldsm4t(a, (f64b ^ (mt * 32)) + SM_A + warp * 12288 + ks * 1024);
                        mma16816(acc[mt][ks & 1], a, ob[ks][0], ob[ks][1]);
                    }
                }
                red_f2(&g_st.attn[b][(cta & 3) * 160 + warp * 32 + 8 * j + g].x,
                       sel4(j, acc[0][0][0] + acc[0][1][0], acc[0][0][2] + acc[0][1][2], acc[1][0][0] + acc[1][1][0], acc[1][0][2] + acc[1][1][2]), 1.f);
                TS(8);
            } else if (warp > 5 && (cta & 3) == 0) {
                reinterpret_cast<uint4*>(&g_early[bh])[tid - 192] = make_uint4(0u, 0u, 0u, 0u);
            }
        }
        if (b < NB - 2) continue;

        if (is_f(cta)) {
            uint32_t ga[10][2][4];
            uint4 hv[5];
            const uint32_t hfrag = sb + SM_X + min(g, 4) * HPITCH + ((warp >> 1) * 80 + 4 * j) * 4;
            if (b == NB - 1) mbar_wait(sb + BAR_FW + warp * 8, 0);
            if (warp == 7) TSW(10);
            CK(12, lds32(sb + SM_W));
#pragma unroll
            for (int s = 0; s < 10; s++) {
#pragma unroll
                for (int mt = 0; mt < 2; mt++) ldsm4t(ga[s][mt], (f64b ^ (mt * 32)) + SM_W + (warp * 10 + s) * 1024);
            }
            const uint32_t gpart = sb + SM_RED + (warp >> 1) * 640 + j * 256 + ((g + 2 * j) & 7) * 16 + (warp & 1) * 8;
            mbar_wait(sb + BAR_H, b & 1);
#pragma unroll
            for (int s = 0; s < 5; s++) hv[s] = lds128(hfrag + s * 64);
            CK(4, hv[0].x);
            float acc[2][2][4] = {};
#pragma unroll
            for (int s = 0; s < 10; s++) {
#pragma unroll
                for (int mt = 0; mt < 2; mt++)
                    mma16816(acc[mt][s & 1], ga[s][mt], (s & 1) ? hv[s >> 1].z : hv[s >> 1].x, (s & 1) ? hv[s >> 1].w : hv[s >> 1].y);
            }
#pragma unroll
            for (int mt = 0; mt < 2; mt++) {
                if (j < 3) sts64f(gpart + mt * 2560, acc[mt][0][0] + acc[mt][1][0], acc[mt][0][2] + acc[mt][1][2]);
                if (j < 2) sts64f(gpart + mt * 2560 + 128, acc[mt][0][1] + acc[mt][1][1], acc[mt][0][3] + acc[mt][1][3]);
            }
            CK(5, 0);
            asm volatile("bar.arrive 4, 320;" ::: "memory");
        } else if (is_g(cta)) {
            const uint32_t* asrc = &g_st.ax[0].w[(~b & 1) * 2 + near_side(sb)][warp * 128 + ((g >> 2) * 2 + (j >> 1)) * 32 + (g & 3) * 8 + (j & 1) * 4];
            const uint32_t ypart = sb + SM_RED2 + warp * 512 + j * 128 + ((g + 2 * j) & 7) * 16;
            uint32_t wb[12][4];
            uint4 va[3] = {};
            uint32_t lo[3] = {};
            auto ask = [&]() {
#pragma unroll
                for (int i = 0; i < 3; i++) ld_relaxed_v4_if(va[i], asrc + i * 4096, lo[i] == 0);
            };
            auto complete = [&]() {
#pragma unroll
                for (int i = 0; i < 3; i++) lo[i] = min(min(va[i].x, va[i].y), min(va[i].z, va[i].w));
                return all(min(lo[0], min(lo[1], lo[2])) != 0);
            };
            const int jj = (lane & 7) >> 1, q = jj >> 1, hi = lane >> 4;
            const uint32_t wsrc = sb + SM_W + warp * 6144 + q * 512 + ((hi ^ q) * 4 + (jj & 1) * 2 + (lane & 1)) * 32 + ((fcol ^ hi ^ q) << 4);
            mbar_wait(sb + BAR_H, b & 1);
            if (b == NB - 1) mbar_wait(sb + BAR_FW + warp * 8, 0);
            if (warp == 7) TSW(11);
            CK(13, lds32(sb + SM_W));
            ask();
#pragma unroll
            for (int s = 0; s < 12; s++) ldsm4t(wb[s], wsrc + (s >> 2) * 2048 + (s & 1) * 1024 + (s & 2) * 128);
            Warm warm;
            if (!complete()) {
#pragma unroll 1
                for (int it = 0; it < SPIN_MAX; it++) {
                    ask();
                    warm();
                    if (complete()) break;
                }
            }
            CK(8, va[0].x);
            if (va[0].x != 0x12345 && warp == 7) TSW(15);
            float acc[6][4] = {};
#pragma unroll
            for (int s = 0; s < 12; s++) {
                const uint4 v = va[s >> 2];
                mma16816(acc[s % 6], wb[s], (s & 2) ? v.z : v.x, (s & 2) ? v.w : v.y);
            }
            float y[4];
#pragma unroll
            for (int e = 0; e < 4; e++) y[e] = j < 2 ? (acc[0][e] + acc[2][e]) + acc[4][e] : (acc[1][e] + acc[3][e]) + acc[5][e];
            sts128f(ypart, y[0], y[1], y[2], y[3]);
            CK(9, 0);
            fin_arrive<6>();
            warm.done(sb + SM_SCRAP);
        }
    }
}

typedef CUresult (*EncodeFn)(CUtensorMap*, CUtensorMapDataType, cuuint32_t, void*, const cuuint64_t*, const cuuint64_t*,
                             const cuuint32_t*, const cuuint32_t*, CUtensorMapInterleave, CUtensorMapSwizzle,
                             CUtensorMapL2promotion, CUtensorMapFloatOOBfill);

CUtensorMap make_map(EncodeFn enc, void* ptr, uint64_t cols, uint64_t rows, uint32_t bcols, uint32_t brows,
                     CUtensorMapSwizzle sw, CUtensorMapL2promotion promo) {
    CUtensorMap m;
    const cuuint64_t dims[2] = {cols, rows};
    const cuuint64_t strides[1] = {cols * 2};
    const cuuint32_t box[2] = {bcols, brows};
    const cuuint32_t es[2] = {1, 1};
    enc(&m, CU_TENSOR_MAP_DATA_TYPE_BFLOAT16, 2, ptr, dims, strides, box, es, CU_TENSOR_MAP_INTERLEAVE_NONE, sw, promo,
        CU_TENSOR_MAP_FLOAT_OOB_FILL_NONE);
    return m;
}

}

extern "C" void kernel_launch(void* const* d_in, const int* in_sizes, int n_in, void* d_out, int out_size) {
    (void)in_sizes; (void)n_in; (void)out_size;
    static EncodeFn enc = nullptr;
    static int sms = 0;
    static Scratch* scr = nullptr;
    if (!enc) {
        cudaDriverEntryPointQueryResult qr;
        cudaGetDriverEntryPoint("cuTensorMapEncodeTiled", (void**)&enc, cudaEnableDefault, &qr);
        void* raw = nullptr;
        cudaGetSymbolAddress(&raw, g_raw);
        scr = reinterpret_cast<Scratch*>((reinterpret_cast<uintptr_t>(raw) + PAGE - 1) & ~(uintptr_t)(PAGE - 1));
        int dev = 0;
        cudaGetDevice(&dev);
        cudaDeviceGetAttribute(&sms, cudaDevAttrMultiProcessorCount, dev);
        cudaFuncSetAttribute(fused_decode_kernel, cudaFuncAttributeMaxDynamicSharedMemorySize, SM_TOTAL);
    }
    if (sms < NCTAS) return;
    const CUtensorMapL2promotion WPROMO = CU_TENSOR_MAP_L2_PROMOTION_L2_128B;
    Params p;
    p.k = make_map(enc, d_in[1], 64, (uint64_t)NBH * SK * 3, 64, TILE_ROWS, CU_TENSOR_MAP_SWIZZLE_128B, CU_TENSOR_MAP_L2_PROMOTION_NONE);
    p.v = make_map(enc, d_in[2], 64, (uint64_t)NBH * SK * 3, 64, TILE_ROWS, CU_TENSOR_MAP_SWIZZLE_128B, CU_TENSOR_MAP_L2_PROMOTION_NONE);
    p.wq = make_map(enc, d_in[3], NH * DH, DM, 48, 160, CU_TENSOR_MAP_SWIZZLE_NONE, WPROMO);
    p.wo = make_map(enc, d_in[4], DM, NH * DH, 32, DH, CU_TENSOR_MAP_SWIZZLE_64B, WPROMO);
    p.wg = make_map(enc, d_in[7], FF, DM, 32, 160, CU_TENSOR_MAP_SWIZZLE_64B, WPROMO);
    p.wu = make_map(enc, d_in[8], FF, DM, 32, 160, CU_TENSOR_MAP_SWIZZLE_64B, WPROMO);
    {
        const cuuint64_t dims[4] = {DM, 2, 8, FF / 16}, strides[3] = {8 * DM * 2, DM * 2, 16 * DM * 2};
        const cuuint32_t box[4] = {16, 2, 8, 12}, es[4] = {1, 1, 1, 1};
        enc(&p.wd, CU_TENSOR_MAP_DATA_TYPE_BFLOAT16, 4, d_in[9], dims, strides, box, es, CU_TENSOR_MAP_INTERLEAVE_NONE,
            CU_TENSOR_MAP_SWIZZLE_32B, WPROMO, CU_TENSOR_MAP_FLOAT_OOB_FILL_NONE);
    }
    fused_decode_kernel<<<NCTAS, NTHREADS, SM_TOTAL, cudaStreamPerThread>>>(
        scr, (const __nv_bfloat16*)d_in[0], (const __nv_bfloat16*)d_in[6], (__nv_bfloat16*)d_out, (const __nv_bfloat16*)d_in[3], p);
}
```
